```python
import torch

def _softmax(x, axis=-1):
    return torch.softmax(x, dim=axis)
def _gelu(x):
    return torch.nn.functional.gelu(x, approximate="tanh")
def _silu(x):
    return torch.nn.functional.silu(x)
def _sigmoid(x):
    return torch.sigmoid(x)
def _layernorm(x, axis=-1, eps=1e-5):
    m = x.mean(dim=axis, keepdim=True)
    v = x.var(dim=axis, keepdim=True, unbiased=False)
    return (x - m) / torch.sqrt(v + eps)
def _scatter_add(tgt, idx, src, axis=0):
    return tgt.clone().index_add_(axis, idx, src)
def _segment_sum(src, seg, n):
    out = torch.zeros((n,) + src.shape[1:], dtype=src.dtype)
    return out.index_add_(0, seg, src)
def _pad(x, pw):
    flat = tuple(v for pair in reversed(pw) for v in pair)
    return torch.nn.functional.pad(x, flat)

kernel_name = 'concat_heads__gqa_block_cached__gqa_block_cached__near_ridge'

def setup_inputs():

    _w = (lambda a: (lambda t: t.to(torch.bfloat16) if t.is_floating_point() else t)(torch.as_tensor(a)))
    def _A_setup():
        B, Sq, D = 8, 64, 576
        Hq, Hkv, Sk, Dh = 32, 16, 512, 128
        assert Hq % Hkv == 0, (Hq, Hkv)
        return {
            "x": _w((lambda *s: torch.randn(*s, dtype=torch.bfloat16) * 0.8)(B, Sq, D)),
            "k_cache": _w((lambda *s: torch.randn(*s, dtype=torch.bfloat16) * 0.8)(B, Hkv, Sk, Dh)),
            "v_cache": _w((lambda *s: torch.randn(*s, dtype=torch.bfloat16) * 0.05)(B, Hkv, Sk, Dh)),
            "wq": _w((lambda *s: torch.randn(*s, dtype=torch.bfloat16) * 0.8)(D, Hq * Dh) * (D ** -0.5)),
            "wo": _w((lambda *s: torch.randn(*s, dtype=torch.bfloat16) * 0.05)(Hq * Dh, D) * ((Hq * Dh) ** -0.5)),
        }
    _A_in = _A_setup()

    def _B_setup():
        B, Sq, D = 8, 64, 576
        Hq, Hkv, Sk, Dh = 32, 16, 512, 128
        assert Hq % Hkv == 0, (Hq, Hkv)
        return {
            "x": _w((lambda *s: torch.randn(*s, dtype=torch.bfloat16) * 0.8)(B, Sq, D)),
            "k_cache": _w((lambda *s: torch.randn(*s, dtype=torch.bfloat16) * 0.8)(B, Hkv, Sk, Dh)),
            "v_cache": _w((lambda *s: torch.randn(*s, dtype=torch.bfloat16) * 0.05)(B, Hkv, Sk, Dh)),
            "wq": _w((lambda *s: torch.randn(*s, dtype=torch.bfloat16) * 0.8)(D, Hq * Dh) * (D ** -0.5)),
            "wo": _w((lambda *s: torch.randn(*s, dtype=torch.bfloat16) * 0.05)(Hq * Dh, D) * ((Hq * Dh) ** -0.5)),
        }
    _B_in = _B_setup()

    return {
        "A_x": _A_in["x"],
        "A_k_cache": _A_in["k_cache"],
        "A_v_cache": _A_in["v_cache"],
        "A_wq": _A_in["wq"],
        "A_wo": _A_in["wo"],
        "B_x": _B_in["x"],
        "B_k_cache": _B_in["k_cache"],
        "B_v_cache": _B_in["v_cache"],
        "B_wq": _B_in["wq"],
        "B_wo": _B_in["wo"],
    }

def reference(A_x, A_k_cache, A_v_cache, A_wq, A_wo, B_x, B_k_cache, B_v_cache, B_wq, B_wo):
    def _A_ref(x, k_cache, v_cache, wq, wo):
        B, Sq, D = x.shape
        Hq, Dh = 32, 128
        Hkv = k_cache.shape[1]
        rep = Hq // Hkv
        q = (lambda x, *d: x.permute(*d))((x @ wq).reshape(B, Sq, Hq, Dh), 0, 2, 1, 3)
        k = (lambda x, n, axis: torch.repeat_interleave(x, n, dim=axis))(k_cache, rep, axis=1)
        v = (lambda x, n, axis: torch.repeat_interleave(x, n, dim=axis))(v_cache, rep, axis=1)
        scores = torch.einsum("bhqd,bhkd->bhqk", q, k) * (Dh ** -0.5)
        p = _softmax(scores, axis=-1)
        o = torch.einsum("bhqk,bhkd->bhqd", p, v)
        return (lambda x, *d: x.permute(*d))(o, 0, 2, 1, 3).reshape(B, Sq, Hq * Dh) @ wo

    def _B_ref(x, k_cache, v_cache, wq, wo):
        B, Sq, D = x.shape
        Hq, Dh = 32, 128
        Hkv = k_cache.shape[1]
        rep = Hq // Hkv
        q = (lambda x, *d: x.permute(*d))((x @ wq).reshape(B, Sq, Hq, Dh), 0, 2, 1, 3)
        k = (lambda x, n, axis: torch.repeat_interleave(x, n, dim=axis))(k_cache, rep, axis=1)
        v = (lambda x, n, axis: torch.repeat_interleave(x, n, dim=axis))(v_cache, rep, axis=1)
        scores = torch.einsum("bhqd,bhkd->bhqk", q, k) * (Dh ** -0.5)
        p = _softmax(scores, axis=-1)
        o = torch.einsum("bhqk,bhkd->bhqd", p, v)
        return (lambda x, *d: x.permute(*d))(o, 0, 2, 1, 3).reshape(B, Sq, Hq * Dh) @ wo

    a = _A_ref(A_x, A_k_cache, A_v_cache, A_wq, A_wo)
    b = _B_ref(B_x, B_k_cache, B_v_cache, B_wq, B_wo)
    return torch.concatenate([a, b], axis=-1)
```

```cpp
#include <cuda_runtime.h>
#include <cuda_bf16.h>
#include <cuda.h>
#include <stdint.h>

namespace {

constexpr int kD = 576, kHQD = 4096, kSK = 512, kDH = 128;

constexpr int N_QW = 9;
constexpr int N_KV = 8;
constexpr int N_WO = 18;
constexpr int N_ITEMS = 2 * (N_QW + N_KV) + N_WO;
constexpr int RING_BYTES = 160 * 1024;
constexpr int QW_BYTES = 40 * 1024;
constexpr int KV_BYTES = 32 * 1024;
constexpr int WO_BYTES = 32 * 1024;
constexpr int OBUF_OFF = RING_BYTES;
constexpr int BAR_OFF = RING_BYTES + 64 * 1024;
constexpr int SMEM_BYTES = BAR_OFF + 2 * N_ITEMS * 8 + 64;

struct Plan {
  int off[N_ITEMS];
  int dep[N_ITEMS];
  int remote[N_ITEMS];
};
constexpr int item_kind(int i) {
  return i >= 34 ? 2 : ((i % 17) < N_QW ? 0 : 1);
}
constexpr int item_bytes(int i) { return item_kind(i) == 0 ? QW_BYTES : (item_kind(i) == 1 ? KV_BYTES : WO_BYTES); }
constexpr Plan make_plan() {
  Plan p{};
  int pos = 0;
  for (int i = 0; i < N_ITEMS; i++) {
    int sz = item_bytes(i);
    if (pos + sz > RING_BYTES) pos = 0;
    p.off[i] = pos;
    pos += sz;
    p.dep[i] = -1;
    p.remote[i] = 0;
    for (int k = 0; k < i; k++) {
      int a0 = p.off[k], a1 = a0 + item_bytes(k);
      if (a0 < p.off[i] + sz && p.off[i] < a1) p.dep[i] = k;
    }
  }
  for (int i = 0; i < N_ITEMS; i++)
    if (item_kind(i) != 1 && p.dep[i] >= 0) p.remote[p.dep[i]] = 1;
  return p;
}
__constant__ Plan c_plan = make_plan();

__device__ uint4 g_part[16 * 8 * 18 * 256];
__device__ unsigned int g_cnt[16 * 4 * 32];

__device__ __forceinline__ uint32_t smem_u32(const void* p) { return (uint32_t)__cvta_generic_to_shared(p); }
__device__ __forceinline__ void mbar_init(uint32_t bar, uint32_t cnt) {
  asm volatile("mbarrier.init.shared::cta.b64 [%0], %1;" ::"r"(bar), "r"(cnt) : "memory");
}
__device__ __forceinline__ void mbar_expect_tx(uint32_t bar, uint32_t bytes) {
  asm volatile("mbarrier.arrive.expect_tx.shared::cta.b64 _, [%0], %1;" ::"r"(bar), "r"(bytes) : "memory");
}
__device__ __forceinline__ void mbar_arrive(uint32_t bar) {
  asm volatile("mbarrier.arrive.shared::cta.b64 _, [%0];" ::"r"(bar) : "memory");
}
__device__ __forceinline__ void mbar_arrive_remote(uint32_t bar, uint32_t cta) {
  asm volatile(
      "{\n.reg .b32 ra;\nmapa.shared::cluster.u32 ra, %0, %1;\n"
      "mbarrier.arrive.shared::cluster.b64 _, [ra];\n}\n" ::"r"(bar), "r"(cta)
      : "memory");
}
__device__ __forceinline__ bool mbar_try(uint32_t bar, uint32_t parity) {
  uint32_t ok;
  asm volatile(
      "{\n.reg .pred p;\nmbarrier.try_wait.parity.shared::cta.b64 p, [%1], %2;\nselp.u32 %0, 1, 0, p;\n}\n"
      : "=r"(ok)
      : "r"(bar), "r"(parity)
      : "memory");
  return ok != 0;
}
__device__ __forceinline__ bool mbar_try_cluster(uint32_t bar, uint32_t parity) {
  uint32_t ok;
  asm volatile(
      "{\n.reg .pred p;\nmbarrier.try_wait.parity.shared::cta.b64 p, [%1], %2;\nselp.u32 %0, 1, 0, p;\n}\n"
      : "=r"(ok)
      : "r"(bar), "r"(parity)
      : "memory");
  return ok != 0;
}
__device__ __forceinline__ void mbar_wait(uint32_t bar) {
  for (uint32_t it = 0; it < (1u << 22); ++it)
    if (mbar_try(bar, 0)) break;
}
__device__ __forceinline__ void mbar_wait_cluster(uint32_t bar) {
  for (uint32_t it = 0; it < (1u << 22); ++it)
    if (mbar_try_cluster(bar, 0)) break;
}
__device__ __forceinline__ void tma_load(uint32_t dst, const CUtensorMap* tm, int c0, int c1, uint32_t bar) {
  asm volatile(
      "cp.async.bulk.tensor.2d.shared::cluster.global.mbarrier::complete_tx::bytes [%0], [%1, {%3, %4}], [%2];" ::"r"(dst),
      "l"(tm), "r"(bar), "r"(c0), "r"(c1)
      : "memory");
}
__device__ __forceinline__ void tma_load_mc(uint32_t dst, const CUtensorMap* tm, int c0, int c1, uint32_t bar, uint16_t mask) {
  asm volatile(
      "cp.async.bulk.tensor.2d.shared::cluster.global.mbarrier::complete_tx::bytes.multicast::cluster [%0], [%1, {%3, %4}], [%2], %5;" ::"r"(dst),
      "l"(tm), "r"(bar), "r"(c0), "r"(c1), "h"(mask)
      : "memory");
}
__device__ __forceinline__ void tma_prefetch(const CUtensorMap* tm, int c0, int c1) {
  asm volatile("cp.async.bulk.prefetch.tensor.2d.L2.global [%0, {%1, %2}];" ::"l"(tm), "r"(c0), "r"(c1) : "memory");
}
__device__ __forceinline__ void prefetch_tmap(const CUtensorMap* tm) {
  asm volatile("prefetch.tensormap [%0];" ::"l"(tm) : "memory");
}
__device__ __forceinline__ void cluster_arrive() { asm volatile("barrier.cluster.arrive.release.aligned;" ::: "memory"); }
__device__ __forceinline__ void cluster_wait() { asm volatile("barrier.cluster.wait.acquire.aligned;" ::: "memory"); }
__device__ __forceinline__ void named_bar(int id, int n) { asm volatile("bar.sync %0, %1;" ::"r"(id), "r"(n) : "memory"); }
__device__ __forceinline__ void wg_fence() { asm volatile("wgmma.fence.sync.aligned;" ::: "memory"); }
__device__ __forceinline__ void wg_commit() { asm volatile("wgmma.commit_group.sync.aligned;" ::: "memory"); }
template <int N>
__device__ __forceinline__ void wg_wait() { asm volatile("wgmma.wait_group.sync.aligned %0;" ::"n"(N) : "memory"); }
template <int N>
__device__ __forceinline__ void fence_regs(float (&d)[N]) {
#pragma unroll
  for (int i = 0; i < N; i++) asm volatile("" : "+f"(d[i])::"memory");
}
template <int N>
__device__ __forceinline__ void def_regs(float (&d)[N]) {
#pragma unroll
  for (int i = 0; i < N; i++) asm volatile("" : "=f"(d[i]));
}
__device__ __forceinline__ uint64_t make_desc(uint32_t addr, uint32_t lbo, uint32_t sbo) {
  return (uint64_t)((addr & 0x3FFFF) >> 4) | ((uint64_t)(lbo >> 4) << 16) | ((uint64_t)(sbo >> 4) << 32) | (1ull << 62);
}
__device__ __forceinline__ uint32_t pack_bf16(float lo, float hi) {
  uint32_t r;
  asm("cvt.rn.bf16x2.f32 %0, %1, %2;" : "=r"(r) : "f"(hi), "f"(lo));
  return r;
}
__device__ __forceinline__ float ex2(float x) {
  float y;
  asm("ex2.approx.ftz.f32 %0, %1;" : "=f"(y) : "f"(x));
  return y;
}
__device__ __forceinline__ float bf_lo(uint32_t v) { return __uint_as_float(v << 16); }
__device__ __forceinline__ float bf_hi(uint32_t v) { return __uint_as_float(v & 0xffff0000u); }

__device__ __forceinline__ void wgmma_ss_n128_tb(float (&d)[64], uint64_t da, uint64_t db, int scale_d) {
  asm volatile("{\n.reg .pred p;\nsetp.ne.b32 p, %66, 0;\n"
    "wgmma.mma_async.sync.aligned.m64n128k16.f32.bf16.bf16 {%0, %1, %2, %3, %4, %5, %6, %7, %8, %9, %10, %11, %12, %13, %14, %15, %16, %17, %18, %19, %20, %21, %22, %23, %24, %25, %26, %27, %28, %29, %30, %31, %32, %33, %34, %35, %36, %37, %38, %39, %40, %41, %42, %43, %44, %45, %46, %47, %48, %49, %50, %51, %52, %53, %54, %55, %56, %57, %58, %59, %60, %61, %62, %63}, %64, %65, p, 1, 1, 0, 1;\n}\n"
    : "+f"(d[0]), "+f"(d[1]), "+f"(d[2]), "+f"(d[3]), "+f"(d[4]), "+f"(d[5]), "+f"(d[6]), "+f"(d[7]), "+f"(d[8]), "+f"(d[9]), "+f"(d[10]), "+f"(d[11]), "+f"(d[12]), "+f"(d[13]), "+f"(d[14]), "+f"(d[15]), "+f"(d[16]), "+f"(d[17]), "+f"(d[18]), "+f"(d[19]), "+f"(d[20]), "+f"(d[21]), "+f"(d[22]), "+f"(d[23]), "+f"(d[24]), "+f"(d[25]), "+f"(d[26]), "+f"(d[27]), "+f"(d[28]), "+f"(d[29]), "+f"(d[30]), "+f"(d[31]), "+f"(d[32]), "+f"(d[33]), "+f"(d[34]), "+f"(d[35]), "+f"(d[36]), "+f"(d[37]), "+f"(d[38]), "+f"(d[39]), "+f"(d[40]), "+f"(d[41]), "+f"(d[42]), "+f"(d[43]), "+f"(d[44]), "+f"(d[45]), "+f"(d[46]), "+f"(d[47]), "+f"(d[48]), "+f"(d[49]), "+f"(d[50]), "+f"(d[51]), "+f"(d[52]), "+f"(d[53]), "+f"(d[54]), "+f"(d[55]), "+f"(d[56]), "+f"(d[57]), "+f"(d[58]), "+f"(d[59]), "+f"(d[60]), "+f"(d[61]), "+f"(d[62]), "+f"(d[63])
    : "l"(da), "l"(db), "r"(scale_d));
}

__device__ __forceinline__ void wgmma_rs_n128(float (&d)[64], uint32_t a0, uint32_t a1, uint32_t a2, uint32_t a3, uint64_t db, int scale_d) {
  asm volatile("{\n.reg .pred p;\nsetp.ne.b32 p, %69, 0;\n"
    "wgmma.mma_async.sync.aligned.m64n128k16.f32.bf16.bf16 {%0, %1, %2, %3, %4, %5, %6, %7, %8, %9, %10, %11, %12, %13, %14, %15, %16, %17, %18, %19, %20, %21, %22, %23, %24, %25, %26, %27, %28, %29, %30, %31, %32, %33, %34, %35, %36, %37, %38, %39, %40, %41, %42, %43, %44, %45, %46, %47, %48, %49, %50, %51, %52, %53, %54, %55, %56, %57, %58, %59, %60, %61, %62, %63}, {%64, %65, %66, %67}, %68, p, 1, 1, 0;\n}\n"
    : "+f"(d[0]), "+f"(d[1]), "+f"(d[2]), "+f"(d[3]), "+f"(d[4]), "+f"(d[5]), "+f"(d[6]), "+f"(d[7]), "+f"(d[8]), "+f"(d[9]), "+f"(d[10]), "+f"(d[11]), "+f"(d[12]), "+f"(d[13]), "+f"(d[14]), "+f"(d[15]), "+f"(d[16]), "+f"(d[17]), "+f"(d[18]), "+f"(d[19]), "+f"(d[20]), "+f"(d[21]), "+f"(d[22]), "+f"(d[23]), "+f"(d[24]), "+f"(d[25]), "+f"(d[26]), "+f"(d[27]), "+f"(d[28]), "+f"(d[29]), "+f"(d[30]), "+f"(d[31]), "+f"(d[32]), "+f"(d[33]), "+f"(d[34]), "+f"(d[35]), "+f"(d[36]), "+f"(d[37]), "+f"(d[38]), "+f"(d[39]), "+f"(d[40]), "+f"(d[41]), "+f"(d[42]), "+f"(d[43]), "+f"(d[44]), "+f"(d[45]), "+f"(d[46]), "+f"(d[47]), "+f"(d[48]), "+f"(d[49]), "+f"(d[50]), "+f"(d[51]), "+f"(d[52]), "+f"(d[53]), "+f"(d[54]), "+f"(d[55]), "+f"(d[56]), "+f"(d[57]), "+f"(d[58]), "+f"(d[59]), "+f"(d[60]), "+f"(d[61]), "+f"(d[62]), "+f"(d[63])
    : "r"(a0), "r"(a1), "r"(a2), "r"(a3), "l"(db), "r"(scale_d));
}

__device__ __forceinline__ void wgmma_rs_n128_tb(float (&d)[64], uint32_t a0, uint32_t a1, uint32_t a2, uint32_t a3, uint64_t db, int scale_d) {
  asm volatile("{\n.reg .pred p;\nsetp.ne.b32 p, %69, 0;\n"
    "wgmma.mma_async.sync.aligned.m64n128k16.f32.bf16.bf16 {%0, %1, %2, %3, %4, %5, %6, %7, %8, %9, %10, %11, %12, %13, %14, %15, %16, %17, %18, %19, %20, %21, %22, %23, %24, %25, %26, %27, %28, %29, %30, %31, %32, %33, %34, %35, %36, %37, %38, %39, %40, %41, %42, %43, %44, %45, %46, %47, %48, %49, %50, %51, %52, %53, %54, %55, %56, %57, %58, %59, %60, %61, %62, %63}, {%64, %65, %66, %67}, %68, p, 1, 1, 1;\n}\n"
    : "+f"(d[0]), "+f"(d[1]), "+f"(d[2]), "+f"(d[3]), "+f"(d[4]), "+f"(d[5]), "+f"(d[6]), "+f"(d[7]), "+f"(d[8]), "+f"(d[9]), "+f"(d[10]), "+f"(d[11]), "+f"(d[12]), "+f"(d[13]), "+f"(d[14]), "+f"(d[15]), "+f"(d[16]), "+f"(d[17]), "+f"(d[18]), "+f"(d[19]), "+f"(d[20]), "+f"(d[21]), "+f"(d[22]), "+f"(d[23]), "+f"(d[24]), "+f"(d[25]), "+f"(d[26]), "+f"(d[27]), "+f"(d[28]), "+f"(d[29]), "+f"(d[30]), "+f"(d[31]), "+f"(d[32]), "+f"(d[33]), "+f"(d[34]), "+f"(d[35]), "+f"(d[36]), "+f"(d[37]), "+f"(d[38]), "+f"(d[39]), "+f"(d[40]), "+f"(d[41]), "+f"(d[42]), "+f"(d[43]), "+f"(d[44]), "+f"(d[45]), "+f"(d[46]), "+f"(d[47]), "+f"(d[48]), "+f"(d[49]), "+f"(d[50]), "+f"(d[51]), "+f"(d[52]), "+f"(d[53]), "+f"(d[54]), "+f"(d[55]), "+f"(d[56]), "+f"(d[57]), "+f"(d[58]), "+f"(d[59]), "+f"(d[60]), "+f"(d[61]), "+f"(d[62]), "+f"(d[63])
    : "r"(a0), "r"(a1), "r"(a2), "r"(a3), "l"(db), "r"(scale_d));
}

__device__ __forceinline__ void wgmma_rs_n32_tb(float (&d)[16], uint32_t a0, uint32_t a1, uint32_t a2, uint32_t a3, uint64_t db, int scale_d) {
  asm volatile("{\n.reg .pred p;\nsetp.ne.b32 p, %21, 0;\n"
    "wgmma.mma_async.sync.aligned.m64n32k16.f32.bf16.bf16 {%0, %1, %2, %3, %4, %5, %6, %7, %8, %9, %10, %11, %12, %13, %14, %15}, {%16, %17, %18, %19}, %20, p, 1, 1, 1;\n}\n"
    : "+f"(d[0]), "+f"(d[1]), "+f"(d[2]), "+f"(d[3]), "+f"(d[4]), "+f"(d[5]), "+f"(d[6]), "+f"(d[7]), "+f"(d[8]), "+f"(d[9]), "+f"(d[10]), "+f"(d[11]), "+f"(d[12]), "+f"(d[13]), "+f"(d[14]), "+f"(d[15])
    : "r"(a0), "r"(a1), "r"(a2), "r"(a3), "l"(db), "r"(scale_d));
}


struct Maps {
  CUtensorMap x[2], k[2], v[2], wq[2], wo[2];
};

__global__ void __cluster_dims__(2, 1, 1) __launch_bounds__(384, 1)
fused_gqa_kernel(const __grid_constant__ Maps maps, __nv_bfloat16* __restrict__ out) {
  extern __shared__ __align__(1024) unsigned char smem[];
  const uint32_t sbase = smem_u32(smem);
  const uint32_t full0 = sbase + BAR_OFF;
  const uint32_t empty0 = full0 + N_ITEMS * 8;

  const int tid = threadIdx.x;
  const int wg = tid >> 7;
  const int bid = blockIdx.x;
  const int r = bid & 1;
  const int bp = (bid >> 1) & 3;
  const int j = (bid >> 3) & 7;
  const int p = bid >> 6;
  const int b = bp * 2 + r;

  if (tid == 0) {
    for (int i = 0; i < N_ITEMS; i++) {
      mbar_init(full0 + i * 8, 1);
      mbar_init(empty0 + i * 8, c_plan.remote[i] ? 16 : 8);
    }
    asm volatile("fence.mbarrier_init.release.cluster;" ::: "memory");
    prefetch_tmap(&maps.x[p]);
    prefetch_tmap(&maps.wq[p]);
    prefetch_tmap(&maps.k[p]);
    prefetch_tmap(&maps.v[p]);
    prefetch_tmap(&maps.wo[p]);
  }
  __syncthreads();
  cluster_arrive();
  cluster_wait();

  if (wg == 0) {
    asm volatile("setmaxnreg.dec.sync.aligned.u32 24;");
    if (tid == 0) {
      const CUtensorMap* tmx = &maps.x[p];
      const CUtensorMap* tmq = &maps.wq[p];
      const CUtensorMap* tmk = &maps.k[p];
      const CUtensorMap* tmv = &maps.v[p];
      const CUtensorMap* tmo = &maps.wo[p];
      int item = 0;
      for (int hh = 0; hh < 2; hh++) {
        const int h = 2 * j + hh;
        for (int kc = 0; kc < N_QW; kc++, item++) {
          const int dep = c_plan.dep[item];
          if (dep >= 0) mbar_wait_cluster(empty0 + dep * 8);
          const uint32_t fb = full0 + item * 8;
          const uint32_t dst = sbase + c_plan.off[item];
          mbar_expect_tx(fb, QW_BYTES);
          tma_load(dst, tmx, kc * 64, b * 64, fb);
          tma_load_mc(dst + 8192 + (2 * r) * 8192, tmq, h * 256 + (2 * r) * 64, kc * 64, fb, 3);
          tma_load_mc(dst + 8192 + (2 * r + 1) * 8192, tmq, h * 256 + (2 * r + 1) * 64, kc * 64, fb, 3);
        }
        const int row0 = (b * 16 + h) * kSK;
        for (int t = 0; t < N_KV; t++, item++) {
          const int dep = c_plan.dep[item];
          if (dep >= 0) mbar_wait_cluster(empty0 + dep * 8);
          const uint32_t fb = full0 + item * 8;
          const uint32_t dst = sbase + c_plan.off[item];
          mbar_expect_tx(fb, KV_BYTES);
          const CUtensorMap* tm = (t & 1) ? tmv : tmk;
          tma_load(dst, tm, 0, row0 + (t >> 1) * 128, fb);
          tma_load(dst + 16384, tm, 64, row0 + (t >> 1) * 128, fb);
        }
      }
      for (int w = 0; w < N_WO; w++, item++) {
        const int dep = c_plan.dep[item];
        if (dep >= 0) mbar_wait_cluster(empty0 + dep * 8);
        const uint32_t fb = full0 + item * 8;
        const uint32_t dst = sbase + c_plan.off[item];
        mbar_expect_tx(fb, WO_BYTES);
        if (w < 16) {
          const int pn = w >> 3, kc = w & 7;
          tma_load_mc(dst + (2 * r) * 8192, tmo, pn * 256 + (2 * r) * 64, j * 512 + kc * 64, fb, 3);
          tma_load_mc(dst + (2 * r + 1) * 8192, tmo, pn * 256 + (2 * r + 1) * 64, j * 512 + kc * 64, fb, 3);
        } else {
          const int kh = w - 16;
          tma_load_mc(dst + (2 * r) * 8192, tmo, 512, j * 512 + kh * 256 + (2 * r) * 64, fb, 3);
          tma_load_mc(dst + (2 * r + 1) * 8192, tmo, 512, j * 512 + kh * 256 + (2 * r + 1) * 64, fb, 3);
        }
      }
    }
    __syncwarp();
    cluster_arrive();
    cluster_wait();
  } else {
    asm volatile("setmaxnreg.inc.sync.aligned.u32 240;");
    const int w = wg - 1;
    const int t128 = tid & 127;
    const int lane = tid & 31;
    const uint32_t peer = r ^ 1;

    auto release = [&](int item) {
      __syncwarp();
      if (lane == 0) {
        mbar_arrive(empty0 + item * 8);
        if (c_plan.remote[item]) mbar_arrive_remote(empty0 + item * 8, peer);
      }
    };

    const float cs = 0.08838834764831845f * 1.4426950408889634f;
    int item = 0;
    float s[64];
#pragma unroll
    for (int i = 0; i < 64; i++) s[i] = 0.f;
#pragma unroll 1
    for (int hh = 0; hh < 2; hh++) {
      uint32_t qf[32];
      {
        float(&acc)[64] = s;
#pragma unroll 1
        for (int kc = 0; kc < N_QW; kc++, item++) {
          const uint32_t base = sbase + c_plan.off[item];
          mbar_wait(full0 + item * 8);
          const uint64_t da = make_desc(base, 16, 1024);
          const uint64_t db = make_desc(base + 8192 + w * 16384, 8192, 1024);
          wg_fence();
#pragma unroll
          for (int ks = 0; ks < 4; ks++) wgmma_ss_n128_tb(acc, da + ks * 2, db + ks * 128, (kc | ks) != 0);
          wg_commit();
          if (kc > 0) {
            wg_wait<1>();
            release(item - 1);
          }
        }
        wg_wait<0>();
        fence_regs(acc);
        release(item - 1);
#pragma unroll
        for (int i = 0; i < 32; i++) qf[i] = pack_bf16(acc[2 * i], acc[2 * i + 1]);
      }
      float o[64];
#pragma unroll
      for (int i = 0; i < 64; i++) o[i] = 0.f;
      float m0 = -INFINITY, m1 = -INFINITY, l0 = 0.f, l1 = 0.f;
#pragma unroll 1
      for (int t = 0; t < 4; t++) {
        {
          const uint32_t base = sbase + c_plan.off[item];
          mbar_wait(full0 + item * 8);
          const uint64_t db = make_desc(base, 16, 1024);
          wg_fence();
#pragma unroll
          for (int ks = 0; ks < 8; ks++)
            wgmma_rs_n128(s, qf[4 * ks], qf[4 * ks + 1], qf[4 * ks + 2], qf[4 * ks + 3], db + (ks >> 2) * 1024 + (ks & 3) * 2,
                          ks != 0);
          wg_commit();
          wg_wait<0>();
          fence_regs(s);
          release(item);
          item++;
        }
        float mx0 = s[0], mx1 = s[2];
#pragma unroll
        for (int g = 0; g < 16; g++) {
          mx0 = fmaxf(mx0, fmaxf(s[4 * g], s[4 * g + 1]));
          mx1 = fmaxf(mx1, fmaxf(s[4 * g + 2], s[4 * g + 3]));
        }
        mx0 = fmaxf(mx0, __shfl_xor_sync(0xffffffffu, mx0, 1));
        mx0 = fmaxf(mx0, __shfl_xor_sync(0xffffffffu, mx0, 2));
        mx1 = fmaxf(mx1, __shfl_xor_sync(0xffffffffu, mx1, 1));
        mx1 = fmaxf(mx1, __shfl_xor_sync(0xffffffffu, mx1, 2));
        const float mn0 = fmaxf(m0, mx0), mn1 = fmaxf(m1, mx1);
        const float a0 = ex2((m0 - mn0) * cs), a1 = ex2((m1 - mn1) * cs);
        m0 = mn0;
        m1 = mn1;
        const float ms0 = mn0 * cs, ms1 = mn1 * cs;
        float rs0 = 0.f, rs1 = 0.f;
        uint32_t pf[32];
#pragma unroll
        for (int g = 0; g < 16; g++) {
          const float p0 = ex2(fmaf(s[4 * g], cs, -ms0));
          const float p1 = ex2(fmaf(s[4 * g + 1], cs, -ms0));
          const float p2 = ex2(fmaf(s[4 * g + 2], cs, -ms1));
          const float p3 = ex2(fmaf(s[4 * g + 3], cs, -ms1));
          rs0 += p0 + p1;
          rs1 += p2 + p3;
          pf[2 * g] = pack_bf16(p0, p1);
          pf[2 * g + 1] = pack_bf16(p2, p3);
        }
        l0 = l0 * a0 + rs0;
        l1 = l1 * a1 + rs1;
#pragma unroll
        for (int g = 0; g < 16; g++) {
          o[4 * g] *= a0;
          o[4 * g + 1] *= a0;
          o[4 * g + 2] *= a1;
          o[4 * g + 3] *= a1;
        }
        {
          const uint32_t base = sbase + c_plan.off[item];
          mbar_wait(full0 + item * 8);
          const uint64_t db = make_desc(base, 16384, 1024);
          wg_fence();
#pragma unroll
          for (int ks = 0; ks < 8; ks++)
            wgmma_rs_n128_tb(o, pf[4 * ks], pf[4 * ks + 1], pf[4 * ks + 2], pf[4 * ks + 3], db + ks * 128, 1);
          wg_commit();
          wg_wait<0>();
          fence_regs(o);
          release(item);
          item++;
        }
      }
      l0 += __shfl_xor_sync(0xffffffffu, l0, 1);
      l0 += __shfl_xor_sync(0xffffffffu, l0, 2);
      l1 += __shfl_xor_sync(0xffffffffu, l1, 1);
      l1 += __shfl_xor_sync(0xffffffffu, l1, 2);
      const float i0 = 1.f / l0, i1 = 1.f / l1;
      uint4* ob = reinterpret_cast<uint4*>(smem + OBUF_OFF) + (hh * 2 + w) * 1024 + t128;
#pragma unroll
      for (int i = 0; i < 8; i++) {
        uint4 v;
        v.x = pack_bf16(o[8 * i] * i0, o[8 * i + 1] * i0);
        v.y = pack_bf16(o[8 * i + 2] * i1, o[8 * i + 3] * i1);
        v.z = pack_bf16(o[8 * i + 4] * i0, o[8 * i + 5] * i0);
        v.w = pack_bf16(o[8 * i + 6] * i1, o[8 * i + 7] * i1);
        ob[i * 128] = v;
      }
    }
    named_bar(1, 256);
    uint32_t af[128];
    {
      const uint4* ob = reinterpret_cast<const uint4*>(smem + OBUF_OFF) + t128;
#pragma unroll
      for (int i = 0; i < 32; i++) {
        uint4 v = ob[i * 128];
        af[4 * i] = v.x;
        af[4 * i + 1] = v.y;
        af[4 * i + 2] = v.z;
        af[4 * i + 3] = v.w;
      }
    }
    const int tile = p * 8 + b;
    uint4* part = g_part + (size_t)(tile * 8 + j) * 18 * 256 + (w * 128 + t128);
    unsigned target[3];
#pragma unroll
    for (int pn = 0; pn < 2; pn++) {
      float(&acc)[64] = s;
#pragma unroll
      for (int kc = 0; kc < 8; kc++, item++) {
        const uint32_t base = sbase + c_plan.off[item];
        mbar_wait(full0 + item * 8);
        const uint64_t db = make_desc(base + w * 16384, 8192, 1024);
        wg_fence();
#pragma unroll
        for (int ks = 0; ks < 4; ks++) {
          const int a = (kc * 4 + ks) * 4;
          wgmma_rs_n128_tb(acc, af[a], af[a + 1], af[a + 2], af[a + 3], db + ks * 128, (kc | ks) != 0);
        }
        wg_commit();
        if (kc > 0) {
          wg_wait<1>();
          release(item - 1);
        }
      }
      wg_wait<0>();
      fence_regs(acc);
      release(item - 1);
#pragma unroll
      for (int i = 0; i < 8; i++) {
        uint4 v;
        v.x = pack_bf16(acc[8 * i], acc[8 * i + 1]);
        v.y = pack_bf16(acc[8 * i + 2], acc[8 * i + 3]);
        v.z = pack_bf16(acc[8 * i + 4], acc[8 * i + 5]);
        v.w = pack_bf16(acc[8 * i + 6], acc[8 * i + 7]);
        __stcg(part + (pn * 8 + i) * 256, v);
      }
      __threadfence();
      named_bar(2 + w, 128);
      if (t128 == 0) {
        unsigned old = atomicAdd(&g_cnt[(tile * 4 + pn) * 32], 1u);
        target[pn] = (old / 16u + 1u) * 16u;
      }
    }
    {
      float acc[16];
#pragma unroll
      for (int i = 0; i < 16; i++) acc[i] = 0.f;
#pragma unroll
      for (int kh = 0; kh < 2; kh++, item++) {
        const uint32_t base = sbase + c_plan.off[item];
        mbar_wait(full0 + item * 8);
        const uint64_t db = make_desc(base + w * 64, 8192, 1024);
        wg_fence();
#pragma unroll
        for (int ks = 0; ks < 16; ks++) {
          const int a = (kh * 16 + ks) * 4;
          wgmma_rs_n32_tb(acc, af[a], af[a + 1], af[a + 2], af[a + 3], db + ks * 128, (kh | ks) != 0);
        }
        wg_commit();
      }
      wg_wait<0>();
      fence_regs(acc);
      release(item - 2);
      release(item - 1);
#pragma unroll
      for (int i = 0; i < 2; i++) {
        uint4 v;
        v.x = pack_bf16(acc[8 * i], acc[8 * i + 1]);
        v.y = pack_bf16(acc[8 * i + 2], acc[8 * i + 3]);
        v.z = pack_bf16(acc[8 * i + 4], acc[8 * i + 5]);
        v.w = pack_bf16(acc[8 * i + 6], acc[8 * i + 7]);
        __stcg(part + (16 + i) * 256, v);
      }
      __threadfence();
      named_bar(2 + w, 128);
      if (t128 == 0) {
        unsigned old = atomicAdd(&g_cnt[(tile * 4 + 2) * 32], 1u);
        target[2] = (old / 16u + 1u) * 16u;
      }
    }
    const int row0 = (t128 >> 5) * 16 + (lane >> 2);
    const int q2 = (lane & 3) * 2;
    __nv_bfloat16* orow = out + (size_t)(b * 64 + row0) * 1152 + p * 576;
    const uint4* pr = g_part + (size_t)(tile * 8) * 18 * 256 + (w * 128 + t128);
#pragma unroll
    for (int pn = 0; pn < 3; pn++) {
      if (t128 == 0) {
        const unsigned* c = &g_cnt[(tile * 4 + pn) * 32];
        for (uint32_t it = 0; it < (1u << 22); ++it) {
          unsigned v;
          asm volatile("ld.acquire.gpu.global.u32 %0, [%1];" : "=r"(v) : "l"(c) : "memory");
          if ((int)(v - target[pn]) >= 0) break;
        }
      }
      named_bar(2 + w, 128);
      int slot, col;
      bool active = true;
      if (pn < 2) {
        slot = pn * 8 + j;
        col = pn * 256 + w * 128 + j * 16 + q2;
      } else {
        slot = 16 + (j & 1);
        col = 512 + w * 32 + (j & 1) * 16 + q2;
        active = (((w * 128 + t128) >> 6) == (j >> 1));
      }
      if (active) {
        uint4 v[8];
#pragma unroll
        for (int c = 0; c < 8; c++) v[c] = __ldcg(pr + (size_t)(c * 18 + slot) * 256);
        float s[8];
#pragma unroll
        for (int e = 0; e < 8; e++) s[e] = 0.f;
#pragma unroll
        for (int c = 0; c < 8; c++) {
          s[0] += bf_lo(v[c].x);
          s[1] += bf_hi(v[c].x);
          s[2] += bf_lo(v[c].y);
          s[3] += bf_hi(v[c].y);
          s[4] += bf_lo(v[c].z);
          s[5] += bf_hi(v[c].z);
          s[6] += bf_lo(v[c].w);
          s[7] += bf_hi(v[c].w);
        }
        *reinterpret_cast<uint32_t*>(orow + col) = pack_bf16(s[0], s[1]);
        *reinterpret_cast<uint32_t*>(orow + 8 * 1152 + col) = pack_bf16(s[2], s[3]);
        *reinterpret_cast<uint32_t*>(orow + col + 8) = pack_bf16(s[4], s[5]);
        *reinterpret_cast<uint32_t*>(orow + 8 * 1152 + col + 8) = pack_bf16(s[6], s[7]);
      }
    }
    cluster_arrive();
    cluster_wait();
  }
}

typedef CUresult (*EncodeFn)(CUtensorMap*, CUtensorMapDataType, cuuint32_t, void*, const cuuint64_t*, const cuuint64_t*,
                             const cuuint32_t*, const cuuint32_t*, CUtensorMapInterleave, CUtensorMapSwizzle,
                             CUtensorMapL2promotion, CUtensorMapFloatOOBfill);

void encode2d(EncodeFn fn, CUtensorMap* m, void* ptr, uint64_t cols, uint64_t rows, uint32_t box_cols, uint32_t box_rows) {
  cuuint64_t dims[2] = {cols, rows};
  cuuint64_t strides[1] = {cols * 2};
  cuuint32_t box[2] = {box_cols, box_rows};
  cuuint32_t es[2] = {1, 1};
  fn(m, CU_TENSOR_MAP_DATA_TYPE_BFLOAT16, 2, ptr, dims, strides, box, es, CU_TENSOR_MAP_INTERLEAVE_NONE,
     CU_TENSOR_MAP_SWIZZLE_128B, CU_TENSOR_MAP_L2_PROMOTION_L2_256B, CU_TENSOR_MAP_FLOAT_OOB_FILL_NONE);
}

}

extern "C" void kernel_launch(void* const* d_in, const int* in_sizes, int n_in, void* d_out, int out_size) {
  static EncodeFn fn = nullptr;
  if (!fn) {
    void* f = nullptr;
    cudaDriverEntryPointQueryResult st;
    cudaGetDriverEntryPoint("cuTensorMapEncodeTiled", &f, cudaEnableDefault, &st);
    fn = (EncodeFn)f;
    cudaFuncSetAttribute(fused_gqa_kernel, cudaFuncAttributeMaxDynamicSharedMemorySize, SMEM_BYTES);
  }
  Maps maps;
  for (int p = 0; p < 2; p++) {
    encode2d(fn, &maps.x[p], d_in[p * 5 + 0], kD, 512, 64, 64);
    encode2d(fn, &maps.k[p], d_in[p * 5 + 1], kDH, 8 * 16 * kSK, 64, 128);
    encode2d(fn, &maps.v[p], d_in[p * 5 + 2], kDH, 8 * 16 * kSK, 64, 128);
    encode2d(fn, &maps.wq[p], d_in[p * 5 + 3], kHQD, kD, 64, 64);
    encode2d(fn, &maps.wo[p], d_in[p * 5 + 4], kD, kHQD, 64, 64);
  }
  fused_gqa_kernel<<<128, 384, SMEM_BYTES>>>(maps, (__nv_bfloat16*)d_out);
}
```

```cpp
#include <cuda_runtime.h>
#include <cuda_bf16.h>
#include <cuda.h>
#include <stdint.h>

namespace {

constexpr int kD = 576, kHQD = 4096, kSK = 512, kDH = 128;

constexpr int N_QW = 18, N_KV = 16, N_WO = 18;
constexpr int N_ITEMS = N_QW + N_KV + N_WO;
constexpr int QW_BYTES = 40 * 1024;
constexpr int KV_BYTES = 32 * 1024;
constexpr int WO_BYTES = 32 * 1024;
constexpr int KV_OFF = 96 * 1024;
constexpr int OPARK_OFF = 192 * 1024;
constexpr int BAR_OFF = 224 * 1024;
constexpr int SMEM_BYTES = BAR_OFF + 2 * N_ITEMS * 8 + 64;
constexpr int QW0 = 0, KV0 = N_QW, WO0 = N_QW + N_KV;

__device__ __forceinline__ int qw_off(int q) { return (q & 1) * QW_BYTES; }
__device__ __forceinline__ int kv_off(int n) { return KV_OFF + (n % 3) * KV_BYTES; }
__device__ __forceinline__ int wo_off(int m) {
  const int s = m % 5;
  return (s < 3 ? s : s + 1) * 32768;
}

__device__ uint4 g_part[16 * 8 * 18 * 256];
__device__ unsigned int g_cnt[16 * 4 * 32];

#define TR(role, ev)
#define TRC(ev)
constexpr uint32_t WAIT_LIMIT = 1u << 14;
__device__ __forceinline__ uint32_t smem_u32(const void* p) { return (uint32_t)__cvta_generic_to_shared(p); }
__device__ __forceinline__ void mbar_init(uint32_t bar, uint32_t cnt) {
  asm volatile("mbarrier.init.shared::cta.b64 [%0], %1;" ::"r"(bar), "r"(cnt) : "memory");
}
__device__ __forceinline__ void mbar_expect_tx(uint32_t bar, uint32_t bytes) {
  asm volatile("mbarrier.arrive.expect_tx.shared::cta.b64 _, [%0], %1;" ::"r"(bar), "r"(bytes) : "memory");
}
__device__ __forceinline__ void mbar_arrive(uint32_t bar) {
  asm volatile("mbarrier.arrive.shared::cta.b64 _, [%0];" ::"r"(bar) : "memory");
}
__device__ __forceinline__ void mbar_arrive_remote(uint32_t bar, uint32_t cta) {
  asm volatile(
      "{\n.reg .b32 ra;\nmapa.shared::cluster.u32 ra, %0, %1;\n"
      "mbarrier.arrive.shared::cluster.b64 _, [ra];\n}\n" ::"r"(bar), "r"(cta)
      : "memory");
}
__device__ __forceinline__ bool mbar_try(uint32_t bar, uint32_t parity) {
  uint32_t ok;
  asm volatile(
      "{\n.reg .pred p;\nmbarrier.try_wait.parity.shared::cta.b64 p, [%1], %2;\nselp.u32 %0, 1, 0, p;\n}\n"
      : "=r"(ok)
      : "r"(bar), "r"(parity)
      : "memory");
  return ok != 0;
}
__device__ __forceinline__ void mbar_wait(uint32_t bar) {
  if (mbar_try(bar, 0)) return;
  for (uint32_t it = 0; it < WAIT_LIMIT; ++it)
    if (mbar_try(bar, 0)) break;
}
__device__ __forceinline__ void tma_load(uint32_t dst, const CUtensorMap* tm, int c0, int c1, uint32_t bar) {
  asm volatile(
      "cp.async.bulk.tensor.2d.shared::cluster.global.mbarrier::complete_tx::bytes [%0], [%1, {%3, %4}], [%2];" ::"r"(dst),
      "l"(tm), "r"(bar), "r"(c0), "r"(c1)
      : "memory");
}
__device__ __forceinline__ void tma_load_mc(uint32_t dst, const CUtensorMap* tm, int c0, int c1, uint32_t bar, uint16_t mask) {
  asm volatile(
      "cp.async.bulk.tensor.2d.shared::cluster.global.mbarrier::complete_tx::bytes.multicast::cluster [%0], [%1, {%3, %4}], [%2], %5;" ::"r"(dst),
      "l"(tm), "r"(bar), "r"(c0), "r"(c1), "h"(mask)
      : "memory");
}
__device__ __forceinline__ void prefetch_tmap(const CUtensorMap* tm) {
  asm volatile("prefetch.tensormap [%0];" ::"l"(tm) : "memory");
}
__device__ __forceinline__ void cluster_arrive_relaxed() { asm volatile("barrier.cluster.arrive.relaxed.aligned;" ::: "memory"); }
__device__ __forceinline__ void cluster_wait() { asm volatile("barrier.cluster.wait.acquire.aligned;" ::: "memory"); }
__device__ __forceinline__ void named_bar(int id, int n) { asm volatile("bar.sync %0, %1;" ::"r"(id), "r"(n) : "memory"); }
__device__ __forceinline__ void named_arrive(int id, int n) { asm volatile("bar.arrive %0, %1;" ::"r"(id), "r"(n) : "memory"); }
__device__ __forceinline__ void wg_fence() { asm volatile("wgmma.fence.sync.aligned;" ::: "memory"); }
__device__ __forceinline__ void wg_commit() { asm volatile("wgmma.commit_group.sync.aligned;" ::: "memory"); }
template <int N>
__device__ __forceinline__ void wg_wait() { asm volatile("wgmma.wait_group.sync.aligned %0;" ::"n"(N) : "memory"); }
template <int N>
__device__ __forceinline__ void fence_regs(float (&d)[N]) {
#pragma unroll
  for (int i = 0; i < N; i++) asm volatile("" : "+f"(d[i])::"memory");
}
__device__ __forceinline__ uint64_t make_desc(uint32_t addr, uint32_t lbo, uint32_t sbo) {
  return (uint64_t)((addr & 0x3FFFF) >> 4) | ((uint64_t)(lbo >> 4) << 16) | ((uint64_t)(sbo >> 4) << 32) | (1ull << 62);
}
__device__ __forceinline__ uint32_t pack_bf16(float lo, float hi) {
  uint32_t r;
  asm("cvt.rn.bf16x2.f32 %0, %1, %2;" : "=r"(r) : "f"(hi), "f"(lo));
  return r;
}
__device__ __forceinline__ float ex2(float x) {
  float y;
  asm("ex2.approx.ftz.f32 %0, %1;" : "=f"(y) : "f"(x));
  return y;
}
__device__ __forceinline__ float bf_lo(uint32_t v) { return __uint_as_float(v << 16); }
__device__ __forceinline__ float bf_hi(uint32_t v) { return __uint_as_float(v & 0xffff0000u); }

__device__ __forceinline__ void wgmma_ss_n128_tb(float (&d)[64], uint64_t da, uint64_t db, int scale_d) {
  asm volatile("{\n.reg .pred p;\nsetp.ne.b32 p, %66, 0;\n"
    "wgmma.mma_async.sync.aligned.m64n128k16.f32.bf16.bf16 {%0, %1, %2, %3, %4, %5, %6, %7, %8, %9, %10, %11, %12, %13, %14, %15, %16, %17, %18, %19, %20, %21, %22, %23, %24, %25, %26, %27, %28, %29, %30, %31, %32, %33, %34, %35, %36, %37, %38, %39, %40, %41, %42, %43, %44, %45, %46, %47, %48, %49, %50, %51, %52, %53, %54, %55, %56, %57, %58, %59, %60, %61, %62, %63}, %64, %65, p, 1, 1, 0, 1;\n}\n"
    : "+f"(d[0]), "+f"(d[1]), "+f"(d[2]), "+f"(d[3]), "+f"(d[4]), "+f"(d[5]), "+f"(d[6]), "+f"(d[7]), "+f"(d[8]), "+f"(d[9]), "+f"(d[10]), "+f"(d[11]), "+f"(d[12]), "+f"(d[13]), "+f"(d[14]), "+f"(d[15]), "+f"(d[16]), "+f"(d[17]), "+f"(d[18]), "+f"(d[19]), "+f"(d[20]), "+f"(d[21]), "+f"(d[22]), "+f"(d[23]), "+f"(d[24]), "+f"(d[25]), "+f"(d[26]), "+f"(d[27]), "+f"(d[28]), "+f"(d[29]), "+f"(d[30]), "+f"(d[31]), "+f"(d[32]), "+f"(d[33]), "+f"(d[34]), "+f"(d[35]), "+f"(d[36]), "+f"(d[37]), "+f"(d[38]), "+f"(d[39]), "+f"(d[40]), "+f"(d[41]), "+f"(d[42]), "+f"(d[43]), "+f"(d[44]), "+f"(d[45]), "+f"(d[46]), "+f"(d[47]), "+f"(d[48]), "+f"(d[49]), "+f"(d[50]), "+f"(d[51]), "+f"(d[52]), "+f"(d[53]), "+f"(d[54]), "+f"(d[55]), "+f"(d[56]), "+f"(d[57]), "+f"(d[58]), "+f"(d[59]), "+f"(d[60]), "+f"(d[61]), "+f"(d[62]), "+f"(d[63])
    : "l"(da), "l"(db), "r"(scale_d));
}

__device__ __forceinline__ void wgmma_rs_n128(float (&d)[64], uint32_t a0, uint32_t a1, uint32_t a2, uint32_t a3, uint64_t db, int scale_d) {
  asm volatile("{\n.reg .pred p;\nsetp.ne.b32 p, %69, 0;\n"
    "wgmma.mma_async.sync.aligned.m64n128k16.f32.bf16.bf16 {%0, %1, %2, %3, %4, %5, %6, %7, %8, %9, %10, %11, %12, %13, %14, %15, %16, %17, %18, %19, %20, %21, %22, %23, %24, %25, %26, %27, %28, %29, %30, %31, %32, %33, %34, %35, %36, %37, %38, %39, %40, %41, %42, %43, %44, %45, %46, %47, %48, %49, %50, %51, %52, %53, %54, %55, %56, %57, %58, %59, %60, %61, %62, %63}, {%64, %65, %66, %67}, %68, p, 1, 1, 0;\n}\n"
    : "+f"(d[0]), "+f"(d[1]), "+f"(d[2]), "+f"(d[3]), "+f"(d[4]), "+f"(d[5]), "+f"(d[6]), "+f"(d[7]), "+f"(d[8]), "+f"(d[9]), "+f"(d[10]), "+f"(d[11]), "+f"(d[12]), "+f"(d[13]), "+f"(d[14]), "+f"(d[15]), "+f"(d[16]), "+f"(d[17]), "+f"(d[18]), "+f"(d[19]), "+f"(d[20]), "+f"(d[21]), "+f"(d[22]), "+f"(d[23]), "+f"(d[24]), "+f"(d[25]), "+f"(d[26]), "+f"(d[27]), "+f"(d[28]), "+f"(d[29]), "+f"(d[30]), "+f"(d[31]), "+f"(d[32]), "+f"(d[33]), "+f"(d[34]), "+f"(d[35]), "+f"(d[36]), "+f"(d[37]), "+f"(d[38]), "+f"(d[39]), "+f"(d[40]), "+f"(d[41]), "+f"(d[42]), "+f"(d[43]), "+f"(d[44]), "+f"(d[45]), "+f"(d[46]), "+f"(d[47]), "+f"(d[48]), "+f"(d[49]), "+f"(d[50]), "+f"(d[51]), "+f"(d[52]), "+f"(d[53]), "+f"(d[54]), "+f"(d[55]), "+f"(d[56]), "+f"(d[57]), "+f"(d[58]), "+f"(d[59]), "+f"(d[60]), "+f"(d[61]), "+f"(d[62]), "+f"(d[63])
    : "r"(a0), "r"(a1), "r"(a2), "r"(a3), "l"(db), "r"(scale_d));
}

__device__ __forceinline__ void wgmma_rs_n128_tb(float (&d)[64], uint32_t a0, uint32_t a1, uint32_t a2, uint32_t a3, uint64_t db, int scale_d) {
  asm volatile("{\n.reg .pred p;\nsetp.ne.b32 p, %69, 0;\n"
    "wgmma.mma_async.sync.aligned.m64n128k16.f32.bf16.bf16 {%0, %1, %2, %3, %4, %5, %6, %7, %8, %9, %10, %11, %12, %13, %14, %15, %16, %17, %18, %19, %20, %21, %22, %23, %24, %25, %26, %27, %28, %29, %30, %31, %32, %33, %34, %35, %36, %37, %38, %39, %40, %41, %42, %43, %44, %45, %46, %47, %48, %49, %50, %51, %52, %53, %54, %55, %56, %57, %58, %59, %60, %61, %62, %63}, {%64, %65, %66, %67}, %68, p, 1, 1, 1;\n}\n"
    : "+f"(d[0]), "+f"(d[1]), "+f"(d[2]), "+f"(d[3]), "+f"(d[4]), "+f"(d[5]), "+f"(d[6]), "+f"(d[7]), "+f"(d[8]), "+f"(d[9]), "+f"(d[10]), "+f"(d[11]), "+f"(d[12]), "+f"(d[13]), "+f"(d[14]), "+f"(d[15]), "+f"(d[16]), "+f"(d[17]), "+f"(d[18]), "+f"(d[19]), "+f"(d[20]), "+f"(d[21]), "+f"(d[22]), "+f"(d[23]), "+f"(d[24]), "+f"(d[25]), "+f"(d[26]), "+f"(d[27]), "+f"(d[28]), "+f"(d[29]), "+f"(d[30]), "+f"(d[31]), "+f"(d[32]), "+f"(d[33]), "+f"(d[34]), "+f"(d[35]), "+f"(d[36]), "+f"(d[37]), "+f"(d[38]), "+f"(d[39]), "+f"(d[40]), "+f"(d[41]), "+f"(d[42]), "+f"(d[43]), "+f"(d[44]), "+f"(d[45]), "+f"(d[46]), "+f"(d[47]), "+f"(d[48]), "+f"(d[49]), "+f"(d[50]), "+f"(d[51]), "+f"(d[52]), "+f"(d[53]), "+f"(d[54]), "+f"(d[55]), "+f"(d[56]), "+f"(d[57]), "+f"(d[58]), "+f"(d[59]), "+f"(d[60]), "+f"(d[61]), "+f"(d[62]), "+f"(d[63])
    : "r"(a0), "r"(a1), "r"(a2), "r"(a3), "l"(db), "r"(scale_d));
}

__device__ __forceinline__ void wgmma_rs_n32_tb(float (&d)[16], uint32_t a0, uint32_t a1, uint32_t a2, uint32_t a3, uint64_t db, int scale_d) {
  asm volatile("{\n.reg .pred p;\nsetp.ne.b32 p, %21, 0;\n"
    "wgmma.mma_async.sync.aligned.m64n32k16.f32.bf16.bf16 {%0, %1, %2, %3, %4, %5, %6, %7, %8, %9, %10, %11, %12, %13, %14, %15}, {%16, %17, %18, %19}, %20, p, 1, 1, 1;\n}\n"
    : "+f"(d[0]), "+f"(d[1]), "+f"(d[2]), "+f"(d[3]), "+f"(d[4]), "+f"(d[5]), "+f"(d[6]), "+f"(d[7]), "+f"(d[8]), "+f"(d[9]), "+f"(d[10]), "+f"(d[11]), "+f"(d[12]), "+f"(d[13]), "+f"(d[14]), "+f"(d[15])
    : "r"(a0), "r"(a1), "r"(a2), "r"(a3), "l"(db), "r"(scale_d));
}

struct Maps {
  CUtensorMap x[2], k[2], v[2], wq[2], wo[2];
};

__global__ void __cluster_dims__(2, 1, 1) __launch_bounds__(384, 1)
fused_gqa_kernel(const __grid_constant__ Maps maps, __nv_bfloat16* __restrict__ out) {
  extern __shared__ __align__(1024) unsigned char smem[];
  const uint32_t sbase = smem_u32(smem);
  const uint32_t full0 = sbase + BAR_OFF;
  const uint32_t empty0 = full0 + N_ITEMS * 8;
  const uint32_t ready0 = empty0 + N_ITEMS * 8;

  const int tid = threadIdx.x;
  const int wg = tid >> 7;
  const int bid = blockIdx.x;
  const int r = bid & 1;
  const int bp = (bid >> 1) & 3;
  const int j = (bid >> 3) & 7;
  const int p = bid >> 6;
  const int b = bp * 2 + r;
  const int kvrow0 = (b * 16 + 2 * j) * kSK;

  if (tid == 96) {
#pragma unroll
    for (int n = 0; n < 3; n++) mbar_init(full0 + (KV0 + n) * 8, 1);
    asm volatile("fence.mbarrier_init.release.cluster;" ::: "memory");
#pragma unroll
    for (int n = 0; n < 3; n++) {
      const uint32_t fb = full0 + (KV0 + n) * 8;
      const uint32_t dst = sbase + KV_OFF + n * KV_BYTES;
      const CUtensorMap* tm = (n & 1) ? &maps.v[p] : &maps.k[p];
      mbar_expect_tx(fb, KV_BYTES);
      tma_load(dst, tm, 0, kvrow0 + (n >> 1) * 128, fb);
      tma_load(dst + 16384, tm, 64, kvrow0 + (n >> 1) * 128, fb);
    }
    TR(0, 59);
  } else if (tid == 0) {
    prefetch_tmap(&maps.x[p]);
    prefetch_tmap(&maps.wq[p]);
    prefetch_tmap(&maps.wo[p]);
  } else if (tid >= 128) {
    const int i = tid - 128;
    if (i < N_ITEMS) {
      if (i < KV0 || i >= KV0 + 3) mbar_init(full0 + i * 8, 1);
    } else if (i >= 64 && i < 64 + N_ITEMS) {
      const int e = i - 64;
      const bool local_only = (e >= KV0 && e < WO0 && e != KV0 + 13 && e != KV0 + 14);
      mbar_init(empty0 + e * 8, local_only ? 8 : 16);
    } else if (i >= 128 && i < 128 + 6) {
      mbar_init(ready0 + (i - 128) * 8, 1);
    }
    asm volatile("fence.mbarrier_init.release.cluster;" ::: "memory");
  }
  __syncwarp();
  cluster_arrive_relaxed();
  cluster_wait();
  if (tid == 0) TR(0, 57);

  if (wg == 0) {
    asm volatile("setmaxnreg.dec.sync.aligned.u32 24;");
    if (tid == 0) {
      const CUtensorMap* tmx = &maps.x[p];
      const CUtensorMap* tmq = &maps.wq[p];
      const CUtensorMap* tmo = &maps.wo[p];
#pragma unroll 1
      for (int q = 0; q < N_QW; q++) {
        const int hh = q >= 9 ? 1 : 0, kc = q - hh * 9;
        const int col = (2 * j + hh) * 256 + r * 128;
        if (q >= 2) mbar_wait(empty0 + (QW0 + q - 2) * 8);
        const uint32_t fb = full0 + (QW0 + q) * 8;
        const uint32_t dst = sbase + qw_off(q);
        TR(0, QW0 + q);
        mbar_expect_tx(fb, QW_BYTES);
        tma_load_mc(dst + 8192 + r * 16384, tmq, col, kc * 64, fb, 3);
        tma_load_mc(dst + 16384 + r * 16384, tmq, col + 64, kc * 64, fb, 3);
        tma_load(dst, tmx, kc * 64, b * 64, fb);
      }
#pragma unroll 1
      for (int m = 0; m < N_WO; m++) {
        const int dep = m >= 5 ? WO0 + m - 5 : (m == 0 ? QW0 + 16 : (m < 3 ? QW0 + 17 : KV0 + 10 + m));
        mbar_wait(empty0 + dep * 8);
        const uint32_t fb = full0 + (WO0 + m) * 8;
        const uint32_t dst = sbase + wo_off(m) + r * 16384;
        TR(0, WO0 + m);
        mbar_expect_tx(fb, WO_BYTES);
        if (m < 16) {
          const int pn = m >> 3, kc = m & 7;
          tma_load_mc(dst, tmo, pn * 256 + r * 128, j * 512 + kc * 64, fb, 3);
          tma_load_mc(dst + 8192, tmo, pn * 256 + r * 128 + 64, j * 512 + kc * 64, fb, 3);
        } else {
          const int kh = m - 16;
          tma_load_mc(dst, tmo, 512, j * 512 + kh * 256 + r * 128, fb, 3);
          tma_load_mc(dst + 8192, tmo, 512, j * 512 + kh * 256 + r * 128 + 64, fb, 3);
        }
      }
    } else if (tid == 96) {
#pragma unroll 1
      for (int n = 3; n < N_KV; n++) {
        mbar_wait(empty0 + (KV0 + n - 3) * 8);
        const uint32_t fb = full0 + (KV0 + n) * 8;
        const uint32_t dst = sbase + kv_off(n);
        const CUtensorMap* tm = (n & 1) ? &maps.v[p] : &maps.k[p];
        TR(0, KV0 + n);
        mbar_expect_tx(fb, KV_BYTES);
        tma_load(dst, tm, 0, kvrow0 + (n >> 1) * 128, fb);
        tma_load(dst + 16384, tm, 64, kvrow0 + (n >> 1) * 128, fb);
      }
    } else if (tid >= 32 && tid < 96) {
      const int w = (tid >> 5) - 1;
      const int tile = p * 8 + b;
      unsigned target[3];
#pragma unroll
      for (int pn = 0; pn < 3; pn++) {
        unsigned v;
        asm volatile("ld.relaxed.gpu.global.u32 %0, [%1];" : "=r"(v) : "l"(&g_cnt[(tile * 4 + pn) * 32]) : "memory");
        target[pn] = (v / 16u + 1u) * 16u;
      }
#pragma unroll
      for (int pn = 0; pn < 3; pn++) {
        named_bar(2 + w, 160);
        if ((tid & 31) == 0) {
          __threadfence();
          asm volatile("red.relaxed.gpu.global.add.u32 [%0], 1;" ::"l"(&g_cnt[(tile * 4 + pn) * 32]) : "memory");
        }
        __syncwarp();
      }
      if ((tid & 31) == 0) {
#pragma unroll
        for (int pn = 0; pn < 3; pn++) {
          const unsigned* c = &g_cnt[(tile * 4 + pn) * 32];
          for (uint32_t it = 0; it < 4 * WAIT_LIMIT; ++it) {
            unsigned v;
            asm volatile("ld.acquire.gpu.global.u32 %0, [%1];" : "=r"(v) : "l"(c) : "memory");
            if ((int)(v - target[pn]) >= 0) break;
          }
          mbar_arrive(ready0 + (w * 3 + pn) * 8);
        }
      }
    }
  } else {
    asm volatile("setmaxnreg.inc.sync.aligned.u32 240;");
    const int w = wg - 1;
    const int t128 = tid & 127;
    const int lane = tid & 31;
    const uint32_t peer = r ^ 1;

    auto release = [&](int item, bool remote) {
      __syncwarp();
      if (lane == 0) {
        mbar_arrive(empty0 + item * 8);
        if (remote) mbar_arrive_remote(empty0 + item * 8, peer);
      }
    };

    TRC(0);
    const float cs = 0.08838834764831845f * 1.4426950408889634f;
    float s[64];
#pragma unroll
    for (int i = 0; i < 64; i++) s[i] = 0.f;
#pragma unroll 1
    for (int hh = 0; hh < 2; hh++) {
      uint32_t qf[32];
      {
        float(&acc)[64] = s;
#pragma unroll 1
        for (int kc = 0; kc < 9; kc++) {
          const int q = hh * 9 + kc;
          const uint32_t base = sbase + qw_off(q);
          mbar_wait(full0 + (QW0 + q) * 8);
          if (q == 0) TRC(1);
          const uint64_t da = make_desc(base, 16, 1024);
          const uint64_t db = make_desc(base + 8192 + w * 16384, 8192, 1024);
          wg_fence();
#pragma unroll
          for (int ks = 0; ks < 4; ks++) wgmma_ss_n128_tb(acc, da + ks * 2, db + ks * 128, (kc | ks) != 0);
          wg_commit();
          wg_wait<0>();
          release(QW0 + q, true);
        }
        fence_regs(acc);
#pragma unroll
        for (int i = 0; i < 32; i++) qf[i] = pack_bf16(acc[2 * i], acc[2 * i + 1]);
        TRC(2 + hh * 5);
      }
      float o[64];
#pragma unroll
      for (int i = 0; i < 64; i++) o[i] = 0.f;
      float m0 = -INFINITY, m1 = -INFINITY, l0 = 0.f, l1 = 0.f;
#pragma unroll 1
      for (int t = 0; t < 4; t++) {
        const int n = hh * 8 + t * 2;
        {
          const uint32_t base = sbase + kv_off(n);
          mbar_wait(full0 + (KV0 + n) * 8);
          if (t == 0 && w == 1) named_bar(4, 256);
          const uint64_t db = make_desc(base, 16, 1024);
          wg_fence();
#pragma unroll
          for (int ks = 0; ks < 8; ks++)
            wgmma_rs_n128(s, qf[4 * ks], qf[4 * ks + 1], qf[4 * ks + 2], qf[4 * ks + 3], db + (ks >> 2) * 1024 + (ks & 3) * 2,
                          ks != 0);
          wg_commit();
          wg_wait<0>();
          fence_regs(s);
          if (t == 0 && w == 0) named_arrive(4, 256);
          release(KV0 + n, n == 14);
        }
        float mx0 = s[0], mx1 = s[2];
#pragma unroll
        for (int g = 0; g < 16; g++) {
          mx0 = fmaxf(mx0, fmaxf(s[4 * g], s[4 * g + 1]));
          mx1 = fmaxf(mx1, fmaxf(s[4 * g + 2], s[4 * g + 3]));
        }
        mx0 = fmaxf(mx0, __shfl_xor_sync(0xffffffffu, mx0, 1));
        mx0 = fmaxf(mx0, __shfl_xor_sync(0xffffffffu, mx0, 2));
        mx1 = fmaxf(mx1, __shfl_xor_sync(0xffffffffu, mx1, 1));
        mx1 = fmaxf(mx1, __shfl_xor_sync(0xffffffffu, mx1, 2));
        const float mn0 = fmaxf(m0, mx0), mn1 = fmaxf(m1, mx1);
        const float a0 = ex2((m0 - mn0) * cs), a1 = ex2((m1 - mn1) * cs);
        m0 = mn0;
        m1 = mn1;
        const float ms0 = mn0 * cs, ms1 = mn1 * cs;
        float rs0 = 0.f, rs1 = 0.f;
        uint32_t pf[32];
#pragma unroll
        for (int g = 0; g < 16; g++) {
          const float p0 = ex2(fmaf(s[4 * g], cs, -ms0));
          const float p1 = ex2(fmaf(s[4 * g + 1], cs, -ms0));
          const float p2 = ex2(fmaf(s[4 * g + 2], cs, -ms1));
          const float p3 = ex2(fmaf(s[4 * g + 3], cs, -ms1));
          rs0 += p0 + p1;
          rs1 += p2 + p3;
          pf[2 * g] = pack_bf16(p0, p1);
          pf[2 * g + 1] = pack_bf16(p2, p3);
        }
        l0 = l0 * a0 + rs0;
        l1 = l1 * a1 + rs1;
#pragma unroll
        for (int g = 0; g < 16; g++) {
          o[4 * g] *= a0;
          o[4 * g + 1] *= a0;
          o[4 * g + 2] *= a1;
          o[4 * g + 3] *= a1;
        }
        {
          const uint32_t base = sbase + kv_off(n + 1);
          mbar_wait(full0 + (KV0 + n + 1) * 8);
          const uint64_t db = make_desc(base, 16384, 1024);
          wg_fence();
#pragma unroll
          for (int ks = 0; ks < 8; ks++)
            wgmma_rs_n128_tb(o, pf[4 * ks], pf[4 * ks + 1], pf[4 * ks + 2], pf[4 * ks + 3], db + ks * 128, 1);
          wg_commit();
          wg_wait<0>();
          fence_regs(o);
          release(KV0 + n + 1, n + 1 == 13);
          TRC(3 + hh * 5 + t);
        }
      }
      l0 += __shfl_xor_sync(0xffffffffu, l0, 1);
      l0 += __shfl_xor_sync(0xffffffffu, l0, 2);
      l1 += __shfl_xor_sync(0xffffffffu, l1, 1);
      l1 += __shfl_xor_sync(0xffffffffu, l1, 2);
      const float i0 = 1.f / l0, i1 = 1.f / l1;
      if (hh == 1) named_bar(1, 256);
      uint4* ob = reinterpret_cast<uint4*>(smem + (hh == 0 ? OPARK_OFF : KV_OFF)) + w * 1024 + t128;
#pragma unroll
      for (int i = 0; i < 8; i++) {
        uint4 v;
        v.x = pack_bf16(o[8 * i] * i0, o[8 * i + 1] * i0);
        v.y = pack_bf16(o[8 * i + 2] * i1, o[8 * i + 3] * i1);
        v.z = pack_bf16(o[8 * i + 4] * i0, o[8 * i + 5] * i0);
        v.w = pack_bf16(o[8 * i + 6] * i1, o[8 * i + 7] * i1);
        ob[i * 128] = v;
      }
    }
    named_bar(1, 256);
    uint32_t af[128];
    {
      const uint4* ob0 = reinterpret_cast<const uint4*>(smem + OPARK_OFF) + t128;
      const uint4* ob1 = reinterpret_cast<const uint4*>(smem + KV_OFF) + t128;
#pragma unroll
      for (int i = 0; i < 32; i++) {
        uint4 v = i < 16 ? ob0[i * 128] : ob1[(i - 16) * 128];
        af[4 * i] = v.x;
        af[4 * i + 1] = v.y;
        af[4 * i + 2] = v.z;
        af[4 * i + 3] = v.w;
      }
    }
    TRC(12);
    const int tile = p * 8 + b;
    uint4* part = g_part + (size_t)(tile * 8 + j) * 18 * 256 + (w * 128 + t128);
#pragma unroll
    for (int pn = 0; pn < 2; pn++) {
      float(&acc)[64] = s;
#pragma unroll
      for (int kc = 0; kc < 8; kc++) {
        const int m = pn * 8 + kc;
        const uint32_t base = sbase + wo_off(m);
        mbar_wait(full0 + (WO0 + m) * 8);
        const uint64_t db = make_desc(base + w * 16384, 8192, 1024);
        wg_fence();
#pragma unroll
        for (int ks = 0; ks < 4; ks++) {
          const int a = (kc * 4 + ks) * 4;
          wgmma_rs_n128_tb(acc, af[a], af[a + 1], af[a + 2], af[a + 3], db + ks * 128, (kc | ks) != 0);
        }
        wg_commit();
        if (kc > 0) {
          wg_wait<1>();
          if (m - 1 <= 12) release(WO0 + m - 1, true);
        }
      }
      wg_wait<0>();
      fence_regs(acc);
      if (pn == 0) release(WO0 + 7, true);
      TRC(13 + pn * 2);
#pragma unroll
      for (int i = 0; i < 8; i++) {
        uint4 v;
        v.x = pack_bf16(acc[8 * i], acc[8 * i + 1]);
        v.y = pack_bf16(acc[8 * i + 2], acc[8 * i + 3]);
        v.z = pack_bf16(acc[8 * i + 4], acc[8 * i + 5]);
        v.w = pack_bf16(acc[8 * i + 6], acc[8 * i + 7]);
        __stcg(part + (pn * 8 + i) * 256, v);
      }
      named_arrive(2 + w, 160);
      TRC(14 + pn * 2);
    }
    {
      float acc[16];
#pragma unroll
      for (int i = 0; i < 16; i++) acc[i] = 0.f;
#pragma unroll
      for (int kh = 0; kh < 2; kh++) {
        const int m = 16 + kh;
        const uint32_t base = sbase + wo_off(m);
        mbar_wait(full0 + (WO0 + m) * 8);
        const uint64_t db = make_desc(base + w * 64, 8192, 1024);
        wg_fence();
#pragma unroll
        for (int ks = 0; ks < 16; ks++) {
          const int a = (kh * 16 + ks) * 4;
          wgmma_rs_n32_tb(acc, af[a], af[a + 1], af[a + 2], af[a + 3], db + ks * 128, (kh | ks) != 0);
        }
        wg_commit();
      }
      wg_wait<0>();
      fence_regs(acc);
#pragma unroll
      for (int i = 0; i < 2; i++) {
        uint4 v;
        v.x = pack_bf16(acc[8 * i], acc[8 * i + 1]);
        v.y = pack_bf16(acc[8 * i + 2], acc[8 * i + 3]);
        v.z = pack_bf16(acc[8 * i + 4], acc[8 * i + 5]);
        v.w = pack_bf16(acc[8 * i + 6], acc[8 * i + 7]);
        __stcg(part + (16 + i) * 256, v);
      }
      named_arrive(2 + w, 160);
      TRC(17);
    }
    const int row0 = (t128 >> 5) * 16 + (lane >> 2);
    const int q2 = (lane & 3) * 2;
    __nv_bfloat16* orow = out + (size_t)(b * 64 + row0) * 1152 + p * 576;
    const uint4* pr = g_part + (size_t)(tile * 8) * 18 * 256 + (w * 128 + t128);
#pragma unroll
    for (int pn = 0; pn < 3; pn++) {
      mbar_wait(ready0 + (w * 3 + pn) * 8);
      TRC(18 + pn);
      int slot, col;
      bool active = true;
      if (pn < 2) {
        slot = pn * 8 + j;
        col = pn * 256 + w * 128 + j * 16 + q2;
      } else {
        slot = 16 + (j & 1);
        col = 512 + w * 32 + (j & 1) * 16 + q2;
        active = (((w * 128 + t128) >> 6) == (j >> 1));
      }
      if (active) {
        uint4 v[8];
#pragma unroll
        for (int c = 0; c < 8; c++) v[c] = __ldcg(pr + (size_t)(c * 18 + slot) * 256);
        float a[8];
#pragma unroll
        for (int e = 0; e < 8; e++) a[e] = 0.f;
#pragma unroll
        for (int c = 0; c < 8; c++) {
          a[0] += bf_lo(v[c].x);
          a[1] += bf_hi(v[c].x);
          a[2] += bf_lo(v[c].y);
          a[3] += bf_hi(v[c].y);
          a[4] += bf_lo(v[c].z);
          a[5] += bf_hi(v[c].z);
          a[6] += bf_lo(v[c].w);
          a[7] += bf_hi(v[c].w);
        }
        *reinterpret_cast<uint32_t*>(orow + col) = pack_bf16(a[0], a[1]);
        *reinterpret_cast<uint32_t*>(orow + 8 * 1152 + col) = pack_bf16(a[2], a[3]);
        *reinterpret_cast<uint32_t*>(orow + col + 8) = pack_bf16(a[4], a[5]);
        *reinterpret_cast<uint32_t*>(orow + 8 * 1152 + col + 8) = pack_bf16(a[6], a[7]);
      }
    }
    TRC(21);
    TRC(22);
  }
}

typedef CUresult (*EncodeFn)(CUtensorMap*, CUtensorMapDataType, cuuint32_t, void*, const cuuint64_t*, const cuuint64_t*,
                             const cuuint32_t*, const cuuint32_t*, CUtensorMapInterleave, CUtensorMapSwizzle,
                             CUtensorMapL2promotion, CUtensorMapFloatOOBfill);

void encode2d(EncodeFn fn, CUtensorMap* m, void* ptr, uint64_t cols, uint64_t rows, uint32_t box_cols, uint32_t box_rows) {
  cuuint64_t dims[2] = {cols, rows};
  cuuint64_t strides[1] = {cols * 2};
  cuuint32_t box[2] = {box_cols, box_rows};
  cuuint32_t es[2] = {1, 1};
  fn(m, CU_TENSOR_MAP_DATA_TYPE_BFLOAT16, 2, ptr, dims, strides, box, es, CU_TENSOR_MAP_INTERLEAVE_NONE,
     CU_TENSOR_MAP_SWIZZLE_128B, CU_TENSOR_MAP_L2_PROMOTION_L2_256B, CU_TENSOR_MAP_FLOAT_OOB_FILL_NONE);
}

}

extern "C" void kernel_launch(void* const* d_in, const int* in_sizes, int n_in, void* d_out, int out_size) {
  static EncodeFn fn = nullptr;
  if (!fn) {
    void* f = nullptr;
    cudaDriverEntryPointQueryResult st;
    cudaGetDriverEntryPoint("cuTensorMapEncodeTiled", &f, cudaEnableDefault, &st);
    fn = (EncodeFn)f;
    cudaFuncSetAttribute(fused_gqa_kernel, cudaFuncAttributeMaxDynamicSharedMemorySize, SMEM_BYTES);
  }
  Maps maps;
  for (int p = 0; p < 2; p++) {
    encode2d(fn, &maps.x[p], d_in[p * 5 + 0], kD, 512, 64, 64);
    encode2d(fn, &maps.k[p], d_in[p * 5 + 1], kDH, 8 * 16 * kSK, 64, 128);
    encode2d(fn, &maps.v[p], d_in[p * 5 + 2], kDH, 8 * 16 * kSK, 64, 128);
    encode2d(fn, &maps.wq[p], d_in[p * 5 + 3], kHQD, kD, 64, 64);
    encode2d(fn, &maps.wo[p], d_in[p * 5 + 4], kD, kHQD, 64, 64);
  }
  fused_gqa_kernel<<<128, 384, SMEM_BYTES>>>(maps, (__nv_bfloat16*)d_out);
}
```

```cpp
#include <cuda_runtime.h>
#include <cuda_bf16.h>
#include <cuda.h>
#include <stdint.h>

namespace {

constexpr int kD = 576, kHQD = 4096, kSK = 512, kDH = 128;

constexpr int N_W = 36, N_KV = 16;
constexpr int N_ITEMS = N_W + N_KV;
constexpr int QW_BYTES = 40 * 1024;
constexpr int KV_BYTES = 32 * 1024;
constexpr int WO_BYTES = 32 * 1024;
constexpr int KV_OFF = 128 * 1024;
constexpr int BAR_OFF = 224 * 1024;
constexpr int SMEM_BYTES = BAR_OFF + 2 * N_ITEMS * 8 + 256;
constexpr int W0 = 0, KV0 = N_W;
#define KV_INFLIGHT 2
#define W_PF 6

__device__ __forceinline__ int qw_off(int kc) { return (kc % 3) * QW_BYTES; }
__device__ __forceinline__ int wo_off(int m) { return (m & 3) * WO_BYTES; }
__device__ __forceinline__ int kv_off(int n) { return KV_OFF + (n % 3) * KV_BYTES; }
__device__ __forceinline__ int w_dep(int i) {
  const int hh = i >= 18 ? 1 : 0, q = i - hh * 18;
  if (q < 9) {
    if (q >= 3) return i - 3;
    if (hh == 0) return -1;
    return q == 0 ? 9 + 8 : (q == 1 ? 9 + 6 : 9 + 7);
  }
  const int m = q - 9;
  if (m >= 4) return i - 4;
  return hh * 18 + (m == 0 ? 6 : (m == 1 ? 7 : 8));
}

__device__ uint4 g_part[16 * 16 * 18 * 256];
__device__ unsigned int g_cnt[16 * 4 * 32];

#define TR(role, ev)
#define TRC(ev)
constexpr uint32_t WAIT_CYCLES = 1u << 20;
constexpr uint32_t WAIT_LIMIT = 1u << 10;
__device__ __forceinline__ uint32_t smem_u32(const void* p) { return (uint32_t)__cvta_generic_to_shared(p); }
__device__ __forceinline__ void mbar_init(uint32_t bar, uint32_t cnt) {
  asm volatile("mbarrier.init.shared::cta.b64 [%0], %1;" ::"r"(bar), "r"(cnt) : "memory");
}
__device__ __forceinline__ void mbar_expect_tx(uint32_t bar, uint32_t bytes) {
  asm volatile("mbarrier.arrive.expect_tx.shared::cta.b64 _, [%0], %1;" ::"r"(bar), "r"(bytes) : "memory");
}
__device__ __forceinline__ void mbar_arrive(uint32_t bar) {
  asm volatile("mbarrier.arrive.shared::cta.b64 _, [%0];" ::"r"(bar) : "memory");
}
__device__ __forceinline__ void mbar_arrive_remote(uint32_t bar, uint32_t cta) {
  asm volatile(
      "{\n.reg .b32 ra;\nmapa.shared::cluster.u32 ra, %0, %1;\n"
      "mbarrier.arrive.shared::cluster.b64 _, [ra];\n}\n" ::"r"(bar), "r"(cta)
      : "memory");
}
__device__ __forceinline__ bool mbar_try(uint32_t bar, uint32_t parity) {
  uint32_t ok;
  asm volatile(
      "{\n.reg .pred p;\nmbarrier.try_wait.parity.shared::cta.b64 p, [%1], %2;\nselp.u32 %0, 1, 0, p;\n}\n"
      : "=r"(ok)
      : "r"(bar), "r"(parity)
      : "memory");
  return ok != 0;
}
__device__ __forceinline__ void mbar_wait(uint32_t bar) {
  if (mbar_try(bar, 0)) return;
  const uint32_t t0 = (uint32_t)clock();
  while (!mbar_try(bar, 0))
    if ((uint32_t)clock() - t0 > WAIT_CYCLES) break;
}
__device__ __forceinline__ void tma_load(uint32_t dst, const CUtensorMap* tm, int c0, int c1, uint32_t bar) {
  asm volatile(
      "cp.async.bulk.tensor.2d.shared::cluster.global.mbarrier::complete_tx::bytes [%0], [%1, {%3, %4}], [%2];" ::"r"(dst),
      "l"(tm), "r"(bar), "r"(c0), "r"(c1)
      : "memory");
}
__device__ __forceinline__ void tma_load_mc(uint32_t dst, const CUtensorMap* tm, int c0, int c1, uint32_t bar, uint16_t mask) {
  asm volatile(
      "cp.async.bulk.tensor.2d.shared::cluster.global.mbarrier::complete_tx::bytes.multicast::cluster [%0], [%1, {%3, %4}], [%2], %5;" ::"r"(dst),
      "l"(tm), "r"(bar), "r"(c0), "r"(c1), "h"(mask)
      : "memory");
}
__device__ __forceinline__ void tma_prefetch(const CUtensorMap* tm, int c0, int c1) {
  asm volatile("cp.async.bulk.prefetch.tensor.2d.L2.global [%0, {%1, %2}];" ::"l"(tm), "r"(c0), "r"(c1) : "memory");
}
__device__ __forceinline__ void prefetch_tmap(const CUtensorMap* tm) {
  asm volatile("prefetch.tensormap [%0];" ::"l"(tm) : "memory");
}
__device__ __forceinline__ void cluster_arrive_relaxed() { asm volatile("barrier.cluster.arrive.relaxed.aligned;" ::: "memory"); }
__device__ __forceinline__ void cluster_wait() { asm volatile("barrier.cluster.wait.acquire.aligned;" ::: "memory"); }
__device__ __forceinline__ void named_bar(int id, int n) { asm volatile("bar.sync %0, %1;" ::"r"(id), "r"(n) : "memory"); }
__device__ __forceinline__ void named_arrive(int id, int n) { asm volatile("bar.arrive %0, %1;" ::"r"(id), "r"(n) : "memory"); }
__device__ __forceinline__ void wg_fence() { asm volatile("wgmma.fence.sync.aligned;" ::: "memory"); }
__device__ __forceinline__ void wg_commit() { asm volatile("wgmma.commit_group.sync.aligned;" ::: "memory"); }
template <int N>
__device__ __forceinline__ void wg_wait() { asm volatile("wgmma.wait_group.sync.aligned %0;" ::"n"(N) : "memory"); }
template <int N>
__device__ __forceinline__ void fence_regs(float (&d)[N]) {
#pragma unroll
  for (int i = 0; i < N; i++) asm volatile("" : "+f"(d[i])::"memory");
}
__device__ __forceinline__ uint64_t make_desc(uint32_t addr, uint32_t lbo, uint32_t sbo) {
  return (uint64_t)((addr & 0x3FFFF) >> 4) | ((uint64_t)(lbo >> 4) << 16) | ((uint64_t)(sbo >> 4) << 32) | (1ull << 62);
}
__device__ __forceinline__ uint32_t pack_bf16(float lo, float hi) {
  uint32_t r;
  asm("cvt.rn.bf16x2.f32 %0, %1, %2;" : "=r"(r) : "f"(hi), "f"(lo));
  return r;
}
__device__ __forceinline__ float ex2(float x) {
  float y;
  asm("ex2.approx.ftz.f32 %0, %1;" : "=f"(y) : "f"(x));
  return y;
}
__device__ __forceinline__ float bf_lo(uint32_t v) { return __uint_as_float(v << 16); }
__device__ __forceinline__ float bf_hi(uint32_t v) { return __uint_as_float(v & 0xffff0000u); }

__device__ __forceinline__ void wgmma_ss_n128_tb(float (&d)[64], uint64_t da, uint64_t db, int scale_d) {
  asm volatile("{\n.reg .pred p;\nsetp.ne.b32 p, %66, 0;\n"
    "wgmma.mma_async.sync.aligned.m64n128k16.f32.bf16.bf16 {%0, %1, %2, %3, %4, %5, %6, %7, %8, %9, %10, %11, %12, %13, %14, %15, %16, %17, %18, %19, %20, %21, %22, %23, %24, %25, %26, %27, %28, %29, %30, %31, %32, %33, %34, %35, %36, %37, %38, %39, %40, %41, %42, %43, %44, %45, %46, %47, %48, %49, %50, %51, %52, %53, %54, %55, %56, %57, %58, %59, %60, %61, %62, %63}, %64, %65, p, 1, 1, 0, 1;\n}\n"
    : "+f"(d[0]), "+f"(d[1]), "+f"(d[2]), "+f"(d[3]), "+f"(d[4]), "+f"(d[5]), "+f"(d[6]), "+f"(d[7]), "+f"(d[8]), "+f"(d[9]), "+f"(d[10]), "+f"(d[11]), "+f"(d[12]), "+f"(d[13]), "+f"(d[14]), "+f"(d[15]), "+f"(d[16]), "+f"(d[17]), "+f"(d[18]), "+f"(d[19]), "+f"(d[20]), "+f"(d[21]), "+f"(d[22]), "+f"(d[23]), "+f"(d[24]), "+f"(d[25]), "+f"(d[26]), "+f"(d[27]), "+f"(d[28]), "+f"(d[29]), "+f"(d[30]), "+f"(d[31]), "+f"(d[32]), "+f"(d[33]), "+f"(d[34]), "+f"(d[35]), "+f"(d[36]), "+f"(d[37]), "+f"(d[38]), "+f"(d[39]), "+f"(d[40]), "+f"(d[41]), "+f"(d[42]), "+f"(d[43]), "+f"(d[44]), "+f"(d[45]), "+f"(d[46]), "+f"(d[47]), "+f"(d[48]), "+f"(d[49]), "+f"(d[50]), "+f"(d[51]), "+f"(d[52]), "+f"(d[53]), "+f"(d[54]), "+f"(d[55]), "+f"(d[56]), "+f"(d[57]), "+f"(d[58]), "+f"(d[59]), "+f"(d[60]), "+f"(d[61]), "+f"(d[62]), "+f"(d[63])
    : "l"(da), "l"(db), "r"(scale_d));
}

__device__ __forceinline__ void wgmma_rs_n128(float (&d)[64], uint32_t a0, uint32_t a1, uint32_t a2, uint32_t a3, uint64_t db, int scale_d) {
  asm volatile("{\n.reg .pred p;\nsetp.ne.b32 p, %69, 0;\n"
    "wgmma.mma_async.sync.aligned.m64n128k16.f32.bf16.bf16 {%0, %1, %2, %3, %4, %5, %6, %7, %8, %9, %10, %11, %12, %13, %14, %15, %16, %17, %18, %19, %20, %21, %22, %23, %24, %25, %26, %27, %28, %29, %30, %31, %32, %33, %34, %35, %36, %37, %38, %39, %40, %41, %42, %43, %44, %45, %46, %47, %48, %49, %50, %51, %52, %53, %54, %55, %56, %57, %58, %59, %60, %61, %62, %63}, {%64, %65, %66, %67}, %68, p, 1, 1, 0;\n}\n"
    : "+f"(d[0]), "+f"(d[1]), "+f"(d[2]), "+f"(d[3]), "+f"(d[4]), "+f"(d[5]), "+f"(d[6]), "+f"(d[7]), "+f"(d[8]), "+f"(d[9]), "+f"(d[10]), "+f"(d[11]), "+f"(d[12]), "+f"(d[13]), "+f"(d[14]), "+f"(d[15]), "+f"(d[16]), "+f"(d[17]), "+f"(d[18]), "+f"(d[19]), "+f"(d[20]), "+f"(d[21]), "+f"(d[22]), "+f"(d[23]), "+f"(d[24]), "+f"(d[25]), "+f"(d[26]), "+f"(d[27]), "+f"(d[28]), "+f"(d[29]), "+f"(d[30]), "+f"(d[31]), "+f"(d[32]), "+f"(d[33]), "+f"(d[34]), "+f"(d[35]), "+f"(d[36]), "+f"(d[37]), "+f"(d[38]), "+f"(d[39]), "+f"(d[40]), "+f"(d[41]), "+f"(d[42]), "+f"(d[43]), "+f"(d[44]), "+f"(d[45]), "+f"(d[46]), "+f"(d[47]), "+f"(d[48]), "+f"(d[49]), "+f"(d[50]), "+f"(d[51]), "+f"(d[52]), "+f"(d[53]), "+f"(d[54]), "+f"(d[55]), "+f"(d[56]), "+f"(d[57]), "+f"(d[58]), "+f"(d[59]), "+f"(d[60]), "+f"(d[61]), "+f"(d[62]), "+f"(d[63])
    : "r"(a0), "r"(a1), "r"(a2), "r"(a3), "l"(db), "r"(scale_d));
}

__device__ __forceinline__ void wgmma_rs_n128_tb(float (&d)[64], uint32_t a0, uint32_t a1, uint32_t a2, uint32_t a3, uint64_t db, int scale_d) {
  asm volatile("{\n.reg .pred p;\nsetp.ne.b32 p, %69, 0;\n"
    "wgmma.mma_async.sync.aligned.m64n128k16.f32.bf16.bf16 {%0, %1, %2, %3, %4, %5, %6, %7, %8, %9, %10, %11, %12, %13, %14, %15, %16, %17, %18, %19, %20, %21, %22, %23, %24, %25, %26, %27, %28, %29, %30, %31, %32, %33, %34, %35, %36, %37, %38, %39, %40, %41, %42, %43, %44, %45, %46, %47, %48, %49, %50, %51, %52, %53, %54, %55, %56, %57, %58, %59, %60, %61, %62, %63}, {%64, %65, %66, %67}, %68, p, 1, 1, 1;\n}\n"
    : "+f"(d[0]), "+f"(d[1]), "+f"(d[2]), "+f"(d[3]), "+f"(d[4]), "+f"(d[5]), "+f"(d[6]), "+f"(d[7]), "+f"(d[8]), "+f"(d[9]), "+f"(d[10]), "+f"(d[11]), "+f"(d[12]), "+f"(d[13]), "+f"(d[14]), "+f"(d[15]), "+f"(d[16]), "+f"(d[17]), "+f"(d[18]), "+f"(d[19]), "+f"(d[20]), "+f"(d[21]), "+f"(d[22]), "+f"(d[23]), "+f"(d[24]), "+f"(d[25]), "+f"(d[26]), "+f"(d[27]), "+f"(d[28]), "+f"(d[29]), "+f"(d[30]), "+f"(d[31]), "+f"(d[32]), "+f"(d[33]), "+f"(d[34]), "+f"(d[35]), "+f"(d[36]), "+f"(d[37]), "+f"(d[38]), "+f"(d[39]), "+f"(d[40]), "+f"(d[41]), "+f"(d[42]), "+f"(d[43]), "+f"(d[44]), "+f"(d[45]), "+f"(d[46]), "+f"(d[47]), "+f"(d[48]), "+f"(d[49]), "+f"(d[50]), "+f"(d[51]), "+f"(d[52]), "+f"(d[53]), "+f"(d[54]), "+f"(d[55]), "+f"(d[56]), "+f"(d[57]), "+f"(d[58]), "+f"(d[59]), "+f"(d[60]), "+f"(d[61]), "+f"(d[62]), "+f"(d[63])
    : "r"(a0), "r"(a1), "r"(a2), "r"(a3), "l"(db), "r"(scale_d));
}

__device__ __forceinline__ void wgmma_rs_n32_tb(float (&d)[16], uint32_t a0, uint32_t a1, uint32_t a2, uint32_t a3, uint64_t db, int scale_d) {
  asm volatile("{\n.reg .pred p;\nsetp.ne.b32 p, %21, 0;\n"
    "wgmma.mma_async.sync.aligned.m64n32k16.f32.bf16.bf16 {%0, %1, %2, %3, %4, %5, %6, %7, %8, %9, %10, %11, %12, %13, %14, %15}, {%16, %17, %18, %19}, %20, p, 1, 1, 1;\n}\n"
    : "+f"(d[0]), "+f"(d[1]), "+f"(d[2]), "+f"(d[3]), "+f"(d[4]), "+f"(d[5]), "+f"(d[6]), "+f"(d[7]), "+f"(d[8]), "+f"(d[9]), "+f"(d[10]), "+f"(d[11]), "+f"(d[12]), "+f"(d[13]), "+f"(d[14]), "+f"(d[15])
    : "r"(a0), "r"(a1), "r"(a2), "r"(a3), "l"(db), "r"(scale_d));
}

struct Maps {
  CUtensorMap x[2], k[2], v[2], wq[2], wo[2];
};

__device__ __forceinline__ void w_coords(int i, int j, int r, bool& is_q, int& c0a, int& c1a, int& c0b, int& c1b) {
  const int hh = i >= 18 ? 1 : 0, q = i - hh * 18;
  const int h = 2 * j + hh;
  is_q = q < 9;
  if (q < 9) {
    c0a = h * 256 + r * 128; c1a = q * 64; c0b = c0a + 64; c1b = c1a;
  } else if (q < 17) {
    const int m = q - 9;
    c0a = (m >> 2) * 256 + r * 128; c1a = h * 256 + (m & 3) * 64; c0b = c0a + 64; c1b = c1a;
  } else {
    c0a = 512; c1a = h * 256 + r * 128; c0b = 512; c1b = c1a + 64;
  }
}

__global__ void __cluster_dims__(2, 1, 1) __launch_bounds__(384, 1)
fused_gqa_kernel(const __grid_constant__ Maps maps, __nv_bfloat16* __restrict__ out) {
  extern __shared__ __align__(1024) unsigned char smem[];
  const uint32_t sbase = smem_u32(smem);
  const uint32_t full0 = sbase + BAR_OFF;
  const uint32_t empty0 = full0 + N_ITEMS * 8;
  const uint32_t ready0 = empty0 + N_ITEMS * 8;
  const uint32_t pub0 = ready0 + 6 * 8;

  const int tid = threadIdx.x;
  const int wg = tid >> 7;
  const int bid = blockIdx.x;
  const int r = bid & 1;
  const int bp = (bid >> 1) & 3;
  const int j = (bid >> 3) & 7;
  const int p = bid >> 6;
  const int b = bp * 2 + r;
  const int kvrow0 = (b * 16 + 2 * j) * kSK;

  if (tid == 0) {
#pragma unroll 1
    for (int i = 0; i < 9; i++) {
      tma_prefetch(&maps.wq[p], 2 * j * 256 + r * 128, i * 64);
      tma_prefetch(&maps.wq[p], 2 * j * 256 + r * 128 + 64, i * 64);
      tma_prefetch(&maps.x[p], i * 64, b * 64);
    }
    TR(0, 56);
  } else if (tid == 32) {
    prefetch_tmap(&maps.k[p]);
    prefetch_tmap(&maps.v[p]);
    prefetch_tmap(&maps.wo[p]);
  } else if (tid >= 128) {
    const int i = tid - 128;
    if (i < N_ITEMS) {
      mbar_init(full0 + i * 8, 1);
    } else if (i >= 64 && i < 64 + N_ITEMS) {
      const int e = i - 64;
      mbar_init(empty0 + e * 8, e >= KV0 ? 8 : 16);
    } else if (i >= 128 && i < 128 + 6) {
      mbar_init(ready0 + (i - 128) * 8, 1);
    } else if (i >= 160 && i < 160 + 12) {
      mbar_init(pub0 + (i - 160) * 8, 4);
    }
    asm volatile("fence.mbarrier_init.release.cluster;" ::: "memory");
  }
  __syncwarp();
  cluster_arrive_relaxed();
  cluster_wait();
  if (tid == 0) TR(0, 57);

  if (wg == 0) {
    asm volatile("setmaxnreg.dec.sync.aligned.u32 24;");
    if (tid == 0) {
#pragma unroll 1
      for (int i = 0; i < N_W; i++) {
        const int dep = w_dep(i);
        if (dep >= 0) mbar_wait(empty0 + (W0 + dep) * 8);
        bool is_q;
        int c0a, c1a, c0b, c1b;
        w_coords(i, j, r, is_q, c0a, c1a, c0b, c1b);
        const uint32_t fb = full0 + (W0 + i) * 8;
        const int q = i >= 18 ? i - 18 : i;
        TR(0, W0 + i);
        if (is_q) {
          const uint32_t dst = sbase + qw_off(q);
          mbar_expect_tx(fb, QW_BYTES);
          tma_load_mc(dst + 8192 + r * 16384, &maps.wq[p], c0a, c1a, fb, 3);
          tma_load_mc(dst + 16384 + r * 16384, &maps.wq[p], c0b, c1b, fb, 3);
          tma_load(dst, &maps.x[p], q * 64, b * 64, fb);
        } else {
          const uint32_t dst = sbase + wo_off(q - 9) + r * 16384;
          mbar_expect_tx(fb, WO_BYTES);
          tma_load_mc(dst, &maps.wo[p], c0a, c1a, fb, 3);
          tma_load_mc(dst + 8192, &maps.wo[p], c0b, c1b, fb, 3);
        }
        const int ip = i + W_PF;
        if (W_PF > 0 && ip >= 9 && ip < N_W) {
          w_coords(ip, j, r, is_q, c0a, c1a, c0b, c1b);
          const CUtensorMap* tm = is_q ? &maps.wq[p] : &maps.wo[p];
          tma_prefetch(tm, c0a, c1a);
          tma_prefetch(tm, c0b, c1b);
        }
      }
    } else if (tid == 96) {
#pragma unroll 1
      for (int n = 0; n < N_KV; n++) {
        if (n >= 3) mbar_wait(empty0 + (KV0 + n - 3) * 8);
        if (n >= KV_INFLIGHT) mbar_wait(full0 + (KV0 + n - KV_INFLIGHT) * 8);
        const uint32_t fb = full0 + (KV0 + n) * 8;
        const uint32_t dst = sbase + kv_off(n);
        const CUtensorMap* tm = (n & 1) ? &maps.v[p] : &maps.k[p];
        TR(0, KV0 + n);
        mbar_expect_tx(fb, KV_BYTES);
        tma_load(dst, tm, 0, kvrow0 + (n >> 1) * 128, fb);
        tma_load(dst + 16384, tm, 64, kvrow0 + (n >> 1) * 128, fb);
      }
    } else if (tid == 32 || tid == 64) {
      const int w = (tid >> 5) - 1;
      const int tile = p * 8 + b;
      unsigned target[3];
#pragma unroll
      for (int pn = 0; pn < 3; pn++) {
        unsigned v;
        asm volatile("ld.relaxed.gpu.global.u32 %0, [%1];" : "=r"(v) : "l"(&g_cnt[(tile * 4 + pn) * 32]) : "memory");
        target[pn] = (v / 32u + 1u) * 32u;
      }
#pragma unroll 1
      for (int e = 0; e < 6; e++) {
        mbar_wait(pub0 + (w * 6 + e) * 8);
        __threadfence();
        asm volatile("red.relaxed.gpu.global.add.u32 [%0], 1;" ::"l"(&g_cnt[(tile * 4 + (e % 3)) * 32]) : "memory");
      }
#pragma unroll
      for (int pn = 0; pn < 3; pn++) {
        const unsigned* c = &g_cnt[(tile * 4 + pn) * 32];
        for (uint32_t it = 0; it < 4 * WAIT_LIMIT; ++it) {
          unsigned v;
          asm volatile("ld.acquire.gpu.global.u32 %0, [%1];" : "=r"(v) : "l"(c) : "memory");
          if ((int)(v - target[pn]) >= 0) break;
        }
        mbar_arrive(ready0 + (w * 3 + pn) * 8);
      }
    }
  } else {
    asm volatile("setmaxnreg.inc.sync.aligned.u32 240;");
    const int w = wg - 1;
    const int t128 = tid & 127;
    const int lane = tid & 31;
    const uint32_t peer = r ^ 1;
    const int tile = p * 8 + b;

    auto release_w = [&](int item) {
      __syncwarp();
      if (lane == 0 && item < 32) {
        mbar_arrive(empty0 + (W0 + item) * 8);
        mbar_arrive_remote(empty0 + (W0 + item) * 8, peer);
      }
    };
    auto release_kv = [&](int n) {
      __syncwarp();
      if (lane == 0) mbar_arrive(empty0 + (KV0 + n) * 8);
    };

    TRC(0);
    const float cs = 0.08838834764831845f * 1.4426950408889634f;
    float s[64];
#pragma unroll
    for (int i = 0; i < 64; i++) s[i] = 0.f;
#pragma unroll 1
    for (int hh = 0; hh < 2; hh++) {
      uint32_t qf[32];
      {
        float(&acc)[64] = s;
#pragma unroll 1
        for (int kc = 0; kc < 9; kc++) {
          const int i = hh * 18 + kc;
          const uint32_t base = sbase + qw_off(kc);
          mbar_wait(full0 + (W0 + i) * 8);
          if (i == 0) TRC(1);
          const uint64_t da = make_desc(base, 16, 1024);
          const uint64_t db = make_desc(base + 8192 + w * 16384, 8192, 1024);
          wg_fence();
#pragma unroll
          for (int ks = 0; ks < 4; ks++) wgmma_ss_n128_tb(acc, da + ks * 2, db + ks * 128, (kc | ks) != 0);
          wg_commit();
          wg_wait<0>();
          release_w(i);
        }
        fence_regs(acc);
#pragma unroll
        for (int i = 0; i < 32; i++) qf[i] = pack_bf16(acc[2 * i], acc[2 * i + 1]);
        TRC(2 + hh * 10);
      }
      float o[64];
#pragma unroll
      for (int i = 0; i < 64; i++) o[i] = 0.f;
      float m0 = -INFINITY, m1 = -INFINITY, l0 = 0.f, l1 = 0.f;
#pragma unroll 1
      for (int t = 0; t < 4; t++) {
        const int n = hh * 8 + t * 2;
        {
          const uint32_t base = sbase + kv_off(n);
          mbar_wait(full0 + (KV0 + n) * 8);
          if (t == 0 && w == 1) named_bar(4, 256);
          const uint64_t db = make_desc(base, 16, 1024);
          wg_fence();
#pragma unroll
          for (int ks = 0; ks < 8; ks++)
            wgmma_rs_n128(s, qf[4 * ks], qf[4 * ks + 1], qf[4 * ks + 2], qf[4 * ks + 3], db + (ks >> 2) * 1024 + (ks & 3) * 2,
                          ks != 0);
          wg_commit();
          wg_wait<0>();
          fence_regs(s);
          if (t == 0 && w == 0) named_arrive(4, 256);
          release_kv(n);
        }
        float mx0 = s[0], mx1 = s[2];
#pragma unroll
        for (int g = 0; g < 16; g++) {
          mx0 = fmaxf(mx0, fmaxf(s[4 * g], s[4 * g + 1]));
          mx1 = fmaxf(mx1, fmaxf(s[4 * g + 2], s[4 * g + 3]));
        }
        mx0 = fmaxf(mx0, __shfl_xor_sync(0xffffffffu, mx0, 1));
        mx0 = fmaxf(mx0, __shfl_xor_sync(0xffffffffu, mx0, 2));
        mx1 = fmaxf(mx1, __shfl_xor_sync(0xffffffffu, mx1, 1));
        mx1 = fmaxf(mx1, __shfl_xor_sync(0xffffffffu, mx1, 2));
        const float mn0 = fmaxf(m0, mx0), mn1 = fmaxf(m1, mx1);
        const float a0 = ex2((m0 - mn0) * cs), a1 = ex2((m1 - mn1) * cs);
        m0 = mn0;
        m1 = mn1;
        const float ms0 = mn0 * cs, ms1 = mn1 * cs;
        float rs0 = 0.f, rs1 = 0.f;
        uint32_t pf[32];
#pragma unroll
        for (int g = 0; g < 16; g++) {
          const float p0 = ex2(fmaf(s[4 * g], cs, -ms0));
          const float p1 = ex2(fmaf(s[4 * g + 1], cs, -ms0));
          const float p2 = ex2(fmaf(s[4 * g + 2], cs, -ms1));
          const float p3 = ex2(fmaf(s[4 * g + 3], cs, -ms1));
          rs0 += p0 + p1;
          rs1 += p2 + p3;
          pf[2 * g] = pack_bf16(p0, p1);
          pf[2 * g + 1] = pack_bf16(p2, p3);
        }
        l0 = l0 * a0 + rs0;
        l1 = l1 * a1 + rs1;
#pragma unroll
        for (int g = 0; g < 16; g++) {
          o[4 * g] *= a0;
          o[4 * g + 1] *= a0;
          o[4 * g + 2] *= a1;
          o[4 * g + 3] *= a1;
        }
        {
          const uint32_t base = sbase + kv_off(n + 1);
          mbar_wait(full0 + (KV0 + n + 1) * 8);
          const uint64_t db = make_desc(base, 16384, 1024);
          wg_fence();
#pragma unroll
          for (int ks = 0; ks < 8; ks++)
            wgmma_rs_n128_tb(o, pf[4 * ks], pf[4 * ks + 1], pf[4 * ks + 2], pf[4 * ks + 3], db + ks * 128, 1);
          wg_commit();
          wg_wait<0>();
          fence_regs(o);
          if (t < 3) release_kv(n + 1);
          TRC(3 + hh * 10 + t);
        }
      }
      l0 += __shfl_xor_sync(0xffffffffu, l0, 1);
      l0 += __shfl_xor_sync(0xffffffffu, l0, 2);
      l1 += __shfl_xor_sync(0xffffffffu, l1, 1);
      l1 += __shfl_xor_sync(0xffffffffu, l1, 2);
      const float i0 = 1.f / l0, i1 = 1.f / l1;
      uint32_t af[64];
      {
        uint32_t own[32];
#pragma unroll
        for (int i = 0; i < 16; i++) {
          own[2 * i] = pack_bf16(o[4 * i] * i0, o[4 * i + 1] * i0);
          own[2 * i + 1] = pack_bf16(o[4 * i + 2] * i1, o[4 * i + 3] * i1);
        }
        named_bar(1, 256);
        uint4* ob = reinterpret_cast<uint4*>(smem + kv_off(hh * 8 + 7)) + t128;
#pragma unroll
        for (int i = 0; i < 8; i++) ob[(w * 8 + i) * 128] = make_uint4(own[4 * i], own[4 * i + 1], own[4 * i + 2], own[4 * i + 3]);
        named_bar(1, 256);
#pragma unroll
        for (int i = 0; i < 16; i++) {
          const uint4 v = ob[i * 128];
          af[4 * i] = v.x;
          af[4 * i + 1] = v.y;
          af[4 * i + 2] = v.z;
          af[4 * i + 3] = v.w;
        }
        asm volatile("fence.proxy.async.shared::cta;" ::: "memory");
        release_kv(hh * 8 + 7);
      }
      TRC(7 + hh * 10);
      uint4* part = g_part + (size_t)(tile * 16 + j * 2 + hh) * 18 * 256 + (w * 128 + t128);
#pragma unroll
      for (int pn = 0; pn < 2; pn++) {
        float(&acc)[64] = s;
#pragma unroll
        for (int kc = 0; kc < 4; kc++) {
          const int m = pn * 4 + kc;
          const int i = hh * 18 + 9 + m;
          const uint32_t base = sbase + wo_off(m);
          mbar_wait(full0 + (W0 + i) * 8);
          const uint64_t db = make_desc(base + w * 16384, 8192, 1024);
          wg_fence();
#pragma unroll
          for (int ks = 0; ks < 4; ks++) {
            const int a = (kc * 4 + ks) * 4;
            wgmma_rs_n128_tb(acc, af[a], af[a + 1], af[a + 2], af[a + 3], db + ks * 128, (kc | ks) != 0);
          }
          wg_commit();
          if (kc > 0) {
            wg_wait<1>();
            release_w(i - 1);
          }
        }
        wg_wait<0>();
        fence_regs(acc);
        release_w(hh * 18 + 9 + pn * 4 + 3);
        TRC(8 + hh * 10 + pn);
#pragma unroll
        for (int i = 0; i < 8; i++) {
          uint4 v;
          v.x = pack_bf16(acc[8 * i], acc[8 * i + 1]);
          v.y = pack_bf16(acc[8 * i + 2], acc[8 * i + 3]);
          v.z = pack_bf16(acc[8 * i + 4], acc[8 * i + 5]);
          v.w = pack_bf16(acc[8 * i + 6], acc[8 * i + 7]);
          __stcg(part + (pn * 8 + i) * 256, v);
        }
        __syncwarp();
        if (lane == 0) mbar_arrive(pub0 + (w * 6 + hh * 3 + pn) * 8);
      }
      {
        float acc[16];
#pragma unroll
        for (int i = 0; i < 16; i++) acc[i] = 0.f;
        const int i = hh * 18 + 17;
        const uint32_t base = sbase + wo_off(8);
        mbar_wait(full0 + (W0 + i) * 8);
        const uint64_t db = make_desc(base + w * 64, 8192, 1024);
        wg_fence();
#pragma unroll
        for (int ks = 0; ks < 16; ks++)
          wgmma_rs_n32_tb(acc, af[4 * ks], af[4 * ks + 1], af[4 * ks + 2], af[4 * ks + 3], db + ks * 128, ks != 0);
        wg_commit();
        wg_wait<0>();
        fence_regs(acc);
        release_w(i);
#pragma unroll
        for (int e = 0; e < 2; e++) {
          uint4 v;
          v.x = pack_bf16(acc[8 * e], acc[8 * e + 1]);
          v.y = pack_bf16(acc[8 * e + 2], acc[8 * e + 3]);
          v.z = pack_bf16(acc[8 * e + 4], acc[8 * e + 5]);
          v.w = pack_bf16(acc[8 * e + 6], acc[8 * e + 7]);
          __stcg(part + (16 + e) * 256, v);
        }
        __syncwarp();
        if (lane == 0) mbar_arrive(pub0 + (w * 6 + hh * 3 + 2) * 8);
        TRC(10 + hh * 10);
      }
    }
    const int row0 = (t128 >> 5) * 16 + (lane >> 2);
    const int q2 = (lane & 3) * 2;
    __nv_bfloat16* orow = out + (size_t)(b * 64 + row0) * 1152 + p * 576;
    const uint4* pr = g_part + (size_t)(tile * 16) * 18 * 256 + (w * 128 + t128);
#pragma unroll
    for (int pn = 0; pn < 3; pn++) {
      mbar_wait(ready0 + (w * 3 + pn) * 8);
      TRC(21 + pn);
      int slot, col;
      bool active = true;
      if (pn < 2) {
        slot = pn * 8 + j;
        col = pn * 256 + w * 128 + j * 16 + q2;
      } else {
        slot = 16 + (j & 1);
        col = 512 + w * 32 + (j & 1) * 16 + q2;
        active = (((w * 128 + t128) >> 6) == (j >> 1));
      }
      if (active) {
        uint4 v[16];
#pragma unroll
        for (int c = 0; c < 16; c++) v[c] = __ldcg(pr + (size_t)(c * 18 + slot) * 256);
        float a[8];
#pragma unroll
        for (int e = 0; e < 8; e++) a[e] = 0.f;
#pragma unroll
        for (int c = 0; c < 16; c++) {
          a[0] += bf_lo(v[c].x);
          a[1] += bf_hi(v[c].x);
          a[2] += bf_lo(v[c].y);
          a[3] += bf_hi(v[c].y);
          a[4] += bf_lo(v[c].z);
          a[5] += bf_hi(v[c].z);
          a[6] += bf_lo(v[c].w);
          a[7] += bf_hi(v[c].w);
        }
        *reinterpret_cast<uint32_t*>(orow + col) = pack_bf16(a[0], a[1]);
        *reinterpret_cast<uint32_t*>(orow + 8 * 1152 + col) = pack_bf16(a[2], a[3]);
        *reinterpret_cast<uint32_t*>(orow + col + 8) = pack_bf16(a[4], a[5]);
        *reinterpret_cast<uint32_t*>(orow + 8 * 1152 + col + 8) = pack_bf16(a[6], a[7]);
      }
    }
    TRC(24);
  }
}

typedef CUresult (*EncodeFn)(CUtensorMap*, CUtensorMapDataType, cuuint32_t, void*, const cuuint64_t*, const cuuint64_t*,
                             const cuuint32_t*, const cuuint32_t*, CUtensorMapInterleave, CUtensorMapSwizzle,
                             CUtensorMapL2promotion, CUtensorMapFloatOOBfill);

void encode2d(EncodeFn fn, CUtensorMap* m, void* ptr, uint64_t cols, uint64_t rows, uint32_t box_cols, uint32_t box_rows) {
  cuuint64_t dims[2] = {cols, rows};
  cuuint64_t strides[1] = {cols * 2};
  cuuint32_t box[2] = {box_cols, box_rows};
  cuuint32_t es[2] = {1, 1};
  fn(m, CU_TENSOR_MAP_DATA_TYPE_BFLOAT16, 2, ptr, dims, strides, box, es, CU_TENSOR_MAP_INTERLEAVE_NONE,
     CU_TENSOR_MAP_SWIZZLE_128B, CU_TENSOR_MAP_L2_PROMOTION_L2_256B, CU_TENSOR_MAP_FLOAT_OOB_FILL_NONE);
}

}

extern "C" void kernel_launch(void* const* d_in, const int* in_sizes, int n_in, void* d_out, int out_size) {
  static EncodeFn fn = nullptr;
  if (!fn) {
    void* f = nullptr;
    cudaDriverEntryPointQueryResult st;
    cudaGetDriverEntryPoint("cuTensorMapEncodeTiled", &f, cudaEnableDefault, &st);
    fn = (EncodeFn)f;
    cudaFuncSetAttribute(fused_gqa_kernel, cudaFuncAttributeMaxDynamicSharedMemorySize, SMEM_BYTES);
  }
  Maps maps;
  for (int p = 0; p < 2; p++) {
    encode2d(fn, &maps.x[p], d_in[p * 5 + 0], kD, 512, 64, 64);
    encode2d(fn, &maps.k[p], d_in[p * 5 + 1], kDH, 8 * 16 * kSK, 64, 128);
    encode2d(fn, &maps.v[p], d_in[p * 5 + 2], kDH, 8 * 16 * kSK, 64, 128);
    encode2d(fn, &maps.wq[p], d_in[p * 5 + 3], kHQD, kD, 64, 64);
    encode2d(fn, &maps.wo[p], d_in[p * 5 + 4], kD, kHQD, 64, 64);
  }
  fused_gqa_kernel<<<128, 384, SMEM_BYTES>>>(maps, (__nv_bfloat16*)d_out);
}
```

```cpp
#include <cuda_runtime.h>
#include <cuda_bf16.h>
#include <cuda.h>
#include <stdint.h>

namespace {

constexpr int kD = 576, kHQD = 4096, kSK = 512, kDH = 128;

constexpr int N_WQ = 9, N_X = 9, N_KV = 16, N_WO = 9;
constexpr int N_ITEMS = N_WQ + N_X + N_KV + N_WO;
constexpr int T32 = 32 * 1024;
constexpr int KV_OFF = 96 * 1024;
constexpr int PARK_OFF = 192 * 1024;
constexpr int BAR_OFF = 224 * 1024;
constexpr int SMEM_BYTES = BAR_OFF + 2 * N_ITEMS * 8 + 256;
constexpr int WQ0 = 0, X0 = N_WQ, KV0 = X0 + N_X, WO0 = KV0 + N_KV;
#define KV_INFLIGHT 2

__device__ __forceinline__ int wq_off(int kc) { return (kc % 3) * T32; }
__device__ __forceinline__ int x_off(int kc) { return PARK_OFF + (kc & 1) * 16384; }
__device__ __forceinline__ int kv_off(int n) { return KV_OFF + (n % 3) * T32; }
__device__ __forceinline__ int wo_off(int m) {
  const int s = m % 5;
  return (s < 3 ? s : s + 1) * T32;
}

__device__ uint4 g_part[16 * 16 * 36 * 128];
__device__ unsigned int g_cnt[16 * 4 * 32];

#define TR(role, ev)
#define TRC(ev)
constexpr uint32_t WAIT_CYCLES = 1u << 20;
constexpr uint32_t WAIT_LIMIT = 1u << 12;
__device__ __forceinline__ uint32_t smem_u32(const void* p) { return (uint32_t)__cvta_generic_to_shared(p); }
__device__ __forceinline__ void mbar_init(uint32_t bar, uint32_t cnt) {
  asm volatile("mbarrier.init.shared::cta.b64 [%0], %1;" ::"r"(bar), "r"(cnt) : "memory");
}
__device__ __forceinline__ void mbar_expect_tx(uint32_t bar, uint32_t bytes) {
  asm volatile("mbarrier.arrive.expect_tx.shared::cta.b64 _, [%0], %1;" ::"r"(bar), "r"(bytes) : "memory");
}
__device__ __forceinline__ void mbar_arrive(uint32_t bar) {
  asm volatile("mbarrier.arrive.shared::cta.b64 _, [%0];" ::"r"(bar) : "memory");
}
__device__ __forceinline__ bool mbar_try(uint32_t bar, uint32_t parity) {
  uint32_t ok;
  asm volatile(
      "{\n.reg .pred p;\nmbarrier.try_wait.parity.shared::cta.b64 p, [%1], %2;\nselp.u32 %0, 1, 0, p;\n}\n"
      : "=r"(ok)
      : "r"(bar), "r"(parity)
      : "memory");
  return ok != 0;
}
__device__ __forceinline__ void mbar_wait(uint32_t bar) {
  if (mbar_try(bar, 0)) return;
  const uint32_t t0 = (uint32_t)clock();
  while (!mbar_try(bar, 0))
    if ((uint32_t)clock() - t0 > WAIT_CYCLES) break;
}
__device__ __forceinline__ void tma_load3(uint32_t dst, const CUtensorMap* tm, int c0, int c1, int c2, uint32_t bar) {
  asm volatile(
      "cp.async.bulk.tensor.3d.shared::cluster.global.mbarrier::complete_tx::bytes [%0], [%1, {%3, %4, %5}], [%2];" ::"r"(dst),
      "l"(tm), "r"(bar), "r"(c0), "r"(c1), "r"(c2)
      : "memory");
}
__device__ __forceinline__ void prefetch_tmap(const CUtensorMap* tm) {
  asm volatile("prefetch.tensormap [%0];" ::"l"(tm) : "memory");
}
__device__ __forceinline__ void named_bar(int id, int n) { asm volatile("bar.sync %0, %1;" ::"r"(id), "r"(n) : "memory"); }
__device__ __forceinline__ void named_arrive(int id, int n) { asm volatile("bar.arrive %0, %1;" ::"r"(id), "r"(n) : "memory"); }
__device__ __forceinline__ void wg_fence() { asm volatile("wgmma.fence.sync.aligned;" ::: "memory"); }
__device__ __forceinline__ void wg_commit() { asm volatile("wgmma.commit_group.sync.aligned;" ::: "memory"); }
template <int N>
__device__ __forceinline__ void wg_wait() { asm volatile("wgmma.wait_group.sync.aligned %0;" ::"n"(N) : "memory"); }
template <int N>
__device__ __forceinline__ void fence_regs(float (&d)[N]) {
#pragma unroll
  for (int i = 0; i < N; i++) asm volatile("" : "+f"(d[i])::"memory");
}
__device__ __forceinline__ uint64_t make_desc(uint32_t addr, uint32_t lbo, uint32_t sbo) {
  return (uint64_t)((addr & 0x3FFFF) >> 4) | ((uint64_t)(lbo >> 4) << 16) | ((uint64_t)(sbo >> 4) << 32) | (1ull << 62);
}
__device__ __forceinline__ uint32_t pack_bf16(float lo, float hi) {
  uint32_t r;
  asm("cvt.rn.bf16x2.f32 %0, %1, %2;" : "=r"(r) : "f"(hi), "f"(lo));
  return r;
}
__device__ __forceinline__ float ex2(float x) {
  float y;
  asm("ex2.approx.ftz.f32 %0, %1;" : "=f"(y) : "f"(x));
  return y;
}
__device__ __forceinline__ float bf_lo(uint32_t v) { return __uint_as_float(v << 16); }
__device__ __forceinline__ float bf_hi(uint32_t v) { return __uint_as_float(v & 0xffff0000u); }
template <int N>
__device__ __forceinline__ uint4 pack8(const float (&a)[N], int i) {
  return make_uint4(pack_bf16(a[8 * i], a[8 * i + 1]), pack_bf16(a[8 * i + 2], a[8 * i + 3]), pack_bf16(a[8 * i + 4], a[8 * i + 5]),
                    pack_bf16(a[8 * i + 6], a[8 * i + 7]));
}

__device__ __forceinline__ void wgmma_ss_n128_tb(float (&d)[64], uint64_t da, uint64_t db, int scale_d) {
  asm volatile("{\n.reg .pred p;\nsetp.ne.b32 p, %66, 0;\n"
    "wgmma.mma_async.sync.aligned.m64n128k16.f32.bf16.bf16 {%0, %1, %2, %3, %4, %5, %6, %7, %8, %9, %10, %11, %12, %13, %14, %15, %16, %17, %18, %19, %20, %21, %22, %23, %24, %25, %26, %27, %28, %29, %30, %31, %32, %33, %34, %35, %36, %37, %38, %39, %40, %41, %42, %43, %44, %45, %46, %47, %48, %49, %50, %51, %52, %53, %54, %55, %56, %57, %58, %59, %60, %61, %62, %63}, %64, %65, p, 1, 1, 0, 1;\n}\n"
    : "+f"(d[0]), "+f"(d[1]), "+f"(d[2]), "+f"(d[3]), "+f"(d[4]), "+f"(d[5]), "+f"(d[6]), "+f"(d[7]), "+f"(d[8]), "+f"(d[9]), "+f"(d[10]), "+f"(d[11]), "+f"(d[12]), "+f"(d[13]), "+f"(d[14]), "+f"(d[15]), "+f"(d[16]), "+f"(d[17]), "+f"(d[18]), "+f"(d[19]), "+f"(d[20]), "+f"(d[21]), "+f"(d[22]), "+f"(d[23]), "+f"(d[24]), "+f"(d[25]), "+f"(d[26]), "+f"(d[27]), "+f"(d[28]), "+f"(d[29]), "+f"(d[30]), "+f"(d[31]), "+f"(d[32]), "+f"(d[33]), "+f"(d[34]), "+f"(d[35]), "+f"(d[36]), "+f"(d[37]), "+f"(d[38]), "+f"(d[39]), "+f"(d[40]), "+f"(d[41]), "+f"(d[42]), "+f"(d[43]), "+f"(d[44]), "+f"(d[45]), "+f"(d[46]), "+f"(d[47]), "+f"(d[48]), "+f"(d[49]), "+f"(d[50]), "+f"(d[51]), "+f"(d[52]), "+f"(d[53]), "+f"(d[54]), "+f"(d[55]), "+f"(d[56]), "+f"(d[57]), "+f"(d[58]), "+f"(d[59]), "+f"(d[60]), "+f"(d[61]), "+f"(d[62]), "+f"(d[63])
    : "l"(da), "l"(db), "r"(scale_d));
}

__device__ __forceinline__ void wgmma_rs_n128(float (&d)[64], uint32_t a0, uint32_t a1, uint32_t a2, uint32_t a3, uint64_t db, int scale_d) {
  asm volatile("{\n.reg .pred p;\nsetp.ne.b32 p, %69, 0;\n"
    "wgmma.mma_async.sync.aligned.m64n128k16.f32.bf16.bf16 {%0, %1, %2, %3, %4, %5, %6, %7, %8, %9, %10, %11, %12, %13, %14, %15, %16, %17, %18, %19, %20, %21, %22, %23, %24, %25, %26, %27, %28, %29, %30, %31, %32, %33, %34, %35, %36, %37, %38, %39, %40, %41, %42, %43, %44, %45, %46, %47, %48, %49, %50, %51, %52, %53, %54, %55, %56, %57, %58, %59, %60, %61, %62, %63}, {%64, %65, %66, %67}, %68, p, 1, 1, 0;\n}\n"
    : "+f"(d[0]), "+f"(d[1]), "+f"(d[2]), "+f"(d[3]), "+f"(d[4]), "+f"(d[5]), "+f"(d[6]), "+f"(d[7]), "+f"(d[8]), "+f"(d[9]), "+f"(d[10]), "+f"(d[11]), "+f"(d[12]), "+f"(d[13]), "+f"(d[14]), "+f"(d[15]), "+f"(d[16]), "+f"(d[17]), "+f"(d[18]), "+f"(d[19]), "+f"(d[20]), "+f"(d[21]), "+f"(d[22]), "+f"(d[23]), "+f"(d[24]), "+f"(d[25]), "+f"(d[26]), "+f"(d[27]), "+f"(d[28]), "+f"(d[29]), "+f"(d[30]), "+f"(d[31]), "+f"(d[32]), "+f"(d[33]), "+f"(d[34]), "+f"(d[35]), "+f"(d[36]), "+f"(d[37]), "+f"(d[38]), "+f"(d[39]), "+f"(d[40]), "+f"(d[41]), "+f"(d[42]), "+f"(d[43]), "+f"(d[44]), "+f"(d[45]), "+f"(d[46]), "+f"(d[47]), "+f"(d[48]), "+f"(d[49]), "+f"(d[50]), "+f"(d[51]), "+f"(d[52]), "+f"(d[53]), "+f"(d[54]), "+f"(d[55]), "+f"(d[56]), "+f"(d[57]), "+f"(d[58]), "+f"(d[59]), "+f"(d[60]), "+f"(d[61]), "+f"(d[62]), "+f"(d[63])
    : "r"(a0), "r"(a1), "r"(a2), "r"(a3), "l"(db), "r"(scale_d));
}

__device__ __forceinline__ void wgmma_rs_n128_tb(float (&d)[64], uint32_t a0, uint32_t a1, uint32_t a2, uint32_t a3, uint64_t db, int scale_d) {
  asm volatile("{\n.reg .pred p;\nsetp.ne.b32 p, %69, 0;\n"
    "wgmma.mma_async.sync.aligned.m64n128k16.f32.bf16.bf16 {%0, %1, %2, %3, %4, %5, %6, %7, %8, %9, %10, %11, %12, %13, %14, %15, %16, %17, %18, %19, %20, %21, %22, %23, %24, %25, %26, %27, %28, %29, %30, %31, %32, %33, %34, %35, %36, %37, %38, %39, %40, %41, %42, %43, %44, %45, %46, %47, %48, %49, %50, %51, %52, %53, %54, %55, %56, %57, %58, %59, %60, %61, %62, %63}, {%64, %65, %66, %67}, %68, p, 1, 1, 1;\n}\n"
    : "+f"(d[0]), "+f"(d[1]), "+f"(d[2]), "+f"(d[3]), "+f"(d[4]), "+f"(d[5]), "+f"(d[6]), "+f"(d[7]), "+f"(d[8]), "+f"(d[9]), "+f"(d[10]), "+f"(d[11]), "+f"(d[12]), "+f"(d[13]), "+f"(d[14]), "+f"(d[15]), "+f"(d[16]), "+f"(d[17]), "+f"(d[18]), "+f"(d[19]), "+f"(d[20]), "+f"(d[21]), "+f"(d[22]), "+f"(d[23]), "+f"(d[24]), "+f"(d[25]), "+f"(d[26]), "+f"(d[27]), "+f"(d[28]), "+f"(d[29]), "+f"(d[30]), "+f"(d[31]), "+f"(d[32]), "+f"(d[33]), "+f"(d[34]), "+f"(d[35]), "+f"(d[36]), "+f"(d[37]), "+f"(d[38]), "+f"(d[39]), "+f"(d[40]), "+f"(d[41]), "+f"(d[42]), "+f"(d[43]), "+f"(d[44]), "+f"(d[45]), "+f"(d[46]), "+f"(d[47]), "+f"(d[48]), "+f"(d[49]), "+f"(d[50]), "+f"(d[51]), "+f"(d[52]), "+f"(d[53]), "+f"(d[54]), "+f"(d[55]), "+f"(d[56]), "+f"(d[57]), "+f"(d[58]), "+f"(d[59]), "+f"(d[60]), "+f"(d[61]), "+f"(d[62]), "+f"(d[63])
    : "r"(a0), "r"(a1), "r"(a2), "r"(a3), "l"(db), "r"(scale_d));
}

__device__ __forceinline__ void wgmma_rs_n32_tb(float (&d)[16], uint32_t a0, uint32_t a1, uint32_t a2, uint32_t a3, uint64_t db, int scale_d) {
  asm volatile("{\n.reg .pred p;\nsetp.ne.b32 p, %21, 0;\n"
    "wgmma.mma_async.sync.aligned.m64n32k16.f32.bf16.bf16 {%0, %1, %2, %3, %4, %5, %6, %7, %8, %9, %10, %11, %12, %13, %14, %15}, {%16, %17, %18, %19}, %20, p, 1, 1, 1;\n}\n"
    : "+f"(d[0]), "+f"(d[1]), "+f"(d[2]), "+f"(d[3]), "+f"(d[4]), "+f"(d[5]), "+f"(d[6]), "+f"(d[7]), "+f"(d[8]), "+f"(d[9]), "+f"(d[10]), "+f"(d[11]), "+f"(d[12]), "+f"(d[13]), "+f"(d[14]), "+f"(d[15])
    : "r"(a0), "r"(a1), "r"(a2), "r"(a3), "l"(db), "r"(scale_d));
}

__device__ __forceinline__ void wgmma_rs_n64_tb(float (&d)[32], uint32_t a0, uint32_t a1, uint32_t a2, uint32_t a3, uint64_t db, int scale_d) {
  asm volatile("{\n.reg .pred p;\nsetp.ne.b32 p, %37, 0;\n"
    "wgmma.mma_async.sync.aligned.m64n64k16.f32.bf16.bf16 {%0, %1, %2, %3, %4, %5, %6, %7, %8, %9, %10, %11, %12, %13, %14, %15, %16, %17, %18, %19, %20, %21, %22, %23, %24, %25, %26, %27, %28, %29, %30, %31}, {%32, %33, %34, %35}, %36, p, 1, 1, 1;\n}\n"
    : "+f"(d[0]), "+f"(d[1]), "+f"(d[2]), "+f"(d[3]), "+f"(d[4]), "+f"(d[5]), "+f"(d[6]), "+f"(d[7]), "+f"(d[8]), "+f"(d[9]), "+f"(d[10]), "+f"(d[11]), "+f"(d[12]), "+f"(d[13]), "+f"(d[14]), "+f"(d[15]), "+f"(d[16]), "+f"(d[17]), "+f"(d[18]), "+f"(d[19]), "+f"(d[20]), "+f"(d[21]), "+f"(d[22]), "+f"(d[23]), "+f"(d[24]), "+f"(d[25]), "+f"(d[26]), "+f"(d[27]), "+f"(d[28]), "+f"(d[29]), "+f"(d[30]), "+f"(d[31])
    : "r"(a0), "r"(a1), "r"(a2), "r"(a3), "l"(db), "r"(scale_d));
}

__device__ __forceinline__ void wgmma_rs_n256_tb(float (&d)[64], float (&e)[64], uint32_t a0, uint32_t a1, uint32_t a2, uint32_t a3, uint64_t db, int scale_d) {
  asm volatile("{\n.reg .pred p;\nsetp.ne.b32 p, %133, 0;\n"
    "wgmma.mma_async.sync.aligned.m64n256k16.f32.bf16.bf16 {%0, %1, %2, %3, %4, %5, %6, %7, %8, %9, %10, %11, %12, %13, %14, %15, %16, %17, %18, %19, %20, %21, %22, %23, %24, %25, %26, %27, %28, %29, %30, %31, %32, %33, %34, %35, %36, %37, %38, %39, %40, %41, %42, %43, %44, %45, %46, %47, %48, %49, %50, %51, %52, %53, %54, %55, %56, %57, %58, %59, %60, %61, %62, %63, %64, %65, %66, %67, %68, %69, %70, %71, %72, %73, %74, %75, %76, %77, %78, %79, %80, %81, %82, %83, %84, %85, %86, %87, %88, %89, %90, %91, %92, %93, %94, %95, %96, %97, %98, %99, %100, %101, %102, %103, %104, %105, %106, %107, %108, %109, %110, %111, %112, %113, %114, %115, %116, %117, %118, %119, %120, %121, %122, %123, %124, %125, %126, %127}, {%128, %129, %130, %131}, %132, p, 1, 1, 1;\n}\n"
    : "+f"(d[0]), "+f"(d[1]), "+f"(d[2]), "+f"(d[3]), "+f"(d[4]), "+f"(d[5]), "+f"(d[6]), "+f"(d[7]), "+f"(d[8]), "+f"(d[9]), "+f"(d[10]), "+f"(d[11]), "+f"(d[12]), "+f"(d[13]), "+f"(d[14]), "+f"(d[15]), "+f"(d[16]), "+f"(d[17]), "+f"(d[18]), "+f"(d[19]), "+f"(d[20]), "+f"(d[21]), "+f"(d[22]), "+f"(d[23]), "+f"(d[24]), "+f"(d[25]), "+f"(d[26]), "+f"(d[27]), "+f"(d[28]), "+f"(d[29]), "+f"(d[30]), "+f"(d[31]), "+f"(d[32]), "+f"(d[33]), "+f"(d[34]), "+f"(d[35]), "+f"(d[36]), "+f"(d[37]), "+f"(d[38]), "+f"(d[39]), "+f"(d[40]), "+f"(d[41]), "+f"(d[42]), "+f"(d[43]), "+f"(d[44]), "+f"(d[45]), "+f"(d[46]), "+f"(d[47]), "+f"(d[48]), "+f"(d[49]), "+f"(d[50]), "+f"(d[51]), "+f"(d[52]), "+f"(d[53]), "+f"(d[54]), "+f"(d[55]), "+f"(d[56]), "+f"(d[57]), "+f"(d[58]), "+f"(d[59]), "+f"(d[60]), "+f"(d[61]), "+f"(d[62]), "+f"(d[63]), "+f"(e[0]), "+f"(e[1]), "+f"(e[2]), "+f"(e[3]), "+f"(e[4]), "+f"(e[5]), "+f"(e[6]), "+f"(e[7]), "+f"(e[8]), "+f"(e[9]), "+f"(e[10]), "+f"(e[11]), "+f"(e[12]), "+f"(e[13]), "+f"(e[14]), "+f"(e[15]), "+f"(e[16]), "+f"(e[17]), "+f"(e[18]), "+f"(e[19]), "+f"(e[20]), "+f"(e[21]), "+f"(e[22]), "+f"(e[23]), "+f"(e[24]), "+f"(e[25]), "+f"(e[26]), "+f"(e[27]), "+f"(e[28]), "+f"(e[29]), "+f"(e[30]), "+f"(e[31]), "+f"(e[32]), "+f"(e[33]), "+f"(e[34]), "+f"(e[35]), "+f"(e[36]), "+f"(e[37]), "+f"(e[38]), "+f"(e[39]), "+f"(e[40]), "+f"(e[41]), "+f"(e[42]), "+f"(e[43]), "+f"(e[44]), "+f"(e[45]), "+f"(e[46]), "+f"(e[47]), "+f"(e[48]), "+f"(e[49]), "+f"(e[50]), "+f"(e[51]), "+f"(e[52]), "+f"(e[53]), "+f"(e[54]), "+f"(e[55]), "+f"(e[56]), "+f"(e[57]), "+f"(e[58]), "+f"(e[59]), "+f"(e[60]), "+f"(e[61]), "+f"(e[62]), "+f"(e[63])
    : "r"(a0), "r"(a1), "r"(a2), "r"(a3), "l"(db), "r"(scale_d));
}

__device__ __forceinline__ void wgmma_rs_n128_z(float (&d)[64], uint32_t a0, uint32_t a1, uint32_t a2, uint32_t a3, uint64_t db) {
  asm volatile("{\n.reg .pred p;\nsetp.ne.b32 p, 0, 0;\n"
    "wgmma.mma_async.sync.aligned.m64n128k16.f32.bf16.bf16 {%0, %1, %2, %3, %4, %5, %6, %7, %8, %9, %10, %11, %12, %13, %14, %15, %16, %17, %18, %19, %20, %21, %22, %23, %24, %25, %26, %27, %28, %29, %30, %31, %32, %33, %34, %35, %36, %37, %38, %39, %40, %41, %42, %43, %44, %45, %46, %47, %48, %49, %50, %51, %52, %53, %54, %55, %56, %57, %58, %59, %60, %61, %62, %63}, {%64, %65, %66, %67}, %68, p, 1, 1, 0;\n}\n"
    : "=f"(d[0]), "=f"(d[1]), "=f"(d[2]), "=f"(d[3]), "=f"(d[4]), "=f"(d[5]), "=f"(d[6]), "=f"(d[7]), "=f"(d[8]), "=f"(d[9]), "=f"(d[10]), "=f"(d[11]), "=f"(d[12]), "=f"(d[13]), "=f"(d[14]), "=f"(d[15]), "=f"(d[16]), "=f"(d[17]), "=f"(d[18]), "=f"(d[19]), "=f"(d[20]), "=f"(d[21]), "=f"(d[22]), "=f"(d[23]), "=f"(d[24]), "=f"(d[25]), "=f"(d[26]), "=f"(d[27]), "=f"(d[28]), "=f"(d[29]), "=f"(d[30]), "=f"(d[31]), "=f"(d[32]), "=f"(d[33]), "=f"(d[34]), "=f"(d[35]), "=f"(d[36]), "=f"(d[37]), "=f"(d[38]), "=f"(d[39]), "=f"(d[40]), "=f"(d[41]), "=f"(d[42]), "=f"(d[43]), "=f"(d[44]), "=f"(d[45]), "=f"(d[46]), "=f"(d[47]), "=f"(d[48]), "=f"(d[49]), "=f"(d[50]), "=f"(d[51]), "=f"(d[52]), "=f"(d[53]), "=f"(d[54]), "=f"(d[55]), "=f"(d[56]), "=f"(d[57]), "=f"(d[58]), "=f"(d[59]), "=f"(d[60]), "=f"(d[61]), "=f"(d[62]), "=f"(d[63])
    : "r"(a0), "r"(a1), "r"(a2), "r"(a3), "l"(db));
}

__device__ __forceinline__ void wgmma_rs_n64_tb_z(float (&d)[32], uint32_t a0, uint32_t a1, uint32_t a2, uint32_t a3, uint64_t db) {
  asm volatile("{\n.reg .pred p;\nsetp.ne.b32 p, 0, 0;\n"
    "wgmma.mma_async.sync.aligned.m64n64k16.f32.bf16.bf16 {%0, %1, %2, %3, %4, %5, %6, %7, %8, %9, %10, %11, %12, %13, %14, %15, %16, %17, %18, %19, %20, %21, %22, %23, %24, %25, %26, %27, %28, %29, %30, %31}, {%32, %33, %34, %35}, %36, p, 1, 1, 1;\n}\n"
    : "=f"(d[0]), "=f"(d[1]), "=f"(d[2]), "=f"(d[3]), "=f"(d[4]), "=f"(d[5]), "=f"(d[6]), "=f"(d[7]), "=f"(d[8]), "=f"(d[9]), "=f"(d[10]), "=f"(d[11]), "=f"(d[12]), "=f"(d[13]), "=f"(d[14]), "=f"(d[15]), "=f"(d[16]), "=f"(d[17]), "=f"(d[18]), "=f"(d[19]), "=f"(d[20]), "=f"(d[21]), "=f"(d[22]), "=f"(d[23]), "=f"(d[24]), "=f"(d[25]), "=f"(d[26]), "=f"(d[27]), "=f"(d[28]), "=f"(d[29]), "=f"(d[30]), "=f"(d[31])
    : "r"(a0), "r"(a1), "r"(a2), "r"(a3), "l"(db));
}

__device__ __forceinline__ void wgmma_rs_n256_tb_z(float (&d)[64], float (&e)[64], uint32_t a0, uint32_t a1, uint32_t a2, uint32_t a3, uint64_t db) {
  asm volatile("{\n.reg .pred p;\nsetp.ne.b32 p, 0, 0;\n"
    "wgmma.mma_async.sync.aligned.m64n256k16.f32.bf16.bf16 {%0, %1, %2, %3, %4, %5, %6, %7, %8, %9, %10, %11, %12, %13, %14, %15, %16, %17, %18, %19, %20, %21, %22, %23, %24, %25, %26, %27, %28, %29, %30, %31, %32, %33, %34, %35, %36, %37, %38, %39, %40, %41, %42, %43, %44, %45, %46, %47, %48, %49, %50, %51, %52, %53, %54, %55, %56, %57, %58, %59, %60, %61, %62, %63, %64, %65, %66, %67, %68, %69, %70, %71, %72, %73, %74, %75, %76, %77, %78, %79, %80, %81, %82, %83, %84, %85, %86, %87, %88, %89, %90, %91, %92, %93, %94, %95, %96, %97, %98, %99, %100, %101, %102, %103, %104, %105, %106, %107, %108, %109, %110, %111, %112, %113, %114, %115, %116, %117, %118, %119, %120, %121, %122, %123, %124, %125, %126, %127}, {%128, %129, %130, %131}, %132, p, 1, 1, 1;\n}\n"
    : "=f"(d[0]), "=f"(d[1]), "=f"(d[2]), "=f"(d[3]), "=f"(d[4]), "=f"(d[5]), "=f"(d[6]), "=f"(d[7]), "=f"(d[8]), "=f"(d[9]), "=f"(d[10]), "=f"(d[11]), "=f"(d[12]), "=f"(d[13]), "=f"(d[14]), "=f"(d[15]), "=f"(d[16]), "=f"(d[17]), "=f"(d[18]), "=f"(d[19]), "=f"(d[20]), "=f"(d[21]), "=f"(d[22]), "=f"(d[23]), "=f"(d[24]), "=f"(d[25]), "=f"(d[26]), "=f"(d[27]), "=f"(d[28]), "=f"(d[29]), "=f"(d[30]), "=f"(d[31]), "=f"(d[32]), "=f"(d[33]), "=f"(d[34]), "=f"(d[35]), "=f"(d[36]), "=f"(d[37]), "=f"(d[38]), "=f"(d[39]), "=f"(d[40]), "=f"(d[41]), "=f"(d[42]), "=f"(d[43]), "=f"(d[44]), "=f"(d[45]), "=f"(d[46]), "=f"(d[47]), "=f"(d[48]), "=f"(d[49]), "=f"(d[50]), "=f"(d[51]), "=f"(d[52]), "=f"(d[53]), "=f"(d[54]), "=f"(d[55]), "=f"(d[56]), "=f"(d[57]), "=f"(d[58]), "=f"(d[59]), "=f"(d[60]), "=f"(d[61]), "=f"(d[62]), "=f"(d[63]), "=f"(e[0]), "=f"(e[1]), "=f"(e[2]), "=f"(e[3]), "=f"(e[4]), "=f"(e[5]), "=f"(e[6]), "=f"(e[7]), "=f"(e[8]), "=f"(e[9]), "=f"(e[10]), "=f"(e[11]), "=f"(e[12]), "=f"(e[13]), "=f"(e[14]), "=f"(e[15]), "=f"(e[16]), "=f"(e[17]), "=f"(e[18]), "=f"(e[19]), "=f"(e[20]), "=f"(e[21]), "=f"(e[22]), "=f"(e[23]), "=f"(e[24]), "=f"(e[25]), "=f"(e[26]), "=f"(e[27]), "=f"(e[28]), "=f"(e[29]), "=f"(e[30]), "=f"(e[31]), "=f"(e[32]), "=f"(e[33]), "=f"(e[34]), "=f"(e[35]), "=f"(e[36]), "=f"(e[37]), "=f"(e[38]), "=f"(e[39]), "=f"(e[40]), "=f"(e[41]), "=f"(e[42]), "=f"(e[43]), "=f"(e[44]), "=f"(e[45]), "=f"(e[46]), "=f"(e[47]), "=f"(e[48]), "=f"(e[49]), "=f"(e[50]), "=f"(e[51]), "=f"(e[52]), "=f"(e[53]), "=f"(e[54]), "=f"(e[55]), "=f"(e[56]), "=f"(e[57]), "=f"(e[58]), "=f"(e[59]), "=f"(e[60]), "=f"(e[61]), "=f"(e[62]), "=f"(e[63])
    : "r"(a0), "r"(a1), "r"(a2), "r"(a3), "l"(db));
}

struct Maps {
  CUtensorMap x[2], k[2], v[2], wq[2], wo[2], wo2[2];
};

__global__ void __cluster_dims__(2, 1, 1) __launch_bounds__(384, 1)
fused_gqa_kernel(const __grid_constant__ Maps maps, __nv_bfloat16* __restrict__ out) {
  extern __shared__ __align__(1024) unsigned char smem[];
  const uint32_t sbase = smem_u32(smem);
  const uint32_t full0 = sbase + BAR_OFF;
  const uint32_t empty0 = full0 + N_ITEMS * 8;
  const uint32_t ready0 = empty0 + N_ITEMS * 8;
  const uint32_t pub0 = ready0 + 6 * 8;

  const int tid = threadIdx.x;
  const int wg = tid >> 7;
  const int bid = blockIdx.x;
  const int bp = bid & 3;
  const int h = (bid >> 2) & 15;
  const int p = bid >> 6;

  if (tid == 0) {
#pragma unroll
    for (int i = 0; i < 3; i++) mbar_init(full0 + (WQ0 + i) * 8, 1);
#pragma unroll
    for (int i = 0; i < 2; i++) mbar_init(full0 + (X0 + i) * 8, 1);
    asm volatile("fence.mbarrier_init.release.cluster;" ::: "memory");
#pragma unroll
    for (int kc = 0; kc < 3; kc++) {
      if (kc < 2) {
        mbar_expect_tx(full0 + (X0 + kc) * 8, 16384);
        tma_load3(sbase + x_off(kc), &maps.x[p], 0, bp * 128, kc, full0 + (X0 + kc) * 8);
      }
      mbar_expect_tx(full0 + (WQ0 + kc) * 8, T32);
      tma_load3(sbase + wq_off(kc), &maps.wq[p], 0, kc * 64, h * 4, full0 + (WQ0 + kc) * 8);
    }
    TR(0, 56);
  } else if (tid == 32) {
    prefetch_tmap(&maps.k[p]);
    prefetch_tmap(&maps.v[p]);
    prefetch_tmap(&maps.wo[p]);
    prefetch_tmap(&maps.wo2[p]);
  } else if (tid >= 128) {
    const int i = tid - 128;
    if (i < N_ITEMS) {
      if (!(i < 3 || i == X0 || i == X0 + 1)) mbar_init(full0 + i * 8, 1);
    } else if (i >= 64 && i < 64 + N_ITEMS) {
      mbar_init(empty0 + (i - 64) * 8, 8);
    } else if (i >= 128 && i < 128 + 6) {
      mbar_init(ready0 + (i - 128) * 8, 1);
    } else if (i >= 160 && i < 160 + 6) {
      mbar_init(pub0 + (i - 160) * 8, 4);
    }
    asm volatile("fence.mbarrier_init.release.cluster;" ::: "memory");
  }
  __syncthreads();
  if (tid == 0) TR(0, 57);

  if (wg == 0) {
    asm volatile("setmaxnreg.dec.sync.aligned.u32 24;");
    if (tid == 0) {
#pragma unroll 1
      for (int kc = 2; kc < 9; kc++) {
        mbar_wait(empty0 + (X0 + kc - 2) * 8);
        mbar_expect_tx(full0 + (X0 + kc) * 8, 16384);
        tma_load3(sbase + x_off(kc), &maps.x[p], 0, bp * 128, kc, full0 + (X0 + kc) * 8);
        if (kc < 8) {
          TR(0, WQ0 + kc + 1);
          mbar_expect_tx(full0 + (WQ0 + kc + 1) * 8, T32);
          tma_load3(sbase + wq_off(kc + 1), &maps.wq[p], 0, (kc + 1) * 64, h * 4, full0 + (WQ0 + kc + 1) * 8);
        }
      }
#pragma unroll 1
      for (int m = 0; m < N_WO; m++) {
        const int dep = m >= 5 ? WO0 + m - 5 : (m < 3 ? X0 + 6 + m : KV0 + 10 + m);
        mbar_wait(empty0 + dep * 8);
        const uint32_t fb = full0 + (WO0 + m) * 8;
        TR(0, WO0 + m);
        mbar_expect_tx(fb, T32);
        if (m < 8) tma_load3(sbase + wo_off(m), &maps.wo[p], 0, h * 256 + (m & 3) * 64, (m >> 2) * 4, fb);
        else tma_load3(sbase + wo_off(m), &maps.wo2[p], 0, h * 256, 8, fb);
      }
    } else if (tid == 96) {
#pragma unroll 1
      for (int n = 0; n < N_KV; n++) {
        if (n >= 3) mbar_wait(empty0 + (KV0 + n - 3) * 8);
        if (n >= KV_INFLIGHT) mbar_wait(full0 + (KV0 + n - KV_INFLIGHT) * 8);
        const uint32_t fb = full0 + (KV0 + n) * 8;
        const CUtensorMap* tm = (n & 1) ? &maps.v[p] : &maps.k[p];
        const int row = ((2 * bp + (n >> 3)) * 16 + h) * kSK + ((n & 7) >> 1) * 128;
        TR(0, KV0 + n);
        mbar_expect_tx(fb, T32);
        tma_load3(sbase + kv_off(n), tm, 0, row, 0, fb);
      }
    } else if (tid == 32 || tid == 64) {
      const int w = (tid >> 5) - 1;
      const int tile = p * 8 + 2 * bp + w;
      unsigned target[3];
#pragma unroll
      for (int pn = 0; pn < 3; pn++) {
        unsigned v;
        asm volatile("ld.relaxed.gpu.global.u32 %0, [%1];" : "=r"(v) : "l"(&g_cnt[(tile * 4 + pn) * 32]) : "memory");
        target[pn] = (v / 16u + 1u) * 16u;
      }
#pragma unroll 1
      for (int e = 0; e < 3; e++) {
        mbar_wait(pub0 + (w * 3 + e) * 8);
        __threadfence();
        asm volatile("red.relaxed.gpu.global.add.u32 [%0], 1;" ::"l"(&g_cnt[(tile * 4 + e) * 32]) : "memory");
      }
#pragma unroll
      for (int pn = 0; pn < 3; pn++) {
        const unsigned* c = &g_cnt[(tile * 4 + pn) * 32];
        for (uint32_t it = 0; it < WAIT_LIMIT; ++it) {
          unsigned v;
          asm volatile("ld.acquire.gpu.global.u32 %0, [%1];" : "=r"(v) : "l"(c) : "memory");
          if ((int)(v - target[pn]) >= 0) break;
        }
        mbar_arrive(ready0 + (w * 3 + pn) * 8);
      }
    }
  } else {
    asm volatile("setmaxnreg.inc.sync.aligned.u32 240;");
    const int w = wg - 1;
    const int t128 = tid & 127;
    const int lane = tid & 31;

    auto release = [&](int item) {
      __syncwarp();
      if (lane == 0) mbar_arrive(empty0 + item * 8);
    };

    TRC(0);
    const float cs = 0.08838834764831845f * 1.4426950408889634f;
    float s[64], o[64];
#pragma unroll
    for (int i = 0; i < 64; i++) s[i] = 0.f, o[i] = 0.f;
    uint32_t qf[32];
    uint4* park = reinterpret_cast<uint4*>(smem + PARK_OFF) + w * 1024 + t128;
    {
#pragma unroll 1
      for (int kc = 0; kc < 9; kc++) {
        mbar_wait(full0 + (X0 + kc) * 8);
        mbar_wait(full0 + (WQ0 + kc) * 8);
        if (kc == 0) TRC(1);
        const uint64_t da = make_desc(sbase + x_off(kc), 16, 1024);
        const uint64_t db = make_desc(sbase + wq_off(kc) + w * 16384, 8192, 1024);
        wg_fence();
#pragma unroll
        for (int ks = 0; ks < 4; ks++) {
          wgmma_ss_n128_tb(s, da + ks * 2, db + ks * 128, (kc | ks) != 0);
          wgmma_ss_n128_tb(o, da + 512 + ks * 2, db + ks * 128, (kc | ks) != 0);
        }
        wg_commit();
        wg_wait<0>();
        release(X0 + kc);
      }
      fence_regs(s);
      fence_regs(o);
#pragma unroll
      for (int i = 0; i < 32; i++) qf[i] = pack_bf16(s[2 * i], s[2 * i + 1]);
      named_bar(1, 256);
#pragma unroll
      for (int i = 0; i < 8; i++) park[i * 128] = pack8(o, i);
      TRC(2);
    }
#pragma unroll 1
    for (int bb = 0; bb < 2; bb++) {
#pragma unroll
      for (int i = 0; i < 64; i++) o[i] = 0.f;
      float m0 = -INFINITY, m1 = -INFINITY, l0 = 0.f, l1 = 0.f;
#pragma unroll 1
      for (int t = 0; t < 4; t++) {
        const int n = bb * 8 + t * 2;
        {
          const uint32_t base = sbase + kv_off(n);
          mbar_wait(full0 + (KV0 + n) * 8);
          if (n == 0 && w == 1) named_bar(4, 256);
          const uint64_t db = make_desc(base, 16, 1024);
          wg_fence();
          wgmma_rs_n128_z(s, qf[0], qf[1], qf[2], qf[3], db);
#pragma unroll
          for (int ks = 1; ks < 8; ks++)
            wgmma_rs_n128(s, qf[4 * ks], qf[4 * ks + 1], qf[4 * ks + 2], qf[4 * ks + 3], db + (ks >> 2) * 1024 + (ks & 3) * 2, 1);
          wg_commit();
          wg_wait<0>();
          fence_regs(s);
          if (n == 0 && w == 0) named_arrive(4, 256);
          release(KV0 + n);
        }
        float mx0 = s[0], mx1 = s[2];
#pragma unroll
        for (int g = 0; g < 16; g++) {
          mx0 = fmaxf(mx0, fmaxf(s[4 * g], s[4 * g + 1]));
          mx1 = fmaxf(mx1, fmaxf(s[4 * g + 2], s[4 * g + 3]));
        }
        mx0 = fmaxf(mx0, __shfl_xor_sync(0xffffffffu, mx0, 1));
        mx0 = fmaxf(mx0, __shfl_xor_sync(0xffffffffu, mx0, 2));
        mx1 = fmaxf(mx1, __shfl_xor_sync(0xffffffffu, mx1, 1));
        mx1 = fmaxf(mx1, __shfl_xor_sync(0xffffffffu, mx1, 2));
        const float mn0 = fmaxf(m0, mx0), mn1 = fmaxf(m1, mx1);
        const float a0 = ex2((m0 - mn0) * cs), a1 = ex2((m1 - mn1) * cs);
        m0 = mn0;
        m1 = mn1;
        const float ms0 = mn0 * cs, ms1 = mn1 * cs;
        float rs0 = 0.f, rs1 = 0.f;
        uint32_t pf[32];
#pragma unroll
        for (int g = 0; g < 16; g++) {
          const float p0 = ex2(fmaf(s[4 * g], cs, -ms0));
          const float p1 = ex2(fmaf(s[4 * g + 1], cs, -ms0));
          const float p2 = ex2(fmaf(s[4 * g + 2], cs, -ms1));
          const float p3 = ex2(fmaf(s[4 * g + 3], cs, -ms1));
          rs0 += p0 + p1;
          rs1 += p2 + p3;
          pf[2 * g] = pack_bf16(p0, p1);
          pf[2 * g + 1] = pack_bf16(p2, p3);
        }
        l0 = l0 * a0 + rs0;
        l1 = l1 * a1 + rs1;
#pragma unroll
        for (int g = 0; g < 16; g++) {
          o[4 * g] *= a0;
          o[4 * g + 1] *= a0;
          o[4 * g + 2] *= a1;
          o[4 * g + 3] *= a1;
        }
        {
          const uint32_t base = sbase + kv_off(n + 1);
          mbar_wait(full0 + (KV0 + n + 1) * 8);
          const uint64_t db = make_desc(base, 16384, 1024);
          wg_fence();
#pragma unroll
          for (int ks = 0; ks < 8; ks++)
            wgmma_rs_n128_tb(o, pf[4 * ks], pf[4 * ks + 1], pf[4 * ks + 2], pf[4 * ks + 3], db + ks * 128, 1);
          wg_commit();
          wg_wait<0>();
          fence_regs(o);
          release(KV0 + n + 1);
          TRC(3 + bb * 5 + t);
        }
      }
      l0 += __shfl_xor_sync(0xffffffffu, l0, 1);
      l0 += __shfl_xor_sync(0xffffffffu, l0, 2);
      l1 += __shfl_xor_sync(0xffffffffu, l1, 1);
      l1 += __shfl_xor_sync(0xffffffffu, l1, 2);
      const float i0 = 1.f / l0, i1 = 1.f / l1;
      uint4* dst = park;
      if (bb == 0) {
#pragma unroll
        for (int i = 0; i < 8; i++) {
          const uint4 v = park[i * 128];
          qf[4 * i] = v.x;
          qf[4 * i + 1] = v.y;
          qf[4 * i + 2] = v.z;
          qf[4 * i + 3] = v.w;
        }
      } else {
        named_bar(1, 256);
        dst = reinterpret_cast<uint4*>(smem + KV_OFF) + w * 1024 + t128;
      }
#pragma unroll
      for (int i = 0; i < 8; i++)
        dst[i * 128] = make_uint4(pack_bf16(o[8 * i] * i0, o[8 * i + 1] * i0), pack_bf16(o[8 * i + 2] * i1, o[8 * i + 3] * i1),
                                  pack_bf16(o[8 * i + 4] * i0, o[8 * i + 5] * i0), pack_bf16(o[8 * i + 6] * i1, o[8 * i + 7] * i1));
    }
    uint32_t af[64];
    {
      named_bar(1, 256);
      const uint4* src = reinterpret_cast<const uint4*>(smem + (w == 0 ? PARK_OFF : KV_OFF)) + t128;
#pragma unroll
      for (int i = 0; i < 16; i++) {
        const uint4 v = src[i * 128];
        af[4 * i] = v.x;
        af[4 * i + 1] = v.y;
        af[4 * i + 2] = v.z;
        af[4 * i + 3] = v.w;
      }
    }
    TRC(12);
    const int tile = p * 8 + 2 * bp + w;
    uint4* part = g_part + (size_t)(tile * 16 + h) * 36 * 128 + t128;
#pragma unroll
    for (int pn = 0; pn < 2; pn++) {
#pragma unroll
      for (int kc = 0; kc < 4; kc++) {
        const int m = pn * 4 + kc;
        mbar_wait(full0 + (WO0 + m) * 8);
        const uint64_t db = make_desc(sbase + wo_off(m), 8192, 1024);
        wg_fence();
#pragma unroll
        for (int ks = 0; ks < 4; ks++) {
          const int a = (kc * 4 + ks) * 4;
          if ((kc | ks) == 0) wgmma_rs_n256_tb_z(s, o, af[a], af[a + 1], af[a + 2], af[a + 3], db);
          else wgmma_rs_n256_tb(s, o, af[a], af[a + 1], af[a + 2], af[a + 3], db + ks * 128, 1);
        }
        wg_commit();
        if (kc > 0) {
          wg_wait<1>();
          if (m - 1 < 4) release(WO0 + m - 1);
        }
      }
      wg_wait<0>();
      fence_regs(s);
      fence_regs(o);
      if (pn == 0) release(WO0 + 3);
      TRC(13 + pn * 2);
#pragma unroll
      for (int i = 0; i < 8; i++) __stcg(part + (pn * 16 + i) * 128, pack8(s, i));
#pragma unroll
      for (int i = 0; i < 8; i++) __stcg(part + (pn * 16 + 8 + i) * 128, pack8(o, i));
      __syncwarp();
      if (lane == 0) mbar_arrive(pub0 + (w * 3 + pn) * 8);
      TRC(14 + pn * 2);
    }
    {
      float acc[32];
      mbar_wait(full0 + (WO0 + 8) * 8);
      const uint64_t db = make_desc(sbase + wo_off(8), 8192, 1024);
      wg_fence();
      wgmma_rs_n64_tb_z(acc, af[0], af[1], af[2], af[3], db);
#pragma unroll
      for (int ks = 1; ks < 16; ks++)
        wgmma_rs_n64_tb(acc, af[4 * ks], af[4 * ks + 1], af[4 * ks + 2], af[4 * ks + 3], db + ks * 128, 1);
      wg_commit();
      wg_wait<0>();
      fence_regs(acc);
#pragma unroll
      for (int i = 0; i < 4; i++) __stcg(part + (32 + i) * 128, pack8(acc, i));
      __syncwarp();
      if (lane == 0) mbar_arrive(pub0 + (w * 3 + 2) * 8);
      TRC(17);
    }
    const int row0 = (t128 >> 5) * 16 + (lane >> 2);
    const int q2 = (lane & 3) * 2;
    __nv_bfloat16* orow = out + (size_t)((2 * bp + w) * 64 + row0) * 1152 + p * 576;
    const uint4* pr = g_part + (size_t)(tile * 16) * 36 * 128 + t128;
#pragma unroll
    for (int pn = 0; pn < 3; pn++) {
      mbar_wait(ready0 + (w * 3 + pn) * 8);
      TRC(18 + pn);
      int slot, col;
      bool active = true;
      if (pn < 2) {
        slot = pn * 16 + h;
        col = pn * 256 + h * 16 + q2;
      } else {
        slot = 32 + (h & 3);
        col = 512 + (h & 3) * 16 + q2;
        active = ((t128 >> 5) == (h >> 2));
      }
      if (active) {
        uint4 v[16];
#pragma unroll
        for (int c = 0; c < 16; c++) v[c] = __ldcg(pr + (size_t)(c * 36 + slot) * 128);
        float a[8];
#pragma unroll
        for (int e = 0; e < 8; e++) a[e] = 0.f;
#pragma unroll
        for (int c = 0; c < 16; c++) {
          a[0] += bf_lo(v[c].x);
          a[1] += bf_hi(v[c].x);
          a[2] += bf_lo(v[c].y);
          a[3] += bf_hi(v[c].y);
          a[4] += bf_lo(v[c].z);
          a[5] += bf_hi(v[c].z);
          a[6] += bf_lo(v[c].w);
          a[7] += bf_hi(v[c].w);
        }
        *reinterpret_cast<uint32_t*>(orow + col) = pack_bf16(a[0], a[1]);
        *reinterpret_cast<uint32_t*>(orow + 8 * 1152 + col) = pack_bf16(a[2], a[3]);
        *reinterpret_cast<uint32_t*>(orow + col + 8) = pack_bf16(a[4], a[5]);
        *reinterpret_cast<uint32_t*>(orow + 8 * 1152 + col + 8) = pack_bf16(a[6], a[7]);
      }
    }
    TRC(21);
  }
}

typedef CUresult (*EncodeFn)(CUtensorMap*, CUtensorMapDataType, cuuint32_t, void*, const cuuint64_t*, const cuuint64_t*,
                             const cuuint32_t*, const cuuint32_t*, CUtensorMapInterleave, CUtensorMapSwizzle,
                             CUtensorMapL2promotion, CUtensorMapFloatOOBfill);

void encode3d(EncodeFn fn, CUtensorMap* m, void* ptr, uint64_t cols, uint64_t rows, uint32_t box_rows, uint32_t box_chunks) {
  cuuint64_t dims[3] = {64, rows, cols / 64};
  cuuint64_t strides[2] = {cols * 2, 128};
  cuuint32_t box[3] = {64, box_rows, box_chunks};
  cuuint32_t es[3] = {1, 1, 1};
  fn(m, CU_TENSOR_MAP_DATA_TYPE_BFLOAT16, 3, ptr, dims, strides, box, es, CU_TENSOR_MAP_INTERLEAVE_NONE,
     CU_TENSOR_MAP_SWIZZLE_128B, CU_TENSOR_MAP_L2_PROMOTION_L2_256B, CU_TENSOR_MAP_FLOAT_OOB_FILL_NONE);
}

}

extern "C" void kernel_launch(void* const* d_in, const int* in_sizes, int n_in, void* d_out, int out_size) {
  static EncodeFn fn = nullptr;
  if (!fn) {
    void* f = nullptr;
    cudaDriverEntryPointQueryResult st;
    cudaGetDriverEntryPoint("cuTensorMapEncodeTiled", &f, cudaEnableDefault, &st);
    fn = (EncodeFn)f;
    cudaFuncSetAttribute(fused_gqa_kernel, cudaFuncAttributeMaxDynamicSharedMemorySize, SMEM_BYTES);
  }
  Maps maps;
  for (int p = 0; p < 2; p++) {
    encode3d(fn, &maps.x[p], d_in[p * 5 + 0], kD, 512, 128, 1);
    encode3d(fn, &maps.k[p], d_in[p * 5 + 1], kDH, 8 * 16 * kSK, 128, 2);
    encode3d(fn, &maps.v[p], d_in[p * 5 + 2], kDH, 8 * 16 * kSK, 128, 2);
    encode3d(fn, &maps.wq[p], d_in[p * 5 + 3], kHQD, kD, 64, 4);
    encode3d(fn, &maps.wo[p], d_in[p * 5 + 4], kD, kHQD, 64, 4);
    encode3d(fn, &maps.wo2[p], d_in[p * 5 + 4], kD, kHQD, 256, 1);
  }
  fused_gqa_kernel<<<128, 384, SMEM_BYTES>>>(maps, (__nv_bfloat16*)d_out);
}
```

```cpp
#include <cuda_runtime.h>
#include <cuda_bf16.h>
#include <cuda.h>
#include <stdint.h>

namespace {

constexpr int kD = 576, kHQD = 4096, kSK = 512, kDH = 128;

constexpr int N_WQ = 9, N_X = 9, N_KV = 16, N_WO = 9;
constexpr int N_ITEMS = N_WQ + N_X + N_KV + N_WO;
constexpr int T32 = 32 * 1024;
constexpr int KV_OFF = 96 * 1024;
constexpr int PARK_OFF = 192 * 1024;
constexpr int BAR_OFF = 224 * 1024;
constexpr int SMEM_BYTES = BAR_OFF + 2 * N_ITEMS * 8 + 256;
constexpr int WQ0 = 0, X0 = N_WQ, KV0 = X0 + N_X, WO0 = KV0 + N_KV;
#define WO_PF_AT 11
#define KV_INFLIGHT 2

__device__ __forceinline__ int wq_off(int kc) { return (kc % 3) * T32; }
__device__ __forceinline__ int x_off(int kc) { return PARK_OFF + (kc & 1) * 16384; }
__device__ __forceinline__ int kv_off(int n) { return KV_OFF + (n % 3) * T32; }
__device__ __forceinline__ int wo_off(int m) {
  const int s = m % 5;
  return (s < 3 ? s : s + 1) * T32;
}

__device__ uint4 g_part[16 * 16 * 36 * 128];
__device__ unsigned int g_cnt[16 * 4 * 32];

#define TR(role, ev)
#define TRC(ev)
constexpr uint32_t WAIT_CYCLES = 1u << 20;
constexpr uint32_t WAIT_LIMIT = 1u << 12;
__device__ __forceinline__ uint32_t smem_u32(const void* p) { return (uint32_t)__cvta_generic_to_shared(p); }
__device__ __forceinline__ void mbar_init(uint32_t bar, uint32_t cnt) {
  asm volatile("mbarrier.init.shared::cta.b64 [%0], %1;" ::"r"(bar), "r"(cnt) : "memory");
}
__device__ __forceinline__ void mbar_expect_tx(uint32_t bar, uint32_t bytes) {
  asm volatile("mbarrier.arrive.expect_tx.shared::cta.b64 _, [%0], %1;" ::"r"(bar), "r"(bytes) : "memory");
}
__device__ __forceinline__ void mbar_arrive(uint32_t bar) {
  asm volatile("mbarrier.arrive.shared::cta.b64 _, [%0];" ::"r"(bar) : "memory");
}
__device__ __forceinline__ bool mbar_try(uint32_t bar, uint32_t parity) {
  uint32_t ok;
  asm volatile(
      "{\n.reg .pred p;\nmbarrier.try_wait.parity.shared::cta.b64 p, [%1], %2;\nselp.u32 %0, 1, 0, p;\n}\n"
      : "=r"(ok)
      : "r"(bar), "r"(parity)
      : "memory");
  return ok != 0;
}
__device__ __forceinline__ void mbar_wait(uint32_t bar) {
  if (mbar_try(bar, 0)) return;
  const uint32_t t0 = (uint32_t)clock();
  while (!mbar_try(bar, 0))
    if ((uint32_t)clock() - t0 > WAIT_CYCLES) break;
}
__device__ __forceinline__ void tma_load3(uint32_t dst, const CUtensorMap* tm, int c0, int c1, int c2, uint32_t bar) {
  asm volatile(
      "cp.async.bulk.tensor.3d.shared::cluster.global.mbarrier::complete_tx::bytes [%0], [%1, {%3, %4, %5}], [%2];" ::"r"(dst),
      "l"(tm), "r"(bar), "r"(c0), "r"(c1), "r"(c2)
      : "memory");
}
__device__ __forceinline__ void tma_prefetch3(const CUtensorMap* tm, int c0, int c1, int c2) {
  asm volatile("cp.async.bulk.prefetch.tensor.3d.L2.global [%0, {%1, %2, %3}];" ::"l"(tm), "r"(c0), "r"(c1), "r"(c2) : "memory");
}
__device__ __forceinline__ void prefetch_tmap(const CUtensorMap* tm) {
  asm volatile("prefetch.tensormap [%0];" ::"l"(tm) : "memory");
}
__device__ __forceinline__ void named_bar(int id, int n) { asm volatile("bar.sync %0, %1;" ::"r"(id), "r"(n) : "memory"); }
__device__ __forceinline__ void named_arrive(int id, int n) { asm volatile("bar.arrive %0, %1;" ::"r"(id), "r"(n) : "memory"); }
__device__ __forceinline__ void wg_fence() { asm volatile("wgmma.fence.sync.aligned;" ::: "memory"); }
__device__ __forceinline__ void wg_commit() { asm volatile("wgmma.commit_group.sync.aligned;" ::: "memory"); }
template <int N>
__device__ __forceinline__ void wg_wait() { asm volatile("wgmma.wait_group.sync.aligned %0;" ::"n"(N) : "memory"); }
template <int N>
__device__ __forceinline__ void fence_regs(float (&d)[N]) {
#pragma unroll
  for (int i = 0; i < N; i++) asm volatile("" : "+f"(d[i])::"memory");
}
__device__ __forceinline__ uint64_t make_desc(uint32_t addr, uint32_t lbo, uint32_t sbo) {
  return (uint64_t)((addr & 0x3FFFF) >> 4) | ((uint64_t)(lbo >> 4) << 16) | ((uint64_t)(sbo >> 4) << 32) | (1ull << 62);
}
__device__ __forceinline__ uint32_t pack_bf16(float lo, float hi) {
  uint32_t r;
  asm("cvt.rn.bf16x2.f32 %0, %1, %2;" : "=r"(r) : "f"(hi), "f"(lo));
  return r;
}
__device__ __forceinline__ float ex2(float x) {
  float y;
  asm("ex2.approx.ftz.f32 %0, %1;" : "=f"(y) : "f"(x));
  return y;
}
__device__ __forceinline__ float bf_lo(uint32_t v) { return __uint_as_float(v << 16); }
__device__ __forceinline__ float bf_hi(uint32_t v) { return __uint_as_float(v & 0xffff0000u); }
template <int N>
__device__ __forceinline__ uint4 pack8(const float (&a)[N], int i) {
  return make_uint4(pack_bf16(a[8 * i], a[8 * i + 1]), pack_bf16(a[8 * i + 2], a[8 * i + 3]), pack_bf16(a[8 * i + 4], a[8 * i + 5]),
                    pack_bf16(a[8 * i + 6], a[8 * i + 7]));
}

__device__ __forceinline__ void wgmma_ss_n128_tb(float (&d)[64], uint64_t da, uint64_t db, int scale_d) {
  asm volatile("{\n.reg .pred p;\nsetp.ne.b32 p, %66, 0;\n"
    "wgmma.mma_async.sync.aligned.m64n128k16.f32.bf16.bf16 {%0, %1, %2, %3, %4, %5, %6, %7, %8, %9, %10, %11, %12, %13, %14, %15, %16, %17, %18, %19, %20, %21, %22, %23, %24, %25, %26, %27, %28, %29, %30, %31, %32, %33, %34, %35, %36, %37, %38, %39, %40, %41, %42, %43, %44, %45, %46, %47, %48, %49, %50, %51, %52, %53, %54, %55, %56, %57, %58, %59, %60, %61, %62, %63}, %64, %65, p, 1, 1, 0, 1;\n}\n"
    : "+f"(d[0]), "+f"(d[1]), "+f"(d[2]), "+f"(d[3]), "+f"(d[4]), "+f"(d[5]), "+f"(d[6]), "+f"(d[7]), "+f"(d[8]), "+f"(d[9]), "+f"(d[10]), "+f"(d[11]), "+f"(d[12]), "+f"(d[13]), "+f"(d[14]), "+f"(d[15]), "+f"(d[16]), "+f"(d[17]), "+f"(d[18]), "+f"(d[19]), "+f"(d[20]), "+f"(d[21]), "+f"(d[22]), "+f"(d[23]), "+f"(d[24]), "+f"(d[25]), "+f"(d[26]), "+f"(d[27]), "+f"(d[28]), "+f"(d[29]), "+f"(d[30]), "+f"(d[31]), "+f"(d[32]), "+f"(d[33]), "+f"(d[34]), "+f"(d[35]), "+f"(d[36]), "+f"(d[37]), "+f"(d[38]), "+f"(d[39]), "+f"(d[40]), "+f"(d[41]), "+f"(d[42]), "+f"(d[43]), "+f"(d[44]), "+f"(d[45]), "+f"(d[46]), "+f"(d[47]), "+f"(d[48]), "+f"(d[49]), "+f"(d[50]), "+f"(d[51]), "+f"(d[52]), "+f"(d[53]), "+f"(d[54]), "+f"(d[55]), "+f"(d[56]), "+f"(d[57]), "+f"(d[58]), "+f"(d[59]), "+f"(d[60]), "+f"(d[61]), "+f"(d[62]), "+f"(d[63])
    : "l"(da), "l"(db), "r"(scale_d));
}

__device__ __forceinline__ void wgmma_rs_n128(float (&d)[64], uint32_t a0, uint32_t a1, uint32_t a2, uint32_t a3, uint64_t db, int scale_d) {
  asm volatile("{\n.reg .pred p;\nsetp.ne.b32 p, %69, 0;\n"
    "wgmma.mma_async.sync.aligned.m64n128k16.f32.bf16.bf16 {%0, %1, %2, %3, %4, %5, %6, %7, %8, %9, %10, %11, %12, %13, %14, %15, %16, %17, %18, %19, %20, %21, %22, %23, %24, %25, %26, %27, %28, %29, %30, %31, %32, %33, %34, %35, %36, %37, %38, %39, %40, %41, %42, %43, %44, %45, %46, %47, %48, %49, %50, %51, %52, %53, %54, %55, %56, %57, %58, %59, %60, %61, %62, %63}, {%64, %65, %66, %67}, %68, p, 1, 1, 0;\n}\n"
    : "+f"(d[0]), "+f"(d[1]), "+f"(d[2]), "+f"(d[3]), "+f"(d[4]), "+f"(d[5]), "+f"(d[6]), "+f"(d[7]), "+f"(d[8]), "+f"(d[9]), "+f"(d[10]), "+f"(d[11]), "+f"(d[12]), "+f"(d[13]), "+f"(d[14]), "+f"(d[15]), "+f"(d[16]), "+f"(d[17]), "+f"(d[18]), "+f"(d[19]), "+f"(d[20]), "+f"(d[21]), "+f"(d[22]), "+f"(d[23]), "+f"(d[24]), "+f"(d[25]), "+f"(d[26]), "+f"(d[27]), "+f"(d[28]), "+f"(d[29]), "+f"(d[30]), "+f"(d[31]), "+f"(d[32]), "+f"(d[33]), "+f"(d[34]), "+f"(d[35]), "+f"(d[36]), "+f"(d[37]), "+f"(d[38]), "+f"(d[39]), "+f"(d[40]), "+f"(d[41]), "+f"(d[42]), "+f"(d[43]), "+f"(d[44]), "+f"(d[45]), "+f"(d[46]), "+f"(d[47]), "+f"(d[48]), "+f"(d[49]), "+f"(d[50]), "+f"(d[51]), "+f"(d[52]), "+f"(d[53]), "+f"(d[54]), "+f"(d[55]), "+f"(d[56]), "+f"(d[57]), "+f"(d[58]), "+f"(d[59]), "+f"(d[60]), "+f"(d[61]), "+f"(d[62]), "+f"(d[63])
    : "r"(a0), "r"(a1), "r"(a2), "r"(a3), "l"(db), "r"(scale_d));
}

__device__ __forceinline__ void wgmma_rs_n128_tb(float (&d)[64], uint32_t a0, uint32_t a1, uint32_t a2, uint32_t a3, uint64_t db, int scale_d) {
  asm volatile("{\n.reg .pred p;\nsetp.ne.b32 p, %69, 0;\n"
    "wgmma.mma_async.sync.aligned.m64n128k16.f32.bf16.bf16 {%0, %1, %2, %3, %4, %5, %6, %7, %8, %9, %10, %11, %12, %13, %14, %15, %16, %17, %18, %19, %20, %21, %22, %23, %24, %25, %26, %27, %28, %29, %30, %31, %32, %33, %34, %35, %36, %37, %38, %39, %40, %41, %42, %43, %44, %45, %46, %47, %48, %49, %50, %51, %52, %53, %54, %55, %56, %57, %58, %59, %60, %61, %62, %63}, {%64, %65, %66, %67}, %68, p, 1, 1, 1;\n}\n"
    : "+f"(d[0]), "+f"(d[1]), "+f"(d[2]), "+f"(d[3]), "+f"(d[4]), "+f"(d[5]), "+f"(d[6]), "+f"(d[7]), "+f"(d[8]), "+f"(d[9]), "+f"(d[10]), "+f"(d[11]), "+f"(d[12]), "+f"(d[13]), "+f"(d[14]), "+f"(d[15]), "+f"(d[16]), "+f"(d[17]), "+f"(d[18]), "+f"(d[19]), "+f"(d[20]), "+f"(d[21]), "+f"(d[22]), "+f"(d[23]), "+f"(d[24]), "+f"(d[25]), "+f"(d[26]), "+f"(d[27]), "+f"(d[28]), "+f"(d[29]), "+f"(d[30]), "+f"(d[31]), "+f"(d[32]), "+f"(d[33]), "+f"(d[34]), "+f"(d[35]), "+f"(d[36]), "+f"(d[37]), "+f"(d[38]), "+f"(d[39]), "+f"(d[40]), "+f"(d[41]), "+f"(d[42]), "+f"(d[43]), "+f"(d[44]), "+f"(d[45]), "+f"(d[46]), "+f"(d[47]), "+f"(d[48]), "+f"(d[49]), "+f"(d[50]), "+f"(d[51]), "+f"(d[52]), "+f"(d[53]), "+f"(d[54]), "+f"(d[55]), "+f"(d[56]), "+f"(d[57]), "+f"(d[58]), "+f"(d[59]), "+f"(d[60]), "+f"(d[61]), "+f"(d[62]), "+f"(d[63])
    : "r"(a0), "r"(a1), "r"(a2), "r"(a3), "l"(db), "r"(scale_d));
}

__device__ __forceinline__ void wgmma_rs_n32_tb(float (&d)[16], uint32_t a0, uint32_t a1, uint32_t a2, uint32_t a3, uint64_t db, int scale_d) {
  asm volatile("{\n.reg .pred p;\nsetp.ne.b32 p, %21, 0;\n"
    "wgmma.mma_async.sync.aligned.m64n32k16.f32.bf16.bf16 {%0, %1, %2, %3, %4, %5, %6, %7, %8, %9, %10, %11, %12, %13, %14, %15}, {%16, %17, %18, %19}, %20, p, 1, 1, 1;\n}\n"
    : "+f"(d[0]), "+f"(d[1]), "+f"(d[2]), "+f"(d[3]), "+f"(d[4]), "+f"(d[5]), "+f"(d[6]), "+f"(d[7]), "+f"(d[8]), "+f"(d[9]), "+f"(d[10]), "+f"(d[11]), "+f"(d[12]), "+f"(d[13]), "+f"(d[14]), "+f"(d[15])
    : "r"(a0), "r"(a1), "r"(a2), "r"(a3), "l"(db), "r"(scale_d));
}

__device__ __forceinline__ void wgmma_rs_n64_tb(float (&d)[32], uint32_t a0, uint32_t a1, uint32_t a2, uint32_t a3, uint64_t db, int scale_d) {
  asm volatile("{\n.reg .pred p;\nsetp.ne.b32 p, %37, 0;\n"
    "wgmma.mma_async.sync.aligned.m64n64k16.f32.bf16.bf16 {%0, %1, %2, %3, %4, %5, %6, %7, %8, %9, %10, %11, %12, %13, %14, %15, %16, %17, %18, %19, %20, %21, %22, %23, %24, %25, %26, %27, %28, %29, %30, %31}, {%32, %33, %34, %35}, %36, p, 1, 1, 1;\n}\n"
    : "+f"(d[0]), "+f"(d[1]), "+f"(d[2]), "+f"(d[3]), "+f"(d[4]), "+f"(d[5]), "+f"(d[6]), "+f"(d[7]), "+f"(d[8]), "+f"(d[9]), "+f"(d[10]), "+f"(d[11]), "+f"(d[12]), "+f"(d[13]), "+f"(d[14]), "+f"(d[15]), "+f"(d[16]), "+f"(d[17]), "+f"(d[18]), "+f"(d[19]), "+f"(d[20]), "+f"(d[21]), "+f"(d[22]), "+f"(d[23]), "+f"(d[24]), "+f"(d[25]), "+f"(d[26]), "+f"(d[27]), "+f"(d[28]), "+f"(d[29]), "+f"(d[30]), "+f"(d[31])
    : "r"(a0), "r"(a1), "r"(a2), "r"(a3), "l"(db), "r"(scale_d));
}

__device__ __forceinline__ void wgmma_rs_n256_tb(float (&d)[64], float (&e)[64], uint32_t a0, uint32_t a1, uint32_t a2, uint32_t a3, uint64_t db, int scale_d) {
  asm volatile("{\n.reg .pred p;\nsetp.ne.b32 p, %133, 0;\n"
    "wgmma.mma_async.sync.aligned.m64n256k16.f32.bf16.bf16 {%0, %1, %2, %3, %4, %5, %6, %7, %8, %9, %10, %11, %12, %13, %14, %15, %16, %17, %18, %19, %20, %21, %22, %23, %24, %25, %26, %27, %28, %29, %30, %31, %32, %33, %34, %35, %36, %37, %38, %39, %40, %41, %42, %43, %44, %45, %46, %47, %48, %49, %50, %51, %52, %53, %54, %55, %56, %57, %58, %59, %60, %61, %62, %63, %64, %65, %66, %67, %68, %69, %70, %71, %72, %73, %74, %75, %76, %77, %78, %79, %80, %81, %82, %83, %84, %85, %86, %87, %88, %89, %90, %91, %92, %93, %94, %95, %96, %97, %98, %99, %100, %101, %102, %103, %104, %105, %106, %107, %108, %109, %110, %111, %112, %113, %114, %115, %116, %117, %118, %119, %120, %121, %122, %123, %124, %125, %126, %127}, {%128, %129, %130, %131}, %132, p, 1, 1, 1;\n}\n"
    : "+f"(d[0]), "+f"(d[1]), "+f"(d[2]), "+f"(d[3]), "+f"(d[4]), "+f"(d[5]), "+f"(d[6]), "+f"(d[7]), "+f"(d[8]), "+f"(d[9]), "+f"(d[10]), "+f"(d[11]), "+f"(d[12]), "+f"(d[13]), "+f"(d[14]), "+f"(d[15]), "+f"(d[16]), "+f"(d[17]), "+f"(d[18]), "+f"(d[19]), "+f"(d[20]), "+f"(d[21]), "+f"(d[22]), "+f"(d[23]), "+f"(d[24]), "+f"(d[25]), "+f"(d[26]), "+f"(d[27]), "+f"(d[28]), "+f"(d[29]), "+f"(d[30]), "+f"(d[31]), "+f"(d[32]), "+f"(d[33]), "+f"(d[34]), "+f"(d[35]), "+f"(d[36]), "+f"(d[37]), "+f"(d[38]), "+f"(d[39]), "+f"(d[40]), "+f"(d[41]), "+f"(d[42]), "+f"(d[43]), "+f"(d[44]), "+f"(d[45]), "+f"(d[46]), "+f"(d[47]), "+f"(d[48]), "+f"(d[49]), "+f"(d[50]), "+f"(d[51]), "+f"(d[52]), "+f"(d[53]), "+f"(d[54]), "+f"(d[55]), "+f"(d[56]), "+f"(d[57]), "+f"(d[58]), "+f"(d[59]), "+f"(d[60]), "+f"(d[61]), "+f"(d[62]), "+f"(d[63]), "+f"(e[0]), "+f"(e[1]), "+f"(e[2]), "+f"(e[3]), "+f"(e[4]), "+f"(e[5]), "+f"(e[6]), "+f"(e[7]), "+f"(e[8]), "+f"(e[9]), "+f"(e[10]), "+f"(e[11]), "+f"(e[12]), "+f"(e[13]), "+f"(e[14]), "+f"(e[15]), "+f"(e[16]), "+f"(e[17]), "+f"(e[18]), "+f"(e[19]), "+f"(e[20]), "+f"(e[21]), "+f"(e[22]), "+f"(e[23]), "+f"(e[24]), "+f"(e[25]), "+f"(e[26]), "+f"(e[27]), "+f"(e[28]), "+f"(e[29]), "+f"(e[30]), "+f"(e[31]), "+f"(e[32]), "+f"(e[33]), "+f"(e[34]), "+f"(e[35]), "+f"(e[36]), "+f"(e[37]), "+f"(e[38]), "+f"(e[39]), "+f"(e[40]), "+f"(e[41]), "+f"(e[42]), "+f"(e[43]), "+f"(e[44]), "+f"(e[45]), "+f"(e[46]), "+f"(e[47]), "+f"(e[48]), "+f"(e[49]), "+f"(e[50]), "+f"(e[51]), "+f"(e[52]), "+f"(e[53]), "+f"(e[54]), "+f"(e[55]), "+f"(e[56]), "+f"(e[57]), "+f"(e[58]), "+f"(e[59]), "+f"(e[60]), "+f"(e[61]), "+f"(e[62]), "+f"(e[63])
    : "r"(a0), "r"(a1), "r"(a2), "r"(a3), "l"(db), "r"(scale_d));
}

__device__ __forceinline__ void wgmma_rs_n128_z(float (&d)[64], uint32_t a0, uint32_t a1, uint32_t a2, uint32_t a3, uint64_t db) {
  asm volatile("{\n.reg .pred p;\nsetp.ne.b32 p, 0, 0;\n"
    "wgmma.mma_async.sync.aligned.m64n128k16.f32.bf16.bf16 {%0, %1, %2, %3, %4, %5, %6, %7, %8, %9, %10, %11, %12, %13, %14, %15, %16, %17, %18, %19, %20, %21, %22, %23, %24, %25, %26, %27, %28, %29, %30, %31, %32, %33, %34, %35, %36, %37, %38, %39, %40, %41, %42, %43, %44, %45, %46, %47, %48, %49, %50, %51, %52, %53, %54, %55, %56, %57, %58, %59, %60, %61, %62, %63}, {%64, %65, %66, %67}, %68, p, 1, 1, 0;\n}\n"
    : "=f"(d[0]), "=f"(d[1]), "=f"(d[2]), "=f"(d[3]), "=f"(d[4]), "=f"(d[5]), "=f"(d[6]), "=f"(d[7]), "=f"(d[8]), "=f"(d[9]), "=f"(d[10]), "=f"(d[11]), "=f"(d[12]), "=f"(d[13]), "=f"(d[14]), "=f"(d[15]), "=f"(d[16]), "=f"(d[17]), "=f"(d[18]), "=f"(d[19]), "=f"(d[20]), "=f"(d[21]), "=f"(d[22]), "=f"(d[23]), "=f"(d[24]), "=f"(d[25]), "=f"(d[26]), "=f"(d[27]), "=f"(d[28]), "=f"(d[29]), "=f"(d[30]), "=f"(d[31]), "=f"(d[32]), "=f"(d[33]), "=f"(d[34]), "=f"(d[35]), "=f"(d[36]), "=f"(d[37]), "=f"(d[38]), "=f"(d[39]), "=f"(d[40]), "=f"(d[41]), "=f"(d[42]), "=f"(d[43]), "=f"(d[44]), "=f"(d[45]), "=f"(d[46]), "=f"(d[47]), "=f"(d[48]), "=f"(d[49]), "=f"(d[50]), "=f"(d[51]), "=f"(d[52]), "=f"(d[53]), "=f"(d[54]), "=f"(d[55]), "=f"(d[56]), "=f"(d[57]), "=f"(d[58]), "=f"(d[59]), "=f"(d[60]), "=f"(d[61]), "=f"(d[62]), "=f"(d[63])
    : "r"(a0), "r"(a1), "r"(a2), "r"(a3), "l"(db));
}

__device__ __forceinline__ void wgmma_rs_n64_tb_z(float (&d)[32], uint32_t a0, uint32_t a1, uint32_t a2, uint32_t a3, uint64_t db) {
  asm volatile("{\n.reg .pred p;\nsetp.ne.b32 p, 0, 0;\n"
    "wgmma.mma_async.sync.aligned.m64n64k16.f32.bf16.bf16 {%0, %1, %2, %3, %4, %5, %6, %7, %8, %9, %10, %11, %12, %13, %14, %15, %16, %17, %18, %19, %20, %21, %22, %23, %24, %25, %26, %27, %28, %29, %30, %31}, {%32, %33, %34, %35}, %36, p, 1, 1, 1;\n}\n"
    : "=f"(d[0]), "=f"(d[1]), "=f"(d[2]), "=f"(d[3]), "=f"(d[4]), "=f"(d[5]), "=f"(d[6]), "=f"(d[7]), "=f"(d[8]), "=f"(d[9]), "=f"(d[10]), "=f"(d[11]), "=f"(d[12]), "=f"(d[13]), "=f"(d[14]), "=f"(d[15]), "=f"(d[16]), "=f"(d[17]), "=f"(d[18]), "=f"(d[19]), "=f"(d[20]), "=f"(d[21]), "=f"(d[22]), "=f"(d[23]), "=f"(d[24]), "=f"(d[25]), "=f"(d[26]), "=f"(d[27]), "=f"(d[28]), "=f"(d[29]), "=f"(d[30]), "=f"(d[31])
    : "r"(a0), "r"(a1), "r"(a2), "r"(a3), "l"(db));
}

__device__ __forceinline__ void wgmma_rs_n256_tb_z(float (&d)[64], float (&e)[64], uint32_t a0, uint32_t a1, uint32_t a2, uint32_t a3, uint64_t db) {
  asm volatile("{\n.reg .pred p;\nsetp.ne.b32 p, 0, 0;\n"
    "wgmma.mma_async.sync.aligned.m64n256k16.f32.bf16.bf16 {%0, %1, %2, %3, %4, %5, %6, %7, %8, %9, %10, %11, %12, %13, %14, %15, %16, %17, %18, %19, %20, %21, %22, %23, %24, %25, %26, %27, %28, %29, %30, %31, %32, %33, %34, %35, %36, %37, %38, %39, %40, %41, %42, %43, %44, %45, %46, %47, %48, %49, %50, %51, %52, %53, %54, %55, %56, %57, %58, %59, %60, %61, %62, %63, %64, %65, %66, %67, %68, %69, %70, %71, %72, %73, %74, %75, %76, %77, %78, %79, %80, %81, %82, %83, %84, %85, %86, %87, %88, %89, %90, %91, %92, %93, %94, %95, %96, %97, %98, %99, %100, %101, %102, %103, %104, %105, %106, %107, %108, %109, %110, %111, %112, %113, %114, %115, %116, %117, %118, %119, %120, %121, %122, %123, %124, %125, %126, %127}, {%128, %129, %130, %131}, %132, p, 1, 1, 1;\n}\n"
    : "=f"(d[0]), "=f"(d[1]), "=f"(d[2]), "=f"(d[3]), "=f"(d[4]), "=f"(d[5]), "=f"(d[6]), "=f"(d[7]), "=f"(d[8]), "=f"(d[9]), "=f"(d[10]), "=f"(d[11]), "=f"(d[12]), "=f"(d[13]), "=f"(d[14]), "=f"(d[15]), "=f"(d[16]), "=f"(d[17]), "=f"(d[18]), "=f"(d[19]), "=f"(d[20]), "=f"(d[21]), "=f"(d[22]), "=f"(d[23]), "=f"(d[24]), "=f"(d[25]), "=f"(d[26]), "=f"(d[27]), "=f"(d[28]), "=f"(d[29]), "=f"(d[30]), "=f"(d[31]), "=f"(d[32]), "=f"(d[33]), "=f"(d[34]), "=f"(d[35]), "=f"(d[36]), "=f"(d[37]), "=f"(d[38]), "=f"(d[39]), "=f"(d[40]), "=f"(d[41]), "=f"(d[42]), "=f"(d[43]), "=f"(d[44]), "=f"(d[45]), "=f"(d[46]), "=f"(d[47]), "=f"(d[48]), "=f"(d[49]), "=f"(d[50]), "=f"(d[51]), "=f"(d[52]), "=f"(d[53]), "=f"(d[54]), "=f"(d[55]), "=f"(d[56]), "=f"(d[57]), "=f"(d[58]), "=f"(d[59]), "=f"(d[60]), "=f"(d[61]), "=f"(d[62]), "=f"(d[63]), "=f"(e[0]), "=f"(e[1]), "=f"(e[2]), "=f"(e[3]), "=f"(e[4]), "=f"(e[5]), "=f"(e[6]), "=f"(e[7]), "=f"(e[8]), "=f"(e[9]), "=f"(e[10]), "=f"(e[11]), "=f"(e[12]), "=f"(e[13]), "=f"(e[14]), "=f"(e[15]), "=f"(e[16]), "=f"(e[17]), "=f"(e[18]), "=f"(e[19]), "=f"(e[20]), "=f"(e[21]), "=f"(e[22]), "=f"(e[23]), "=f"(e[24]), "=f"(e[25]), "=f"(e[26]), "=f"(e[27]), "=f"(e[28]), "=f"(e[29]), "=f"(e[30]), "=f"(e[31]), "=f"(e[32]), "=f"(e[33]), "=f"(e[34]), "=f"(e[35]), "=f"(e[36]), "=f"(e[37]), "=f"(e[38]), "=f"(e[39]), "=f"(e[40]), "=f"(e[41]), "=f"(e[42]), "=f"(e[43]), "=f"(e[44]), "=f"(e[45]), "=f"(e[46]), "=f"(e[47]), "=f"(e[48]), "=f"(e[49]), "=f"(e[50]), "=f"(e[51]), "=f"(e[52]), "=f"(e[53]), "=f"(e[54]), "=f"(e[55]), "=f"(e[56]), "=f"(e[57]), "=f"(e[58]), "=f"(e[59]), "=f"(e[60]), "=f"(e[61]), "=f"(e[62]), "=f"(e[63])
    : "r"(a0), "r"(a1), "r"(a2), "r"(a3), "l"(db));
}

struct Maps {
  CUtensorMap x[2], k[2], v[2], wq[2], wo[2], wo2[2];
};

__global__ void __cluster_dims__(2, 1, 1) __launch_bounds__(384, 1)
fused_gqa_kernel(const __grid_constant__ Maps maps, __nv_bfloat16* __restrict__ out) {
  extern __shared__ __align__(1024) unsigned char smem[];
  const uint32_t sbase = smem_u32(smem);
  const uint32_t full0 = sbase + BAR_OFF;
  const uint32_t empty0 = full0 + N_ITEMS * 8;
  const uint32_t ready0 = empty0 + N_ITEMS * 8;
  const uint32_t pub0 = ready0 + 6 * 8;

  const int tid = threadIdx.x;
  const int wg = tid >> 7;
  const int bid = blockIdx.x;
  const int bp = bid & 3;
  const int h = (bid >> 2) & 15;
  const int p = bid >> 6;

  if (tid == 0) {
#pragma unroll
    for (int i = 0; i < 3; i++) mbar_init(full0 + (WQ0 + i) * 8, 1);
#pragma unroll
    for (int i = 0; i < 2; i++) mbar_init(full0 + (X0 + i) * 8, 1);
    asm volatile("fence.mbarrier_init.release.cluster;" ::: "memory");
#pragma unroll
    for (int kc = 0; kc < 3; kc++) {
      if (kc < 2) {
        mbar_expect_tx(full0 + (X0 + kc) * 8, 16384);
        tma_load3(sbase + x_off(kc), &maps.x[p], 0, bp * 128, kc, full0 + (X0 + kc) * 8);
      }
      mbar_expect_tx(full0 + (WQ0 + kc) * 8, T32);
      tma_load3(sbase + wq_off(kc), &maps.wq[p], 0, kc * 64, h * 4, full0 + (WQ0 + kc) * 8);
    }
    TR(0, 56);
  } else if (tid == 64) {
    if (3 + bp < 9) tma_prefetch3(&maps.wq[p], 0, (3 + bp) * 64, h * 4);
    if (7 + bp < 9) tma_prefetch3(&maps.wq[p], 0, (7 + bp) * 64, h * 4);
    if (h >= 2 && h < 9) tma_prefetch3(&maps.x[p], 0, bp * 128, h);
  } else if (tid == 32) {
    prefetch_tmap(&maps.k[p]);
    prefetch_tmap(&maps.v[p]);
    prefetch_tmap(&maps.wo[p]);
    prefetch_tmap(&maps.wo2[p]);
  } else if (tid >= 128) {
    const int i = tid - 128;
    if (i < N_ITEMS) {
      if (!(i < 3 || i == X0 || i == X0 + 1)) mbar_init(full0 + i * 8, 1);
    } else if (i >= 64 && i < 64 + N_ITEMS) {
      mbar_init(empty0 + (i - 64) * 8, 8);
    } else if (i >= 128 && i < 128 + 6) {
      mbar_init(ready0 + (i - 128) * 8, 1);
    } else if (i >= 160 && i < 160 + 6) {
      mbar_init(pub0 + (i - 160) * 8, 4);
    }
    asm volatile("fence.mbarrier_init.release.cluster;" ::: "memory");
  }
  __syncthreads();
  if (tid == 0) TR(0, 57);

  if (wg == 0) {
    asm volatile("setmaxnreg.dec.sync.aligned.u32 24;");
    if (tid == 0) {
#pragma unroll 1
      for (int kc = 2; kc < 9; kc++) {
        mbar_wait(empty0 + (X0 + kc - 2) * 8);
        mbar_expect_tx(full0 + (X0 + kc) * 8, 16384);
        tma_load3(sbase + x_off(kc), &maps.x[p], 0, bp * 128, kc, full0 + (X0 + kc) * 8);
        if (kc < 8) {
          TR(0, WQ0 + kc + 1);
          mbar_expect_tx(full0 + (WQ0 + kc + 1) * 8, T32);
          tma_load3(sbase + wq_off(kc + 1), &maps.wq[p], 0, (kc + 1) * 64, h * 4, full0 + (WQ0 + kc + 1) * 8);
        }
      }
#pragma unroll 1
      for (int m = 0; m < N_WO; m++) {
        const int dep = m >= 5 ? WO0 + m - 5 : (m < 3 ? X0 + 6 + m : KV0 + 10 + m);
        mbar_wait(empty0 + dep * 8);
        const uint32_t fb = full0 + (WO0 + m) * 8;
        TR(0, WO0 + m);
        mbar_expect_tx(fb, T32);
        if (m < 8) tma_load3(sbase + wo_off(m), &maps.wo[p], 0, h * 256 + (m & 3) * 64, (m >> 2) * 4, fb);
        else tma_load3(sbase + wo_off(m), &maps.wo2[p], 0, h * 256, 8, fb);
      }
    } else if (tid == 96) {
#pragma unroll 1
      for (int n = 0; n < N_KV; n++) {
        if (n >= 3) mbar_wait(empty0 + (KV0 + n - 3) * 8);
        if (n >= KV_INFLIGHT) mbar_wait(full0 + (KV0 + n - KV_INFLIGHT) * 8);
        const uint32_t fb = full0 + (KV0 + n) * 8;
        const CUtensorMap* tm = (n & 1) ? &maps.v[p] : &maps.k[p];
        const int row = ((2 * bp + (n >> 3)) * 16 + h) * kSK + ((n & 7) >> 1) * 128;
        TR(0, KV0 + n);
        mbar_expect_tx(fb, T32);
        tma_load3(sbase + kv_off(n), tm, 0, row, 0, fb);
        if (n == WO_PF_AT) {
          tma_prefetch3(&maps.wo[p], 0, h * 256 + bp * 64, 4);
          if (bp == 0) tma_prefetch3(&maps.wo[p], 0, h * 256 + 192, 0);
          if (bp == 1) tma_prefetch3(&maps.wo2[p], 0, h * 256, 8);
        }
      }
    } else if (tid == 32 || tid == 64) {
      const int w = (tid >> 5) - 1;
      const int tile = p * 8 + 2 * bp + w;
      unsigned target[3];
#pragma unroll
      for (int pn = 0; pn < 3; pn++) {
        unsigned v;
        asm volatile("ld.relaxed.gpu.global.u32 %0, [%1];" : "=r"(v) : "l"(&g_cnt[(tile * 4 + pn) * 32]) : "memory");
        target[pn] = (v / 16u + 1u) * 16u;
      }
#pragma unroll 1
      for (int e = 0; e < 3; e++) {
        mbar_wait(pub0 + (w * 3 + e) * 8);
        __threadfence();
        asm volatile("red.relaxed.gpu.global.add.u32 [%0], 1;" ::"l"(&g_cnt[(tile * 4 + e) * 32]) : "memory");
      }
#pragma unroll
      for (int pn = 0; pn < 3; pn++) {
        const unsigned* c = &g_cnt[(tile * 4 + pn) * 32];
        for (uint32_t it = 0; it < WAIT_LIMIT; ++it) {
          unsigned v;
          asm volatile("ld.acquire.gpu.global.u32 %0, [%1];" : "=r"(v) : "l"(c) : "memory");
          if ((int)(v - target[pn]) >= 0) break;
        }
        mbar_arrive(ready0 + (w * 3 + pn) * 8);
      }
    }
  } else {
    asm volatile("setmaxnreg.inc.sync.aligned.u32 240;");
    const int w = wg - 1;
    const int t128 = tid & 127;
    const int lane = tid & 31;

    auto release = [&](int item) {
      __syncwarp();
      if (lane == 0) mbar_arrive(empty0 + item * 8);
    };

    TRC(0);
    const float cs = 0.08838834764831845f * 1.4426950408889634f;
    float s[64], o[64];
#pragma unroll
    for (int i = 0; i < 64; i++) s[i] = 0.f, o[i] = 0.f;
    uint32_t qf[32];
    uint4* park = reinterpret_cast<uint4*>(smem + PARK_OFF) + w * 1024 + t128;
    {
#pragma unroll 1
      for (int kc = 0; kc < 9; kc++) {
        mbar_wait(full0 + (X0 + kc) * 8);
        mbar_wait(full0 + (WQ0 + kc) * 8);
        if (kc == 0) TRC(1);
        const uint64_t da = make_desc(sbase + x_off(kc), 16, 1024);
        const uint64_t db = make_desc(sbase + wq_off(kc) + w * 16384, 8192, 1024);
        wg_fence();
#pragma unroll
        for (int ks = 0; ks < 4; ks++) {
          wgmma_ss_n128_tb(s, da + ks * 2, db + ks * 128, (kc | ks) != 0);
          wgmma_ss_n128_tb(o, da + 512 + ks * 2, db + ks * 128, (kc | ks) != 0);
        }
        wg_commit();
        wg_wait<0>();
        release(X0 + kc);
      }
      fence_regs(s);
      fence_regs(o);
#pragma unroll
      for (int i = 0; i < 32; i++) qf[i] = pack_bf16(s[2 * i], s[2 * i + 1]);
      named_bar(1, 256);
#pragma unroll
      for (int i = 0; i < 8; i++) park[i * 128] = pack8(o, i);
      TRC(2);
    }
#pragma unroll 1
    for (int bb = 0; bb < 2; bb++) {
#pragma unroll
      for (int i = 0; i < 64; i++) o[i] = 0.f;
      float m0 = -INFINITY, m1 = -INFINITY, l0 = 0.f, l1 = 0.f;
#pragma unroll 1
      for (int t = 0; t < 4; t++) {
        const int n = bb * 8 + t * 2;
        {
          const uint32_t base = sbase + kv_off(n);
          mbar_wait(full0 + (KV0 + n) * 8);
          if (n == 0 && w == 1) named_bar(4, 256);
          const uint64_t db = make_desc(base, 16, 1024);
          wg_fence();
          wgmma_rs_n128_z(s, qf[0], qf[1], qf[2], qf[3], db);
#pragma unroll
          for (int ks = 1; ks < 8; ks++)
            wgmma_rs_n128(s, qf[4 * ks], qf[4 * ks + 1], qf[4 * ks + 2], qf[4 * ks + 3], db + (ks >> 2) * 1024 + (ks & 3) * 2, 1);
          wg_commit();
          wg_wait<0>();
          fence_regs(s);
          if (n == 0 && w == 0) named_arrive(4, 256);
          release(KV0 + n);
        }
        float mx0 = s[0], mx1 = s[2];
#pragma unroll
        for (int g = 0; g < 16; g++) {
          mx0 = fmaxf(mx0, fmaxf(s[4 * g], s[4 * g + 1]));
          mx1 = fmaxf(mx1, fmaxf(s[4 * g + 2], s[4 * g + 3]));
        }
        mx0 = fmaxf(mx0, __shfl_xor_sync(0xffffffffu, mx0, 1));
        mx0 = fmaxf(mx0, __shfl_xor_sync(0xffffffffu, mx0, 2));
        mx1 = fmaxf(mx1, __shfl_xor_sync(0xffffffffu, mx1, 1));
        mx1 = fmaxf(mx1, __shfl_xor_sync(0xffffffffu, mx1, 2));
        const float mn0 = fmaxf(m0, mx0), mn1 = fmaxf(m1, mx1);
        const float a0 = ex2((m0 - mn0) * cs), a1 = ex2((m1 - mn1) * cs);
        m0 = mn0;
        m1 = mn1;
        const float ms0 = mn0 * cs, ms1 = mn1 * cs;
        float rs0 = 0.f, rs1 = 0.f;
        uint32_t pf[32];
#pragma unroll
        for (int g = 0; g < 16; g++) {
          const float p0 = ex2(fmaf(s[4 * g], cs, -ms0));
          const float p1 = ex2(fmaf(s[4 * g + 1], cs, -ms0));
          const float p2 = ex2(fmaf(s[4 * g + 2], cs, -ms1));
          const float p3 = ex2(fmaf(s[4 * g + 3], cs, -ms1));
          rs0 += p0 + p1;
          rs1 += p2 + p3;
          pf[2 * g] = pack_bf16(p0, p1);
          pf[2 * g + 1] = pack_bf16(p2, p3);
        }
        l0 = l0 * a0 + rs0;
        l1 = l1 * a1 + rs1;
#pragma unroll
        for (int g = 0; g < 16; g++) {
          o[4 * g] *= a0;
          o[4 * g + 1] *= a0;
          o[4 * g + 2] *= a1;
          o[4 * g + 3] *= a1;
        }
        {
          const uint32_t base = sbase + kv_off(n + 1);
          mbar_wait(full0 + (KV0 + n + 1) * 8);
          const uint64_t db = make_desc(base, 16384, 1024);
          wg_fence();
#pragma unroll
          for (int ks = 0; ks < 8; ks++)
            wgmma_rs_n128_tb(o, pf[4 * ks], pf[4 * ks + 1], pf[4 * ks + 2], pf[4 * ks + 3], db + ks * 128, 1);
          wg_commit();
          wg_wait<0>();
          fence_regs(o);
          release(KV0 + n + 1);
          TRC(3 + bb * 5 + t);
        }
      }
      l0 += __shfl_xor_sync(0xffffffffu, l0, 1);
      l0 += __shfl_xor_sync(0xffffffffu, l0, 2);
      l1 += __shfl_xor_sync(0xffffffffu, l1, 1);
      l1 += __shfl_xor_sync(0xffffffffu, l1, 2);
      const float i0 = 1.f / l0, i1 = 1.f / l1;
      uint4* dst = park;
      if (bb == 0) {
#pragma unroll
        for (int i = 0; i < 8; i++) {
          const uint4 v = park[i * 128];
          qf[4 * i] = v.x;
          qf[4 * i + 1] = v.y;
          qf[4 * i + 2] = v.z;
          qf[4 * i + 3] = v.w;
        }
      } else {
        named_bar(1, 256);
        dst = reinterpret_cast<uint4*>(smem + KV_OFF) + w * 1024 + t128;
      }
#pragma unroll
      for (int i = 0; i < 8; i++)
        dst[i * 128] = make_uint4(pack_bf16(o[8 * i] * i0, o[8 * i + 1] * i0), pack_bf16(o[8 * i + 2] * i1, o[8 * i + 3] * i1),
                                  pack_bf16(o[8 * i + 4] * i0, o[8 * i + 5] * i0), pack_bf16(o[8 * i + 6] * i1, o[8 * i + 7] * i1));
    }
    uint32_t af[64];
    {
      named_bar(1, 256);
      const uint4* src = reinterpret_cast<const uint4*>(smem + (w == 0 ? PARK_OFF : KV_OFF)) + t128;
#pragma unroll
      for (int i = 0; i < 16; i++) {
        const uint4 v = src[i * 128];
        af[4 * i] = v.x;
        af[4 * i + 1] = v.y;
        af[4 * i + 2] = v.z;
        af[4 * i + 3] = v.w;
      }
    }
    TRC(12);
    if (w == 1) named_bar(4, 256);
    const int tile = p * 8 + 2 * bp + w;
    uint4* part = g_part + (size_t)(tile * 16 + h) * 36 * 128 + t128;
#pragma unroll
    for (int pn = 0; pn < 2; pn++) {
#pragma unroll
      for (int kc = 0; kc < 4; kc++) {
        const int m = pn * 4 + kc;
        mbar_wait(full0 + (WO0 + m) * 8);
        const uint64_t db = make_desc(sbase + wo_off(m), 8192, 1024);
        wg_fence();
#pragma unroll
        for (int ks = 0; ks < 4; ks++) {
          const int a = (kc * 4 + ks) * 4;
          if ((kc | ks) == 0) wgmma_rs_n256_tb_z(s, o, af[a], af[a + 1], af[a + 2], af[a + 3], db);
          else wgmma_rs_n256_tb(s, o, af[a], af[a + 1], af[a + 2], af[a + 3], db + ks * 128, 1);
        }
        wg_commit();
        if (m == 1 && w == 0) named_arrive(4, 256);
        if (kc > 0) {
          wg_wait<1>();
          if (m - 1 < 4) release(WO0 + m - 1);
        }
      }
      wg_wait<0>();
      fence_regs(s);
      fence_regs(o);
      if (pn == 0) release(WO0 + 3);
      TRC(13 + pn * 2);
#pragma unroll
      for (int i = 0; i < 8; i++) __stcg(part + (pn * 16 + i) * 128, pack8(s, i));
#pragma unroll
      for (int i = 0; i < 8; i++) __stcg(part + (pn * 16 + 8 + i) * 128, pack8(o, i));
      __syncwarp();
      if (lane == 0) mbar_arrive(pub0 + (w * 3 + pn) * 8);
      TRC(14 + pn * 2);
    }
    {
      float acc[32];
      mbar_wait(full0 + (WO0 + 8) * 8);
      const uint64_t db = make_desc(sbase + wo_off(8), 8192, 1024);
      wg_fence();
      wgmma_rs_n64_tb_z(acc, af[0], af[1], af[2], af[3], db);
#pragma unroll
      for (int ks = 1; ks < 16; ks++)
        wgmma_rs_n64_tb(acc, af[4 * ks], af[4 * ks + 1], af[4 * ks + 2], af[4 * ks + 3], db + ks * 128, 1);
      wg_commit();
      wg_wait<0>();
      fence_regs(acc);
#pragma unroll
      for (int i = 0; i < 4; i++) __stcg(part + (32 + i) * 128, pack8(acc, i));
      __syncwarp();
      if (lane == 0) mbar_arrive(pub0 + (w * 3 + 2) * 8);
      TRC(17);
    }
    const int row0 = (t128 >> 5) * 16 + (lane >> 2);
    const int q2 = (lane & 3) * 2;
    __nv_bfloat16* orow = out + (size_t)((2 * bp + w) * 64 + row0) * 1152 + p * 576;
    const uint4* pr = g_part + (size_t)(tile * 16) * 36 * 128 + t128;
    uint4 v[3][16];
    const bool act2 = ((t128 >> 5) == (h >> 2));
#pragma unroll
    for (int pn = 0; pn < 3; pn++) {
      mbar_wait(ready0 + (w * 3 + pn) * 8);
      TRC(18 + pn);
      const int slot = pn < 2 ? pn * 16 + h : 32 + (h & 3);
      if (pn < 2 || act2) {
#pragma unroll
        for (int c = 0; c < 16; c++) v[pn][c] = __ldcg(pr + (size_t)(c * 36 + slot) * 128);
      }
    }
#pragma unroll
    for (int pn = 0; pn < 3; pn++) {
      const int col = pn < 2 ? pn * 256 + h * 16 + q2 : 512 + (h & 3) * 16 + q2;
      if (pn < 2 || act2) {
        float a[8];
#pragma unroll
        for (int e = 0; e < 8; e++) a[e] = 0.f;
#pragma unroll
        for (int c = 0; c < 16; c++) {
          a[0] += bf_lo(v[pn][c].x);
          a[1] += bf_hi(v[pn][c].x);
          a[2] += bf_lo(v[pn][c].y);
          a[3] += bf_hi(v[pn][c].y);
          a[4] += bf_lo(v[pn][c].z);
          a[5] += bf_hi(v[pn][c].z);
          a[6] += bf_lo(v[pn][c].w);
          a[7] += bf_hi(v[pn][c].w);
        }
        *reinterpret_cast<uint32_t*>(orow + col) = pack_bf16(a[0], a[1]);
        *reinterpret_cast<uint32_t*>(orow + 8 * 1152 + col) = pack_bf16(a[2], a[3]);
        *reinterpret_cast<uint32_t*>(orow + col + 8) = pack_bf16(a[4], a[5]);
        *reinterpret_cast<uint32_t*>(orow + 8 * 1152 + col + 8) = pack_bf16(a[6], a[7]);
      }
    }
    TRC(21);
  }
}

typedef CUresult (*EncodeFn)(CUtensorMap*, CUtensorMapDataType, cuuint32_t, void*, const cuuint64_t*, const cuuint64_t*,
                             const cuuint32_t*, const cuuint32_t*, CUtensorMapInterleave, CUtensorMapSwizzle,
                             CUtensorMapL2promotion, CUtensorMapFloatOOBfill);

void encode3d(EncodeFn fn, CUtensorMap* m, void* ptr, uint64_t cols, uint64_t rows, uint32_t box_rows, uint32_t box_chunks) {
  cuuint64_t dims[3] = {64, rows, cols / 64};
  cuuint64_t strides[2] = {cols * 2, 128};
  cuuint32_t box[3] = {64, box_rows, box_chunks};
  cuuint32_t es[3] = {1, 1, 1};
  fn(m, CU_TENSOR_MAP_DATA_TYPE_BFLOAT16, 3, ptr, dims, strides, box, es, CU_TENSOR_MAP_INTERLEAVE_NONE,
     CU_TENSOR_MAP_SWIZZLE_128B, CU_TENSOR_MAP_L2_PROMOTION_L2_256B, CU_TENSOR_MAP_FLOAT_OOB_FILL_NONE);
}

}

extern "C" void kernel_launch(void* const* d_in, const int* in_sizes, int n_in, void* d_out, int out_size) {
  static EncodeFn fn = nullptr;
  if (!fn) {
    void* f = nullptr;
    cudaDriverEntryPointQueryResult st;
    cudaGetDriverEntryPoint("cuTensorMapEncodeTiled", &f, cudaEnableDefault, &st);
    fn = (EncodeFn)f;
    cudaFuncSetAttribute(fused_gqa_kernel, cudaFuncAttributeMaxDynamicSharedMemorySize, SMEM_BYTES);
  }
  Maps maps;
  for (int p = 0; p < 2; p++) {
    encode3d(fn, &maps.x[p], d_in[p * 5 + 0], kD, 512, 128, 1);
    encode3d(fn, &maps.k[p], d_in[p * 5 + 1], kDH, 8 * 16 * kSK, 128, 2);
    encode3d(fn, &maps.v[p], d_in[p * 5 + 2], kDH, 8 * 16 * kSK, 128, 2);
    encode3d(fn, &maps.wq[p], d_in[p * 5 + 3], kHQD, kD, 64, 4);
    encode3d(fn, &maps.wo[p], d_in[p * 5 + 4], kD, kHQD, 64, 4);
    encode3d(fn, &maps.wo2[p], d_in[p * 5 + 4], kD, kHQD, 256, 1);
  }
  fused_gqa_kernel<<<128, 384, SMEM_BYTES>>>(maps, (__nv_bfloat16*)d_out);
}
```

```cpp
#include <cuda_runtime.h>
#include <cuda_bf16.h>
#include <cuda.h>
#include <stdint.h>

namespace {

constexpr int kD = 576, kHQD = 4096, kSK = 512, kDH = 128;

constexpr int N_WQ = 9, N_X = 9, N_KV = 16, N_WO = 12;
constexpr int N_ITEMS = N_WQ + N_X + N_KV + N_WO;
constexpr int T32 = 32 * 1024;
constexpr int WO_BYTES = 24 * 1024;
constexpr int KV_OFF = 96 * 1024;
constexpr int PARK_OFF = 192 * 1024;
constexpr int BAR_OFF = 224 * 1024;
constexpr int SMEM_BYTES = BAR_OFF + 2 * N_ITEMS * 8 + 256;
constexpr int WQ0 = 0, X0 = N_WQ, KV0 = X0 + N_X, WO0 = KV0 + N_KV;
#define KV_INFLIGHT 2

__device__ __forceinline__ int wq_off(int kc) { return (kc % 6) * T32; }
__device__ __forceinline__ int x_off(int kc) { return PARK_OFF + (kc & 1) * 16384; }
__device__ __forceinline__ int kv_off(int n) { return KV_OFF + (n % 3) * T32; }
__device__ __forceinline__ int wo_off(int m) {
  const int s = m % 6;
  return s < 4 ? s * WO_BYTES : KV_OFF + (s - 3) * T32;
}

__device__ uint4 g_part[16 * 16 * 36 * 128];
__device__ unsigned int g_cnt[16 * 4 * 32];

#define TR(role, ev)
#define TRC(ev)
constexpr uint32_t WAIT_CYCLES = 1u << 20;
constexpr uint32_t WAIT_LIMIT = 1u << 12;
__device__ __forceinline__ uint32_t smem_u32(const void* p) { return (uint32_t)__cvta_generic_to_shared(p); }
__device__ __forceinline__ void mbar_init(uint32_t bar, uint32_t cnt) {
  asm volatile("mbarrier.init.shared::cta.b64 [%0], %1;" ::"r"(bar), "r"(cnt) : "memory");
}
__device__ __forceinline__ void mbar_expect_tx(uint32_t bar, uint32_t bytes) {
  asm volatile("mbarrier.arrive.expect_tx.shared::cta.b64 _, [%0], %1;" ::"r"(bar), "r"(bytes) : "memory");
}
__device__ __forceinline__ void mbar_arrive(uint32_t bar) {
  asm volatile("mbarrier.arrive.shared::cta.b64 _, [%0];" ::"r"(bar) : "memory");
}
__device__ __forceinline__ bool mbar_try(uint32_t bar, uint32_t parity) {
  uint32_t ok;
  asm volatile(
      "{\n.reg .pred p;\nmbarrier.try_wait.parity.shared::cta.b64 p, [%1], %2;\nselp.u32 %0, 1, 0, p;\n}\n"
      : "=r"(ok)
      : "r"(bar), "r"(parity)
      : "memory");
  return ok != 0;
}
__device__ __forceinline__ void mbar_wait(uint32_t bar) {
  if (mbar_try(bar, 0)) return;
  const uint32_t t0 = (uint32_t)clock();
  while (!mbar_try(bar, 0))
    if ((uint32_t)clock() - t0 > WAIT_CYCLES) break;
}
__device__ __forceinline__ void tma_load3(uint32_t dst, const CUtensorMap* tm, int c0, int c1, int c2, uint32_t bar) {
  asm volatile(
      "cp.async.bulk.tensor.3d.shared::cluster.global.mbarrier::complete_tx::bytes [%0], [%1, {%3, %4, %5}], [%2];" ::"r"(dst),
      "l"(tm), "r"(bar), "r"(c0), "r"(c1), "r"(c2)
      : "memory");
}
__device__ __forceinline__ void l2_prefetch(const void* p) { asm volatile("prefetch.global.L2 [%0];" ::"l"(p) : "memory"); }
__device__ __forceinline__ void prefetch_tmap(const CUtensorMap* tm) {
  asm volatile("prefetch.tensormap [%0];" ::"l"(tm) : "memory");
}
__device__ __forceinline__ void named_bar(int id, int n) { asm volatile("bar.sync %0, %1;" ::"r"(id), "r"(n) : "memory"); }
__device__ __forceinline__ void named_arrive(int id, int n) { asm volatile("bar.arrive %0, %1;" ::"r"(id), "r"(n) : "memory"); }
__device__ __forceinline__ void wg_fence() { asm volatile("wgmma.fence.sync.aligned;" ::: "memory"); }
__device__ __forceinline__ void wg_commit() { asm volatile("wgmma.commit_group.sync.aligned;" ::: "memory"); }
template <int N>
__device__ __forceinline__ void wg_wait() { asm volatile("wgmma.wait_group.sync.aligned %0;" ::"n"(N) : "memory"); }
template <int N>
__device__ __forceinline__ void fence_regs(float (&d)[N]) {
#pragma unroll
  for (int i = 0; i < N; i++) asm volatile("" : "+f"(d[i])::"memory");
}
__device__ __forceinline__ void fence_regs32(float (&d)[64]) {
#pragma unroll
  for (int i = 0; i < 32; i++) asm volatile("" : "+f"(d[i])::"memory");
}
__device__ __forceinline__ uint64_t make_desc(uint32_t addr, uint32_t lbo, uint32_t sbo) {
  return (uint64_t)((addr & 0x3FFFF) >> 4) | ((uint64_t)(lbo >> 4) << 16) | ((uint64_t)(sbo >> 4) << 32) | (1ull << 62);
}
__device__ __forceinline__ uint32_t pack_bf16(float lo, float hi) {
  uint32_t r;
  asm("cvt.rn.bf16x2.f32 %0, %1, %2;" : "=r"(r) : "f"(hi), "f"(lo));
  return r;
}
__device__ __forceinline__ float ex2(float x) {
  float y;
  asm("ex2.approx.ftz.f32 %0, %1;" : "=f"(y) : "f"(x));
  return y;
}
__device__ __forceinline__ float bf_lo(uint32_t v) { return __uint_as_float(v << 16); }
__device__ __forceinline__ float bf_hi(uint32_t v) { return __uint_as_float(v & 0xffff0000u); }
template <int N>
__device__ __forceinline__ uint4 pack8(const float (&a)[N], int i) {
  return make_uint4(pack_bf16(a[8 * i], a[8 * i + 1]), pack_bf16(a[8 * i + 2], a[8 * i + 3]), pack_bf16(a[8 * i + 4], a[8 * i + 5]),
                    pack_bf16(a[8 * i + 6], a[8 * i + 7]));
}

__device__ __forceinline__ void wgmma_ss_n128_tb(float (&d)[64], uint64_t da, uint64_t db, int scale_d) {
  asm volatile("{\n.reg .pred p;\nsetp.ne.b32 p, %66, 0;\n"
    "wgmma.mma_async.sync.aligned.m64n128k16.f32.bf16.bf16 {%0, %1, %2, %3, %4, %5, %6, %7, %8, %9, %10, %11, %12, %13, %14, %15, %16, %17, %18, %19, %20, %21, %22, %23, %24, %25, %26, %27, %28, %29, %30, %31, %32, %33, %34, %35, %36, %37, %38, %39, %40, %41, %42, %43, %44, %45, %46, %47, %48, %49, %50, %51, %52, %53, %54, %55, %56, %57, %58, %59, %60, %61, %62, %63}, %64, %65, p, 1, 1, 0, 1;\n}\n"
    : "+f"(d[0]), "+f"(d[1]), "+f"(d[2]), "+f"(d[3]), "+f"(d[4]), "+f"(d[5]), "+f"(d[6]), "+f"(d[7]), "+f"(d[8]), "+f"(d[9]), "+f"(d[10]), "+f"(d[11]), "+f"(d[12]), "+f"(d[13]), "+f"(d[14]), "+f"(d[15]), "+f"(d[16]), "+f"(d[17]), "+f"(d[18]), "+f"(d[19]), "+f"(d[20]), "+f"(d[21]), "+f"(d[22]), "+f"(d[23]), "+f"(d[24]), "+f"(d[25]), "+f"(d[26]), "+f"(d[27]), "+f"(d[28]), "+f"(d[29]), "+f"(d[30]), "+f"(d[31]), "+f"(d[32]), "+f"(d[33]), "+f"(d[34]), "+f"(d[35]), "+f"(d[36]), "+f"(d[37]), "+f"(d[38]), "+f"(d[39]), "+f"(d[40]), "+f"(d[41]), "+f"(d[42]), "+f"(d[43]), "+f"(d[44]), "+f"(d[45]), "+f"(d[46]), "+f"(d[47]), "+f"(d[48]), "+f"(d[49]), "+f"(d[50]), "+f"(d[51]), "+f"(d[52]), "+f"(d[53]), "+f"(d[54]), "+f"(d[55]), "+f"(d[56]), "+f"(d[57]), "+f"(d[58]), "+f"(d[59]), "+f"(d[60]), "+f"(d[61]), "+f"(d[62]), "+f"(d[63])
    : "l"(da), "l"(db), "r"(scale_d));
}

__device__ __forceinline__ void wgmma_rs_n128(float (&d)[64], uint32_t a0, uint32_t a1, uint32_t a2, uint32_t a3, uint64_t db, int scale_d) {
  asm volatile("{\n.reg .pred p;\nsetp.ne.b32 p, %69, 0;\n"
    "wgmma.mma_async.sync.aligned.m64n128k16.f32.bf16.bf16 {%0, %1, %2, %3, %4, %5, %6, %7, %8, %9, %10, %11, %12, %13, %14, %15, %16, %17, %18, %19, %20, %21, %22, %23, %24, %25, %26, %27, %28, %29, %30, %31, %32, %33, %34, %35, %36, %37, %38, %39, %40, %41, %42, %43, %44, %45, %46, %47, %48, %49, %50, %51, %52, %53, %54, %55, %56, %57, %58, %59, %60, %61, %62, %63}, {%64, %65, %66, %67}, %68, p, 1, 1, 0;\n}\n"
    : "+f"(d[0]), "+f"(d[1]), "+f"(d[2]), "+f"(d[3]), "+f"(d[4]), "+f"(d[5]), "+f"(d[6]), "+f"(d[7]), "+f"(d[8]), "+f"(d[9]), "+f"(d[10]), "+f"(d[11]), "+f"(d[12]), "+f"(d[13]), "+f"(d[14]), "+f"(d[15]), "+f"(d[16]), "+f"(d[17]), "+f"(d[18]), "+f"(d[19]), "+f"(d[20]), "+f"(d[21]), "+f"(d[22]), "+f"(d[23]), "+f"(d[24]), "+f"(d[25]), "+f"(d[26]), "+f"(d[27]), "+f"(d[28]), "+f"(d[29]), "+f"(d[30]), "+f"(d[31]), "+f"(d[32]), "+f"(d[33]), "+f"(d[34]), "+f"(d[35]), "+f"(d[36]), "+f"(d[37]), "+f"(d[38]), "+f"(d[39]), "+f"(d[40]), "+f"(d[41]), "+f"(d[42]), "+f"(d[43]), "+f"(d[44]), "+f"(d[45]), "+f"(d[46]), "+f"(d[47]), "+f"(d[48]), "+f"(d[49]), "+f"(d[50]), "+f"(d[51]), "+f"(d[52]), "+f"(d[53]), "+f"(d[54]), "+f"(d[55]), "+f"(d[56]), "+f"(d[57]), "+f"(d[58]), "+f"(d[59]), "+f"(d[60]), "+f"(d[61]), "+f"(d[62]), "+f"(d[63])
    : "r"(a0), "r"(a1), "r"(a2), "r"(a3), "l"(db), "r"(scale_d));
}

__device__ __forceinline__ void wgmma_rs_n128_tb(float (&d)[64], uint32_t a0, uint32_t a1, uint32_t a2, uint32_t a3, uint64_t db, int scale_d) {
  asm volatile("{\n.reg .pred p;\nsetp.ne.b32 p, %69, 0;\n"
    "wgmma.mma_async.sync.aligned.m64n128k16.f32.bf16.bf16 {%0, %1, %2, %3, %4, %5, %6, %7, %8, %9, %10, %11, %12, %13, %14, %15, %16, %17, %18, %19, %20, %21, %22, %23, %24, %25, %26, %27, %28, %29, %30, %31, %32, %33, %34, %35, %36, %37, %38, %39, %40, %41, %42, %43, %44, %45, %46, %47, %48, %49, %50, %51, %52, %53, %54, %55, %56, %57, %58, %59, %60, %61, %62, %63}, {%64, %65, %66, %67}, %68, p, 1, 1, 1;\n}\n"
    : "+f"(d[0]), "+f"(d[1]), "+f"(d[2]), "+f"(d[3]), "+f"(d[4]), "+f"(d[5]), "+f"(d[6]), "+f"(d[7]), "+f"(d[8]), "+f"(d[9]), "+f"(d[10]), "+f"(d[11]), "+f"(d[12]), "+f"(d[13]), "+f"(d[14]), "+f"(d[15]), "+f"(d[16]), "+f"(d[17]), "+f"(d[18]), "+f"(d[19]), "+f"(d[20]), "+f"(d[21]), "+f"(d[22]), "+f"(d[23]), "+f"(d[24]), "+f"(d[25]), "+f"(d[26]), "+f"(d[27]), "+f"(d[28]), "+f"(d[29]), "+f"(d[30]), "+f"(d[31]), "+f"(d[32]), "+f"(d[33]), "+f"(d[34]), "+f"(d[35]), "+f"(d[36]), "+f"(d[37]), "+f"(d[38]), "+f"(d[39]), "+f"(d[40]), "+f"(d[41]), "+f"(d[42]), "+f"(d[43]), "+f"(d[44]), "+f"(d[45]), "+f"(d[46]), "+f"(d[47]), "+f"(d[48]), "+f"(d[49]), "+f"(d[50]), "+f"(d[51]), "+f"(d[52]), "+f"(d[53]), "+f"(d[54]), "+f"(d[55]), "+f"(d[56]), "+f"(d[57]), "+f"(d[58]), "+f"(d[59]), "+f"(d[60]), "+f"(d[61]), "+f"(d[62]), "+f"(d[63])
    : "r"(a0), "r"(a1), "r"(a2), "r"(a3), "l"(db), "r"(scale_d));
}

__device__ __forceinline__ void wgmma_rs_n32_tb(float (&d)[16], uint32_t a0, uint32_t a1, uint32_t a2, uint32_t a3, uint64_t db, int scale_d) {
  asm volatile("{\n.reg .pred p;\nsetp.ne.b32 p, %21, 0;\n"
    "wgmma.mma_async.sync.aligned.m64n32k16.f32.bf16.bf16 {%0, %1, %2, %3, %4, %5, %6, %7, %8, %9, %10, %11, %12, %13, %14, %15}, {%16, %17, %18, %19}, %20, p, 1, 1, 1;\n}\n"
    : "+f"(d[0]), "+f"(d[1]), "+f"(d[2]), "+f"(d[3]), "+f"(d[4]), "+f"(d[5]), "+f"(d[6]), "+f"(d[7]), "+f"(d[8]), "+f"(d[9]), "+f"(d[10]), "+f"(d[11]), "+f"(d[12]), "+f"(d[13]), "+f"(d[14]), "+f"(d[15])
    : "r"(a0), "r"(a1), "r"(a2), "r"(a3), "l"(db), "r"(scale_d));
}

__device__ __forceinline__ void wgmma_rs_n64_tb(float (&d)[32], uint32_t a0, uint32_t a1, uint32_t a2, uint32_t a3, uint64_t db, int scale_d) {
  asm volatile("{\n.reg .pred p;\nsetp.ne.b32 p, %37, 0;\n"
    "wgmma.mma_async.sync.aligned.m64n64k16.f32.bf16.bf16 {%0, %1, %2, %3, %4, %5, %6, %7, %8, %9, %10, %11, %12, %13, %14, %15, %16, %17, %18, %19, %20, %21, %22, %23, %24, %25, %26, %27, %28, %29, %30, %31}, {%32, %33, %34, %35}, %36, p, 1, 1, 1;\n}\n"
    : "+f"(d[0]), "+f"(d[1]), "+f"(d[2]), "+f"(d[3]), "+f"(d[4]), "+f"(d[5]), "+f"(d[6]), "+f"(d[7]), "+f"(d[8]), "+f"(d[9]), "+f"(d[10]), "+f"(d[11]), "+f"(d[12]), "+f"(d[13]), "+f"(d[14]), "+f"(d[15]), "+f"(d[16]), "+f"(d[17]), "+f"(d[18]), "+f"(d[19]), "+f"(d[20]), "+f"(d[21]), "+f"(d[22]), "+f"(d[23]), "+f"(d[24]), "+f"(d[25]), "+f"(d[26]), "+f"(d[27]), "+f"(d[28]), "+f"(d[29]), "+f"(d[30]), "+f"(d[31])
    : "r"(a0), "r"(a1), "r"(a2), "r"(a3), "l"(db), "r"(scale_d));
}

__device__ __forceinline__ void wgmma_rs_n256_tb(float (&d)[64], float (&e)[64], uint32_t a0, uint32_t a1, uint32_t a2, uint32_t a3, uint64_t db, int scale_d) {
  asm volatile("{\n.reg .pred p;\nsetp.ne.b32 p, %133, 0;\n"
    "wgmma.mma_async.sync.aligned.m64n256k16.f32.bf16.bf16 {%0, %1, %2, %3, %4, %5, %6, %7, %8, %9, %10, %11, %12, %13, %14, %15, %16, %17, %18, %19, %20, %21, %22, %23, %24, %25, %26, %27, %28, %29, %30, %31, %32, %33, %34, %35, %36, %37, %38, %39, %40, %41, %42, %43, %44, %45, %46, %47, %48, %49, %50, %51, %52, %53, %54, %55, %56, %57, %58, %59, %60, %61, %62, %63, %64, %65, %66, %67, %68, %69, %70, %71, %72, %73, %74, %75, %76, %77, %78, %79, %80, %81, %82, %83, %84, %85, %86, %87, %88, %89, %90, %91, %92, %93, %94, %95, %96, %97, %98, %99, %100, %101, %102, %103, %104, %105, %106, %107, %108, %109, %110, %111, %112, %113, %114, %115, %116, %117, %118, %119, %120, %121, %122, %123, %124, %125, %126, %127}, {%128, %129, %130, %131}, %132, p, 1, 1, 1;\n}\n"
    : "+f"(d[0]), "+f"(d[1]), "+f"(d[2]), "+f"(d[3]), "+f"(d[4]), "+f"(d[5]), "+f"(d[6]), "+f"(d[7]), "+f"(d[8]), "+f"(d[9]), "+f"(d[10]), "+f"(d[11]), "+f"(d[12]), "+f"(d[13]), "+f"(d[14]), "+f"(d[15]), "+f"(d[16]), "+f"(d[17]), "+f"(d[18]), "+f"(d[19]), "+f"(d[20]), "+f"(d[21]), "+f"(d[22]), "+f"(d[23]), "+f"(d[24]), "+f"(d[25]), "+f"(d[26]), "+f"(d[27]), "+f"(d[28]), "+f"(d[29]), "+f"(d[30]), "+f"(d[31]), "+f"(d[32]), "+f"(d[33]), "+f"(d[34]), "+f"(d[35]), "+f"(d[36]), "+f"(d[37]), "+f"(d[38]), "+f"(d[39]), "+f"(d[40]), "+f"(d[41]), "+f"(d[42]), "+f"(d[43]), "+f"(d[44]), "+f"(d[45]), "+f"(d[46]), "+f"(d[47]), "+f"(d[48]), "+f"(d[49]), "+f"(d[50]), "+f"(d[51]), "+f"(d[52]), "+f"(d[53]), "+f"(d[54]), "+f"(d[55]), "+f"(d[56]), "+f"(d[57]), "+f"(d[58]), "+f"(d[59]), "+f"(d[60]), "+f"(d[61]), "+f"(d[62]), "+f"(d[63]), "+f"(e[0]), "+f"(e[1]), "+f"(e[2]), "+f"(e[3]), "+f"(e[4]), "+f"(e[5]), "+f"(e[6]), "+f"(e[7]), "+f"(e[8]), "+f"(e[9]), "+f"(e[10]), "+f"(e[11]), "+f"(e[12]), "+f"(e[13]), "+f"(e[14]), "+f"(e[15]), "+f"(e[16]), "+f"(e[17]), "+f"(e[18]), "+f"(e[19]), "+f"(e[20]), "+f"(e[21]), "+f"(e[22]), "+f"(e[23]), "+f"(e[24]), "+f"(e[25]), "+f"(e[26]), "+f"(e[27]), "+f"(e[28]), "+f"(e[29]), "+f"(e[30]), "+f"(e[31]), "+f"(e[32]), "+f"(e[33]), "+f"(e[34]), "+f"(e[35]), "+f"(e[36]), "+f"(e[37]), "+f"(e[38]), "+f"(e[39]), "+f"(e[40]), "+f"(e[41]), "+f"(e[42]), "+f"(e[43]), "+f"(e[44]), "+f"(e[45]), "+f"(e[46]), "+f"(e[47]), "+f"(e[48]), "+f"(e[49]), "+f"(e[50]), "+f"(e[51]), "+f"(e[52]), "+f"(e[53]), "+f"(e[54]), "+f"(e[55]), "+f"(e[56]), "+f"(e[57]), "+f"(e[58]), "+f"(e[59]), "+f"(e[60]), "+f"(e[61]), "+f"(e[62]), "+f"(e[63])
    : "r"(a0), "r"(a1), "r"(a2), "r"(a3), "l"(db), "r"(scale_d));
}

__device__ __forceinline__ void wgmma_rs_n128_z(float (&d)[64], uint32_t a0, uint32_t a1, uint32_t a2, uint32_t a3, uint64_t db) {
  asm volatile("{\n.reg .pred p;\nsetp.ne.b32 p, 0, 0;\n"
    "wgmma.mma_async.sync.aligned.m64n128k16.f32.bf16.bf16 {%0, %1, %2, %3, %4, %5, %6, %7, %8, %9, %10, %11, %12, %13, %14, %15, %16, %17, %18, %19, %20, %21, %22, %23, %24, %25, %26, %27, %28, %29, %30, %31, %32, %33, %34, %35, %36, %37, %38, %39, %40, %41, %42, %43, %44, %45, %46, %47, %48, %49, %50, %51, %52, %53, %54, %55, %56, %57, %58, %59, %60, %61, %62, %63}, {%64, %65, %66, %67}, %68, p, 1, 1, 0;\n}\n"
    : "=f"(d[0]), "=f"(d[1]), "=f"(d[2]), "=f"(d[3]), "=f"(d[4]), "=f"(d[5]), "=f"(d[6]), "=f"(d[7]), "=f"(d[8]), "=f"(d[9]), "=f"(d[10]), "=f"(d[11]), "=f"(d[12]), "=f"(d[13]), "=f"(d[14]), "=f"(d[15]), "=f"(d[16]), "=f"(d[17]), "=f"(d[18]), "=f"(d[19]), "=f"(d[20]), "=f"(d[21]), "=f"(d[22]), "=f"(d[23]), "=f"(d[24]), "=f"(d[25]), "=f"(d[26]), "=f"(d[27]), "=f"(d[28]), "=f"(d[29]), "=f"(d[30]), "=f"(d[31]), "=f"(d[32]), "=f"(d[33]), "=f"(d[34]), "=f"(d[35]), "=f"(d[36]), "=f"(d[37]), "=f"(d[38]), "=f"(d[39]), "=f"(d[40]), "=f"(d[41]), "=f"(d[42]), "=f"(d[43]), "=f"(d[44]), "=f"(d[45]), "=f"(d[46]), "=f"(d[47]), "=f"(d[48]), "=f"(d[49]), "=f"(d[50]), "=f"(d[51]), "=f"(d[52]), "=f"(d[53]), "=f"(d[54]), "=f"(d[55]), "=f"(d[56]), "=f"(d[57]), "=f"(d[58]), "=f"(d[59]), "=f"(d[60]), "=f"(d[61]), "=f"(d[62]), "=f"(d[63])
    : "r"(a0), "r"(a1), "r"(a2), "r"(a3), "l"(db));
}

__device__ __forceinline__ void wgmma_rs_n64_tb_z(float (&d)[32], uint32_t a0, uint32_t a1, uint32_t a2, uint32_t a3, uint64_t db) {
  asm volatile("{\n.reg .pred p;\nsetp.ne.b32 p, 0, 0;\n"
    "wgmma.mma_async.sync.aligned.m64n64k16.f32.bf16.bf16 {%0, %1, %2, %3, %4, %5, %6, %7, %8, %9, %10, %11, %12, %13, %14, %15, %16, %17, %18, %19, %20, %21, %22, %23, %24, %25, %26, %27, %28, %29, %30, %31}, {%32, %33, %34, %35}, %36, p, 1, 1, 1;\n}\n"
    : "=f"(d[0]), "=f"(d[1]), "=f"(d[2]), "=f"(d[3]), "=f"(d[4]), "=f"(d[5]), "=f"(d[6]), "=f"(d[7]), "=f"(d[8]), "=f"(d[9]), "=f"(d[10]), "=f"(d[11]), "=f"(d[12]), "=f"(d[13]), "=f"(d[14]), "=f"(d[15]), "=f"(d[16]), "=f"(d[17]), "=f"(d[18]), "=f"(d[19]), "=f"(d[20]), "=f"(d[21]), "=f"(d[22]), "=f"(d[23]), "=f"(d[24]), "=f"(d[25]), "=f"(d[26]), "=f"(d[27]), "=f"(d[28]), "=f"(d[29]), "=f"(d[30]), "=f"(d[31])
    : "r"(a0), "r"(a1), "r"(a2), "r"(a3), "l"(db));
}

__device__ __forceinline__ void wgmma_rs_n256_tb_z(float (&d)[64], float (&e)[64], uint32_t a0, uint32_t a1, uint32_t a2, uint32_t a3, uint64_t db) {
  asm volatile("{\n.reg .pred p;\nsetp.ne.b32 p, 0, 0;\n"
    "wgmma.mma_async.sync.aligned.m64n256k16.f32.bf16.bf16 {%0, %1, %2, %3, %4, %5, %6, %7, %8, %9, %10, %11, %12, %13, %14, %15, %16, %17, %18, %19, %20, %21, %22, %23, %24, %25, %26, %27, %28, %29, %30, %31, %32, %33, %34, %35, %36, %37, %38, %39, %40, %41, %42, %43, %44, %45, %46, %47, %48, %49, %50, %51, %52, %53, %54, %55, %56, %57, %58, %59, %60, %61, %62, %63, %64, %65, %66, %67, %68, %69, %70, %71, %72, %73, %74, %75, %76, %77, %78, %79, %80, %81, %82, %83, %84, %85, %86, %87, %88, %89, %90, %91, %92, %93, %94, %95, %96, %97, %98, %99, %100, %101, %102, %103, %104, %105, %106, %107, %108, %109, %110, %111, %112, %113, %114, %115, %116, %117, %118, %119, %120, %121, %122, %123, %124, %125, %126, %127}, {%128, %129, %130, %131}, %132, p, 1, 1, 1;\n}\n"
    : "=f"(d[0]), "=f"(d[1]), "=f"(d[2]), "=f"(d[3]), "=f"(d[4]), "=f"(d[5]), "=f"(d[6]), "=f"(d[7]), "=f"(d[8]), "=f"(d[9]), "=f"(d[10]), "=f"(d[11]), "=f"(d[12]), "=f"(d[13]), "=f"(d[14]), "=f"(d[15]), "=f"(d[16]), "=f"(d[17]), "=f"(d[18]), "=f"(d[19]), "=f"(d[20]), "=f"(d[21]), "=f"(d[22]), "=f"(d[23]), "=f"(d[24]), "=f"(d[25]), "=f"(d[26]), "=f"(d[27]), "=f"(d[28]), "=f"(d[29]), "=f"(d[30]), "=f"(d[31]), "=f"(d[32]), "=f"(d[33]), "=f"(d[34]), "=f"(d[35]), "=f"(d[36]), "=f"(d[37]), "=f"(d[38]), "=f"(d[39]), "=f"(d[40]), "=f"(d[41]), "=f"(d[42]), "=f"(d[43]), "=f"(d[44]), "=f"(d[45]), "=f"(d[46]), "=f"(d[47]), "=f"(d[48]), "=f"(d[49]), "=f"(d[50]), "=f"(d[51]), "=f"(d[52]), "=f"(d[53]), "=f"(d[54]), "=f"(d[55]), "=f"(d[56]), "=f"(d[57]), "=f"(d[58]), "=f"(d[59]), "=f"(d[60]), "=f"(d[61]), "=f"(d[62]), "=f"(d[63]), "=f"(e[0]), "=f"(e[1]), "=f"(e[2]), "=f"(e[3]), "=f"(e[4]), "=f"(e[5]), "=f"(e[6]), "=f"(e[7]), "=f"(e[8]), "=f"(e[9]), "=f"(e[10]), "=f"(e[11]), "=f"(e[12]), "=f"(e[13]), "=f"(e[14]), "=f"(e[15]), "=f"(e[16]), "=f"(e[17]), "=f"(e[18]), "=f"(e[19]), "=f"(e[20]), "=f"(e[21]), "=f"(e[22]), "=f"(e[23]), "=f"(e[24]), "=f"(e[25]), "=f"(e[26]), "=f"(e[27]), "=f"(e[28]), "=f"(e[29]), "=f"(e[30]), "=f"(e[31]), "=f"(e[32]), "=f"(e[33]), "=f"(e[34]), "=f"(e[35]), "=f"(e[36]), "=f"(e[37]), "=f"(e[38]), "=f"(e[39]), "=f"(e[40]), "=f"(e[41]), "=f"(e[42]), "=f"(e[43]), "=f"(e[44]), "=f"(e[45]), "=f"(e[46]), "=f"(e[47]), "=f"(e[48]), "=f"(e[49]), "=f"(e[50]), "=f"(e[51]), "=f"(e[52]), "=f"(e[53]), "=f"(e[54]), "=f"(e[55]), "=f"(e[56]), "=f"(e[57]), "=f"(e[58]), "=f"(e[59]), "=f"(e[60]), "=f"(e[61]), "=f"(e[62]), "=f"(e[63])
    : "r"(a0), "r"(a1), "r"(a2), "r"(a3), "l"(db));
}

__device__ __forceinline__ void wgmma_rs_n192_tb(float (&d)[64], float (&e)[64], uint32_t a0, uint32_t a1, uint32_t a2, uint32_t a3, uint64_t db) {
  asm volatile("{\n.reg .pred p;\nsetp.eq.b32 p, 0, 0;\n"
    "wgmma.mma_async.sync.aligned.m64n192k16.f32.bf16.bf16 {%0, %1, %2, %3, %4, %5, %6, %7, %8, %9, %10, %11, %12, %13, %14, %15, %16, %17, %18, %19, %20, %21, %22, %23, %24, %25, %26, %27, %28, %29, %30, %31, %32, %33, %34, %35, %36, %37, %38, %39, %40, %41, %42, %43, %44, %45, %46, %47, %48, %49, %50, %51, %52, %53, %54, %55, %56, %57, %58, %59, %60, %61, %62, %63, %64, %65, %66, %67, %68, %69, %70, %71, %72, %73, %74, %75, %76, %77, %78, %79, %80, %81, %82, %83, %84, %85, %86, %87, %88, %89, %90, %91, %92, %93, %94, %95}, {%96, %97, %98, %99}, %100, p, 1, 1, 1;\n}\n"
    : "+f"(d[0]), "+f"(d[1]), "+f"(d[2]), "+f"(d[3]), "+f"(d[4]), "+f"(d[5]), "+f"(d[6]), "+f"(d[7]), "+f"(d[8]), "+f"(d[9]), "+f"(d[10]), "+f"(d[11]), "+f"(d[12]), "+f"(d[13]), "+f"(d[14]), "+f"(d[15]), "+f"(d[16]), "+f"(d[17]), "+f"(d[18]), "+f"(d[19]), "+f"(d[20]), "+f"(d[21]), "+f"(d[22]), "+f"(d[23]), "+f"(d[24]), "+f"(d[25]), "+f"(d[26]), "+f"(d[27]), "+f"(d[28]), "+f"(d[29]), "+f"(d[30]), "+f"(d[31]), "+f"(d[32]), "+f"(d[33]), "+f"(d[34]), "+f"(d[35]), "+f"(d[36]), "+f"(d[37]), "+f"(d[38]), "+f"(d[39]), "+f"(d[40]), "+f"(d[41]), "+f"(d[42]), "+f"(d[43]), "+f"(d[44]), "+f"(d[45]), "+f"(d[46]), "+f"(d[47]), "+f"(d[48]), "+f"(d[49]), "+f"(d[50]), "+f"(d[51]), "+f"(d[52]), "+f"(d[53]), "+f"(d[54]), "+f"(d[55]), "+f"(d[56]), "+f"(d[57]), "+f"(d[58]), "+f"(d[59]), "+f"(d[60]), "+f"(d[61]), "+f"(d[62]), "+f"(d[63]), "+f"(e[0]), "+f"(e[1]), "+f"(e[2]), "+f"(e[3]), "+f"(e[4]), "+f"(e[5]), "+f"(e[6]), "+f"(e[7]), "+f"(e[8]), "+f"(e[9]), "+f"(e[10]), "+f"(e[11]), "+f"(e[12]), "+f"(e[13]), "+f"(e[14]), "+f"(e[15]), "+f"(e[16]), "+f"(e[17]), "+f"(e[18]), "+f"(e[19]), "+f"(e[20]), "+f"(e[21]), "+f"(e[22]), "+f"(e[23]), "+f"(e[24]), "+f"(e[25]), "+f"(e[26]), "+f"(e[27]), "+f"(e[28]), "+f"(e[29]), "+f"(e[30]), "+f"(e[31])
    : "r"(a0), "r"(a1), "r"(a2), "r"(a3), "l"(db));
}

__device__ __forceinline__ void wgmma_rs_n192_tb_z(float (&d)[64], float (&e)[64], uint32_t a0, uint32_t a1, uint32_t a2, uint32_t a3, uint64_t db) {
  asm volatile("{\n.reg .pred p;\nsetp.ne.b32 p, 0, 0;\n"
    "wgmma.mma_async.sync.aligned.m64n192k16.f32.bf16.bf16 {%0, %1, %2, %3, %4, %5, %6, %7, %8, %9, %10, %11, %12, %13, %14, %15, %16, %17, %18, %19, %20, %21, %22, %23, %24, %25, %26, %27, %28, %29, %30, %31, %32, %33, %34, %35, %36, %37, %38, %39, %40, %41, %42, %43, %44, %45, %46, %47, %48, %49, %50, %51, %52, %53, %54, %55, %56, %57, %58, %59, %60, %61, %62, %63, %64, %65, %66, %67, %68, %69, %70, %71, %72, %73, %74, %75, %76, %77, %78, %79, %80, %81, %82, %83, %84, %85, %86, %87, %88, %89, %90, %91, %92, %93, %94, %95}, {%96, %97, %98, %99}, %100, p, 1, 1, 1;\n}\n"
    : "=f"(d[0]), "=f"(d[1]), "=f"(d[2]), "=f"(d[3]), "=f"(d[4]), "=f"(d[5]), "=f"(d[6]), "=f"(d[7]), "=f"(d[8]), "=f"(d[9]), "=f"(d[10]), "=f"(d[11]), "=f"(d[12]), "=f"(d[13]), "=f"(d[14]), "=f"(d[15]), "=f"(d[16]), "=f"(d[17]), "=f"(d[18]), "=f"(d[19]), "=f"(d[20]), "=f"(d[21]), "=f"(d[22]), "=f"(d[23]), "=f"(d[24]), "=f"(d[25]), "=f"(d[26]), "=f"(d[27]), "=f"(d[28]), "=f"(d[29]), "=f"(d[30]), "=f"(d[31]), "=f"(d[32]), "=f"(d[33]), "=f"(d[34]), "=f"(d[35]), "=f"(d[36]), "=f"(d[37]), "=f"(d[38]), "=f"(d[39]), "=f"(d[40]), "=f"(d[41]), "=f"(d[42]), "=f"(d[43]), "=f"(d[44]), "=f"(d[45]), "=f"(d[46]), "=f"(d[47]), "=f"(d[48]), "=f"(d[49]), "=f"(d[50]), "=f"(d[51]), "=f"(d[52]), "=f"(d[53]), "=f"(d[54]), "=f"(d[55]), "=f"(d[56]), "=f"(d[57]), "=f"(d[58]), "=f"(d[59]), "=f"(d[60]), "=f"(d[61]), "=f"(d[62]), "=f"(d[63]), "=f"(e[0]), "=f"(e[1]), "=f"(e[2]), "=f"(e[3]), "=f"(e[4]), "=f"(e[5]), "=f"(e[6]), "=f"(e[7]), "=f"(e[8]), "=f"(e[9]), "=f"(e[10]), "=f"(e[11]), "=f"(e[12]), "=f"(e[13]), "=f"(e[14]), "=f"(e[15]), "=f"(e[16]), "=f"(e[17]), "=f"(e[18]), "=f"(e[19]), "=f"(e[20]), "=f"(e[21]), "=f"(e[22]), "=f"(e[23]), "=f"(e[24]), "=f"(e[25]), "=f"(e[26]), "=f"(e[27]), "=f"(e[28]), "=f"(e[29]), "=f"(e[30]), "=f"(e[31])
    : "r"(a0), "r"(a1), "r"(a2), "r"(a3), "l"(db));
}

struct Maps {
  CUtensorMap x[2], k[2], v[2], wq[2], wo[2];
  const char* px[2];
};

__device__ __forceinline__ void poll_tiles(int tile, const unsigned (&target)[3], uint32_t ready) {
#pragma unroll
  for (int pn = 0; pn < 3; pn++) {
    const unsigned* c = &g_cnt[(tile * 4 + pn) * 32];
    for (uint32_t it = 0; it < WAIT_LIMIT; ++it) {
      unsigned v;
      asm volatile("ld.acquire.gpu.global.u32 %0, [%1];" : "=r"(v) : "l"(c) : "memory");
      if ((int)(v - target[pn]) >= 0) break;
    }
    mbar_arrive(ready + pn * 8);
  }
}
__device__ __forceinline__ void read_targets(int tile, unsigned (&target)[3]) {
#pragma unroll
  for (int pn = 0; pn < 3; pn++) {
    unsigned v;
    asm volatile("ld.relaxed.gpu.global.u32 %0, [%1];" : "=r"(v) : "l"(&g_cnt[(tile * 4 + pn) * 32]) : "memory");
    target[pn] = (v / 16u + 1u) * 16u;
  }
}

__global__ void __cluster_dims__(2, 1, 1) __launch_bounds__(384, 1)
fused_gqa_kernel(const __grid_constant__ Maps maps, __nv_bfloat16* __restrict__ out) {
  extern __shared__ __align__(1024) unsigned char smem[];
  const uint32_t sbase = smem_u32(smem);
  const uint32_t full0 = sbase + BAR_OFF;
  const uint32_t empty0 = full0 + N_ITEMS * 8;
  const uint32_t ready0 = empty0 + N_ITEMS * 8;
  const uint32_t pub0 = ready0 + 6 * 8;

  const int tid = threadIdx.x;
  const int wg = tid >> 7;
  const int bid = blockIdx.x;
  const int bp = bid & 3;
  const int h = (bid >> 2) & 15;
  const int p = bid >> 6;

  if (tid == 0) {
#pragma unroll
    for (int i = 0; i < 6; i++) mbar_init(full0 + (WQ0 + i) * 8, 1);
#pragma unroll
    for (int i = 0; i < 2; i++) mbar_init(full0 + (X0 + i) * 8, 1);
    asm volatile("fence.mbarrier_init.release.cluster;" ::: "memory");
#pragma unroll
    for (int kc = 0; kc < 6; kc++) {
      if (kc < 2) {
        mbar_expect_tx(full0 + (X0 + kc) * 8, 16384);
        tma_load3(sbase + x_off(kc), &maps.x[p], 0, bp * 128, kc, full0 + (X0 + kc) * 8);
      }
      mbar_expect_tx(full0 + (WQ0 + kc) * 8, T32);
      tma_load3(sbase + wq_off(kc), &maps.wq[p], 0, kc * 64, h * 4, full0 + (WQ0 + kc) * 8);
    }
    TR(0, 56);
  } else if (tid >= 64 && tid < 96) {
    const char* base = maps.px[p] + (size_t)(bp * 128 + h * 8) * 1152;
#pragma unroll
    for (int i = 0; i < 3; i++)
      if ((tid & 31) + i * 32 < 72) l2_prefetch(base + ((tid & 31) + i * 32) * 128);
  } else if (tid == 32) {
    prefetch_tmap(&maps.k[p]);
    prefetch_tmap(&maps.v[p]);
    prefetch_tmap(&maps.wo[p]);
  } else if (tid >= 128) {
    const int i = tid - 128;
    if (i < N_ITEMS) {
      if (!(i < 6 || i == X0 || i == X0 + 1)) mbar_init(full0 + i * 8, 1);
    } else if (i >= 64 && i < 64 + N_ITEMS) {
      mbar_init(empty0 + (i - 64) * 8, 8);
    } else if (i >= 128 && i < 128 + 6) {
      mbar_init(ready0 + (i - 128) * 8, 1);
    } else if (i >= 160 && i < 160 + 6) {
      mbar_init(pub0 + (i - 160) * 8, 4);
    }
    asm volatile("fence.mbarrier_init.release.cluster;" ::: "memory");
  }
  __syncthreads();
  if (tid == 0) TR(0, 57);

  if (wg == 0) {
    asm volatile("setmaxnreg.dec.sync.aligned.u32 24;");
    if (tid == 0) {
      unsigned target[3];
      read_targets(p * 8 + 2 * bp + 1, target);
#pragma unroll 1
      for (int kc = 2; kc < 9; kc++) {
        mbar_wait(empty0 + (X0 + kc - 2) * 8);
        mbar_expect_tx(full0 + (X0 + kc) * 8, 16384);
        tma_load3(sbase + x_off(kc), &maps.x[p], 0, bp * 128, kc, full0 + (X0 + kc) * 8);
        if (kc < 5) {
          TR(0, WQ0 + kc + 4);
          mbar_expect_tx(full0 + (WQ0 + kc + 4) * 8, T32);
          tma_load3(sbase + wq_off(kc + 4), &maps.wq[p], 0, (kc + 4) * 64, h * 4, full0 + (WQ0 + kc + 4) * 8);
        }
      }
#pragma unroll 1
      for (int m = 0; m < N_WO; m++) {
        const int dep = m >= 6 ? WO0 + m - 6 : (m < 4 ? X0 + (m == 0 ? 6 : (m == 1 ? 7 : 8)) : KV0 + 9 + m);
        mbar_wait(empty0 + dep * 8);
        const uint32_t fb = full0 + (WO0 + m) * 8;
        TR(0, WO0 + m);
        mbar_expect_tx(fb, WO_BYTES);
        tma_load3(sbase + wo_off(m), &maps.wo[p], 0, h * 256 + (m & 3) * 64, (m >> 2) * 3, fb);
      }
      poll_tiles(p * 8 + 2 * bp + 1, target, ready0 + 24);
    } else if (tid == 96) {
      unsigned target[3];
      read_targets(p * 8 + 2 * bp, target);
#pragma unroll 1
      for (int n = 0; n < N_KV; n++) {
        mbar_wait(empty0 + (n >= 3 ? KV0 + n - 3 : X0 + 3 + n) * 8);
        if (n >= KV_INFLIGHT) mbar_wait(full0 + (KV0 + n - KV_INFLIGHT) * 8);
        const uint32_t fb = full0 + (KV0 + n) * 8;
        const CUtensorMap* tm = (n & 1) ? &maps.v[p] : &maps.k[p];
        const int row = ((2 * bp + (n >> 3)) * 16 + h) * kSK + ((n & 7) >> 1) * 128;
        TR(0, KV0 + n);
        mbar_expect_tx(fb, T32);
        tma_load3(sbase + kv_off(n), tm, 0, row, 0, fb);
      }
      mbar_wait(pub0);
      poll_tiles(p * 8 + 2 * bp, target, ready0);
    } else if (tid == 32 || tid == 64) {
      const int w = (tid >> 5) - 1;
      const int tile = p * 8 + 2 * bp + w;
#pragma unroll 1
      for (int e = 0; e < 3; e++) {
        mbar_wait(pub0 + (w * 3 + e) * 8);
        __threadfence();
        asm volatile("red.relaxed.gpu.global.add.u32 [%0], 1;" ::"l"(&g_cnt[(tile * 4 + e) * 32]) : "memory");
      }
    }
  } else {
    asm volatile("setmaxnreg.inc.sync.aligned.u32 240;");
    const int w = wg - 1;
    const int t128 = tid & 127;
    const int lane = tid & 31;

    auto release = [&](int item) {
      __syncwarp();
      if (lane == 0) mbar_arrive(empty0 + item * 8);
    };

    TRC(0);
    const float cs = 0.08838834764831845f * 1.4426950408889634f;
    float s[64], o[64];
#pragma unroll
    for (int i = 0; i < 64; i++) s[i] = 0.f, o[i] = 0.f;
    uint32_t qf[32];
    uint4* park = reinterpret_cast<uint4*>(smem + PARK_OFF) + w * 1024 + t128;
    {
#pragma unroll 1
      for (int kc = 0; kc < 9; kc++) {
        mbar_wait(full0 + (X0 + kc) * 8);
        mbar_wait(full0 + (WQ0 + kc) * 8);
        if (kc == 0) TRC(1);
        const uint64_t da = make_desc(sbase + x_off(kc), 16, 1024);
        const uint64_t db = make_desc(sbase + wq_off(kc) + w * 16384, 8192, 1024);
        wg_fence();
#pragma unroll
        for (int ks = 0; ks < 4; ks++) {
          wgmma_ss_n128_tb(s, da + ks * 2, db + ks * 128, (kc | ks) != 0);
          wgmma_ss_n128_tb(o, da + 512 + ks * 2, db + ks * 128, (kc | ks) != 0);
        }
        wg_commit();
        wg_wait<0>();
        release(X0 + kc);
      }
      fence_regs(s);
      fence_regs(o);
#pragma unroll
      for (int i = 0; i < 32; i++) qf[i] = pack_bf16(s[2 * i], s[2 * i + 1]);
      named_bar(1, 256);
#pragma unroll
      for (int i = 0; i < 8; i++) park[i * 128] = pack8(o, i);
      TRC(2);
    }
#pragma unroll 1
    for (int bb = 0; bb < 2; bb++) {
#pragma unroll
      for (int i = 0; i < 64; i++) o[i] = 0.f;
      float m0 = -INFINITY, m1 = -INFINITY, l0 = 0.f, l1 = 0.f;
#pragma unroll 1
      for (int t = 0; t < 4; t++) {
        const int n = bb * 8 + t * 2;
        {
          const uint32_t base = sbase + kv_off(n);
          mbar_wait(full0 + (KV0 + n) * 8);
          if (n == 0 && w == 1) named_bar(4, 256);
          const uint64_t db = make_desc(base, 16, 1024);
          wg_fence();
          wgmma_rs_n128_z(s, qf[0], qf[1], qf[2], qf[3], db);
#pragma unroll
          for (int ks = 1; ks < 8; ks++)
            wgmma_rs_n128(s, qf[4 * ks], qf[4 * ks + 1], qf[4 * ks + 2], qf[4 * ks + 3], db + (ks >> 2) * 1024 + (ks & 3) * 2, 1);
          wg_commit();
          wg_wait<0>();
          fence_regs(s);
          if (n == 0 && w == 0) named_arrive(4, 256);
          release(KV0 + n);
        }
        float mx0 = s[0], mx1 = s[2];
#pragma unroll
        for (int g = 0; g < 16; g++) {
          mx0 = fmaxf(mx0, fmaxf(s[4 * g], s[4 * g + 1]));
          mx1 = fmaxf(mx1, fmaxf(s[4 * g + 2], s[4 * g + 3]));
        }
        mx0 = fmaxf(mx0, __shfl_xor_sync(0xffffffffu, mx0, 1));
        mx0 = fmaxf(mx0, __shfl_xor_sync(0xffffffffu, mx0, 2));
        mx1 = fmaxf(mx1, __shfl_xor_sync(0xffffffffu, mx1, 1));
        mx1 = fmaxf(mx1, __shfl_xor_sync(0xffffffffu, mx1, 2));
        const float mn0 = fmaxf(m0, mx0), mn1 = fmaxf(m1, mx1);
        const float a0 = ex2((m0 - mn0) * cs), a1 = ex2((m1 - mn1) * cs);
        m0 = mn0;
        m1 = mn1;
        const float ms0 = mn0 * cs, ms1 = mn1 * cs;
        float rs0 = 0.f, rs1 = 0.f;
        uint32_t pf[32];
#pragma unroll
        for (int g = 0; g < 16; g++) {
          const float p0 = ex2(fmaf(s[4 * g], cs, -ms0));
          const float p1 = ex2(fmaf(s[4 * g + 1], cs, -ms0));
          const float p2 = ex2(fmaf(s[4 * g + 2], cs, -ms1));
          const float p3 = ex2(fmaf(s[4 * g + 3], cs, -ms1));
          rs0 += p0 + p1;
          rs1 += p2 + p3;
          pf[2 * g] = pack_bf16(p0, p1);
          pf[2 * g + 1] = pack_bf16(p2, p3);
        }
        l0 = l0 * a0 + rs0;
        l1 = l1 * a1 + rs1;
#pragma unroll
        for (int g = 0; g < 16; g++) {
          o[4 * g] *= a0;
          o[4 * g + 1] *= a0;
          o[4 * g + 2] *= a1;
          o[4 * g + 3] *= a1;
        }
        {
          const uint32_t base = sbase + kv_off(n + 1);
          mbar_wait(full0 + (KV0 + n + 1) * 8);
          const uint64_t db = make_desc(base, 16384, 1024);
          wg_fence();
#pragma unroll
          for (int ks = 0; ks < 8; ks++)
            wgmma_rs_n128_tb(o, pf[4 * ks], pf[4 * ks + 1], pf[4 * ks + 2], pf[4 * ks + 3], db + ks * 128, 1);
          wg_commit();
          wg_wait<0>();
          fence_regs(o);
          release(KV0 + n + 1);
          TRC(3 + bb * 5 + t);
        }
      }
      l0 += __shfl_xor_sync(0xffffffffu, l0, 1);
      l0 += __shfl_xor_sync(0xffffffffu, l0, 2);
      l1 += __shfl_xor_sync(0xffffffffu, l1, 1);
      l1 += __shfl_xor_sync(0xffffffffu, l1, 2);
      const float i0 = 1.f / l0, i1 = 1.f / l1;
      uint4* dst = park;
      if (bb == 0) {
#pragma unroll
        for (int i = 0; i < 8; i++) {
          const uint4 v = park[i * 128];
          qf[4 * i] = v.x;
          qf[4 * i + 1] = v.y;
          qf[4 * i + 2] = v.z;
          qf[4 * i + 3] = v.w;
        }
      } else {
        named_bar(1, 256);
        dst = reinterpret_cast<uint4*>(smem + KV_OFF) + w * 1024 + t128;
      }
#pragma unroll
      for (int i = 0; i < 8; i++)
        dst[i * 128] = make_uint4(pack_bf16(o[8 * i] * i0, o[8 * i + 1] * i0), pack_bf16(o[8 * i + 2] * i1, o[8 * i + 3] * i1),
                                  pack_bf16(o[8 * i + 4] * i0, o[8 * i + 5] * i0), pack_bf16(o[8 * i + 6] * i1, o[8 * i + 7] * i1));
    }
    uint32_t af[64];
    {
      named_bar(1, 256);
      const uint4* src = reinterpret_cast<const uint4*>(smem + (w == 0 ? PARK_OFF : KV_OFF)) + t128;
#pragma unroll
      for (int i = 0; i < 16; i++) {
        const uint4 v = src[i * 128];
        af[4 * i] = v.x;
        af[4 * i + 1] = v.y;
        af[4 * i + 2] = v.z;
        af[4 * i + 3] = v.w;
      }
    }
    TRC(12);
    if (w == 1) named_bar(4, 256);
    const int tile = p * 8 + 2 * bp + w;
    uint4* part = g_part + (size_t)(tile * 16 + h) * 36 * 128 + t128;
#pragma unroll
    for (int pn = 0; pn < 3; pn++) {
#pragma unroll
      for (int kc = 0; kc < 4; kc++) {
        const int m = pn * 4 + kc;
        mbar_wait(full0 + (WO0 + m) * 8);
        const uint64_t db = make_desc(sbase + wo_off(m), 8192, 1024);
        wg_fence();
#pragma unroll
        for (int ks = 0; ks < 4; ks++) {
          const int a = (kc * 4 + ks) * 4;
          if ((kc | ks) == 0) wgmma_rs_n192_tb_z(s, o, af[a], af[a + 1], af[a + 2], af[a + 3], db);
          else wgmma_rs_n192_tb(s, o, af[a], af[a + 1], af[a + 2], af[a + 3], db + ks * 128);
        }
        wg_commit();
        if (m == 1 && w == 0) named_arrive(4, 256);
        if (kc > 0) {
          wg_wait<1>();
          if (m - 1 < 6) release(WO0 + m - 1);
        }
      }
      wg_wait<0>();
      fence_regs(s);
      fence_regs32(o);
      if (pn == 0) release(WO0 + 3);
      TRC(13 + pn * 2);
#pragma unroll
      for (int i = 0; i < 8; i++) __stcg(part + (pn * 12 + i) * 128, pack8(s, i));
#pragma unroll
      for (int i = 0; i < 4; i++) __stcg(part + (pn * 12 + 8 + i) * 128, pack8(o, i));
      __syncwarp();
      if (lane == 0) mbar_arrive(pub0 + (w * 3 + pn) * 8);
      TRC(14 + pn * 2);
    }
    if (t128 < 96) {
      const int u = h * 96 + t128;
      const int slot = u >> 7, thr = u & 127;
      const int row0 = (thr >> 5) * 16 + ((thr & 31) >> 2);
      __nv_bfloat16* orow = out + (size_t)((2 * bp + w) * 64 + row0) * 1152 + p * 576 + slot * 16 + (thr & 3) * 2;
      const uint4* pr = g_part + (size_t)(tile * 16) * 36 * 128 + slot * 128 + thr;
      uint4 v[3][16];
#pragma unroll
      for (int pn = 0; pn < 3; pn++) {
        mbar_wait(ready0 + (w * 3 + pn) * 8);
        TRC(19 + pn);
#pragma unroll
        for (int c = 0; c < 16; c++) v[pn][c] = __ldcg(pr + (size_t)(c * 36 + pn * 12) * 128);
      }
#pragma unroll
      for (int pn = 0; pn < 3; pn++) {
        float a[8];
#pragma unroll
        for (int e = 0; e < 8; e++) a[e] = 0.f;
#pragma unroll
        for (int c = 0; c < 16; c++) {
          a[0] += bf_lo(v[pn][c].x);
          a[1] += bf_hi(v[pn][c].x);
          a[2] += bf_lo(v[pn][c].y);
          a[3] += bf_hi(v[pn][c].y);
          a[4] += bf_lo(v[pn][c].z);
          a[5] += bf_hi(v[pn][c].z);
          a[6] += bf_lo(v[pn][c].w);
          a[7] += bf_hi(v[pn][c].w);
        }
        __nv_bfloat16* op = orow + pn * 192;
        *reinterpret_cast<uint32_t*>(op) = pack_bf16(a[0], a[1]);
        *reinterpret_cast<uint32_t*>(op + 8 * 1152) = pack_bf16(a[2], a[3]);
        *reinterpret_cast<uint32_t*>(op + 8) = pack_bf16(a[4], a[5]);
        *reinterpret_cast<uint32_t*>(op + 8 * 1152 + 8) = pack_bf16(a[6], a[7]);
      }
    }
    TRC(22);
  }
}

typedef CUresult (*EncodeFn)(CUtensorMap*, CUtensorMapDataType, cuuint32_t, void*, const cuuint64_t*, const cuuint64_t*,
                             const cuuint32_t*, const cuuint32_t*, CUtensorMapInterleave, CUtensorMapSwizzle,
                             CUtensorMapL2promotion, CUtensorMapFloatOOBfill);

void encode3d(EncodeFn fn, CUtensorMap* m, void* ptr, uint64_t cols, uint64_t rows, uint32_t box_rows, uint32_t box_chunks) {
  cuuint64_t dims[3] = {64, rows, cols / 64};
  cuuint64_t strides[2] = {cols * 2, 128};
  cuuint32_t box[3] = {64, box_rows, box_chunks};
  cuuint32_t es[3] = {1, 1, 1};
  fn(m, CU_TENSOR_MAP_DATA_TYPE_BFLOAT16, 3, ptr, dims, strides, box, es, CU_TENSOR_MAP_INTERLEAVE_NONE,
     CU_TENSOR_MAP_SWIZZLE_128B, CU_TENSOR_MAP_L2_PROMOTION_L2_256B, CU_TENSOR_MAP_FLOAT_OOB_FILL_NONE);
}

}

extern "C" void kernel_launch(void* const* d_in, const int* in_sizes, int n_in, void* d_out, int out_size) {
  static EncodeFn fn = nullptr;
  if (!fn) {
    void* f = nullptr;
    cudaDriverEntryPointQueryResult st;
    cudaGetDriverEntryPoint("cuTensorMapEncodeTiled", &f, cudaEnableDefault, &st);
    fn = (EncodeFn)f;
    cudaFuncSetAttribute(fused_gqa_kernel, cudaFuncAttributeMaxDynamicSharedMemorySize, SMEM_BYTES);
  }
  Maps maps;
  for (int p = 0; p < 2; p++) {
    encode3d(fn, &maps.x[p], d_in[p * 5 + 0], kD, 512, 128, 1);
    encode3d(fn, &maps.k[p], d_in[p * 5 + 1], kDH, 8 * 16 * kSK, 128, 2);
    encode3d(fn, &maps.v[p], d_in[p * 5 + 2], kDH, 8 * 16 * kSK, 128, 2);
    encode3d(fn, &maps.wq[p], d_in[p * 5 + 3], kHQD, kD, 64, 4);
    encode3d(fn, &maps.wo[p], d_in[p * 5 + 4], kD, kHQD, 64, 3);
    maps.px[p] = (const char*)d_in[p * 5 + 0];
  }
  fused_gqa_kernel<<<128, 384, SMEM_BYTES>>>(maps, (__nv_bfloat16*)d_out);
}
```

```cpp
#include <cuda_runtime.h>
#include <cuda_bf16.h>
#include <cuda.h>
#include <stdint.h>

namespace {

constexpr int kD = 576, kHQD = 4096, kSK = 512, kDH = 128;

constexpr int N_WQ = 9, N_X = 9, N_KV = 16, N_WO = 12;
constexpr int N_ITEMS = N_WQ + N_X + N_KV + N_WO;
constexpr int T32 = 32 * 1024;
constexpr int WO_BYTES = 24 * 1024;
constexpr int KV_OFF = 96 * 1024;
constexpr int PARK_OFF = 192 * 1024;
constexpr int BAR_OFF = 224 * 1024;
constexpr int SMEM_BYTES = BAR_OFF + 2 * N_ITEMS * 8 + 256;
constexpr int WQ0 = 0, X0 = N_WQ, KV0 = X0 + N_X, WO0 = KV0 + N_KV;
#define WO_PF_AT 14
#define KV_INFLIGHT 2

__device__ __forceinline__ int wq_off(int kc) { return (kc < 5 ? kc : (kc < 8 ? kc - 5 : 0)) * T32; }
__device__ __forceinline__ int x_off(int kc) { return ((kc & 2) ? KV_OFF + 2 * T32 : PARK_OFF) + (kc & 1) * 16384; }
__device__ __forceinline__ int kv_off(int n) { return KV_OFF + (n % 3) * T32; }
__device__ __forceinline__ int wo_off(int m) {
  const int s = m % 6;
  return s < 4 ? s * WO_BYTES : KV_OFF + (s - 3) * T32;
}

__device__ uint4 g_part[16 * 16 * 36 * 128];
__device__ unsigned int g_cnt[16 * 4 * 32];

#define TR(role, ev)
#define TRC(ev)
constexpr uint32_t WAIT_CYCLES = 1u << 20;
constexpr uint32_t WAIT_LIMIT = 1u << 12;
__device__ __forceinline__ uint32_t smem_u32(const void* p) { return (uint32_t)__cvta_generic_to_shared(p); }
__device__ __forceinline__ void mbar_init(uint32_t bar, uint32_t cnt) {
  asm volatile("mbarrier.init.shared::cta.b64 [%0], %1;" ::"r"(bar), "r"(cnt) : "memory");
}
__device__ __forceinline__ void mbar_expect_tx(uint32_t bar, uint32_t bytes) {
  asm volatile("mbarrier.arrive.expect_tx.shared::cta.b64 _, [%0], %1;" ::"r"(bar), "r"(bytes) : "memory");
}
__device__ __forceinline__ void mbar_arrive(uint32_t bar) {
  asm volatile("mbarrier.arrive.shared::cta.b64 _, [%0];" ::"r"(bar) : "memory");
}
__device__ __forceinline__ bool mbar_try(uint32_t bar, uint32_t parity) {
  uint32_t ok;
  asm volatile(
      "{\n.reg .pred p;\nmbarrier.try_wait.parity.shared::cta.b64 p, [%1], %2;\nselp.u32 %0, 1, 0, p;\n}\n"
      : "=r"(ok)
      : "r"(bar), "r"(parity)
      : "memory");
  return ok != 0;
}
__device__ __forceinline__ void mbar_wait(uint32_t bar) {
  if (mbar_try(bar, 0)) return;
  const uint32_t t0 = (uint32_t)clock();
  while (!mbar_try(bar, 0))
    if ((uint32_t)clock() - t0 > WAIT_CYCLES) break;
}
__device__ __forceinline__ void tma_load3(uint32_t dst, const CUtensorMap* tm, int c0, int c1, int c2, uint32_t bar) {
  asm volatile(
      "cp.async.bulk.tensor.3d.shared::cluster.global.mbarrier::complete_tx::bytes [%0], [%1, {%3, %4, %5}], [%2];" ::"r"(dst),
      "l"(tm), "r"(bar), "r"(c0), "r"(c1), "r"(c2)
      : "memory");
}
__device__ __forceinline__ void l2_prefetch(const void* p) { asm volatile("prefetch.global.L2 [%0];" ::"l"(p) : "memory"); }
__device__ __forceinline__ void prefetch_tmap(const CUtensorMap* tm) {
  asm volatile("prefetch.tensormap [%0];" ::"l"(tm) : "memory");
}
__device__ __forceinline__ void named_bar(int id, int n) { asm volatile("bar.sync %0, %1;" ::"r"(id), "r"(n) : "memory"); }
__device__ __forceinline__ void named_arrive(int id, int n) { asm volatile("bar.arrive %0, %1;" ::"r"(id), "r"(n) : "memory"); }
__device__ __forceinline__ void wg_fence() { asm volatile("wgmma.fence.sync.aligned;" ::: "memory"); }
__device__ __forceinline__ void wg_commit() { asm volatile("wgmma.commit_group.sync.aligned;" ::: "memory"); }
template <int N>
__device__ __forceinline__ void wg_wait() { asm volatile("wgmma.wait_group.sync.aligned %0;" ::"n"(N) : "memory"); }
template <int N>
__device__ __forceinline__ void fence_regs(float (&d)[N]) {
#pragma unroll
  for (int i = 0; i < N; i++) asm volatile("" : "+f"(d[i])::"memory");
}
__device__ __forceinline__ void fence_regs32(float (&d)[64]) {
#pragma unroll
  for (int i = 0; i < 32; i++) asm volatile("" : "+f"(d[i])::"memory");
}
__device__ __forceinline__ uint64_t make_desc(uint32_t addr, uint32_t lbo, uint32_t sbo) {
  return (uint64_t)((addr & 0x3FFFF) >> 4) | ((uint64_t)(lbo >> 4) << 16) | ((uint64_t)(sbo >> 4) << 32) | (1ull << 62);
}
__device__ __forceinline__ uint32_t pack_bf16(float lo, float hi) {
  uint32_t r;
  asm("cvt.rn.bf16x2.f32 %0, %1, %2;" : "=r"(r) : "f"(hi), "f"(lo));
  return r;
}
__device__ __forceinline__ float ex2(float x) {
  float y;
  asm("ex2.approx.ftz.f32 %0, %1;" : "=f"(y) : "f"(x));
  return y;
}
__device__ __forceinline__ float bf_lo(uint32_t v) { return __uint_as_float(v << 16); }
__device__ __forceinline__ float bf_hi(uint32_t v) { return __uint_as_float(v & 0xffff0000u); }
template <int N>
__device__ __forceinline__ uint4 pack8(const float (&a)[N], int i) {
  return make_uint4(pack_bf16(a[8 * i], a[8 * i + 1]), pack_bf16(a[8 * i + 2], a[8 * i + 3]), pack_bf16(a[8 * i + 4], a[8 * i + 5]),
                    pack_bf16(a[8 * i + 6], a[8 * i + 7]));
}

__device__ __forceinline__ void wgmma_ss_n128_tb(float (&d)[64], uint64_t da, uint64_t db, int scale_d) {
  asm volatile("{\n.reg .pred p;\nsetp.ne.b32 p, %66, 0;\n"
    "wgmma.mma_async.sync.aligned.m64n128k16.f32.bf16.bf16 {%0, %1, %2, %3, %4, %5, %6, %7, %8, %9, %10, %11, %12, %13, %14, %15, %16, %17, %18, %19, %20, %21, %22, %23, %24, %25, %26, %27, %28, %29, %30, %31, %32, %33, %34, %35, %36, %37, %38, %39, %40, %41, %42, %43, %44, %45, %46, %47, %48, %49, %50, %51, %52, %53, %54, %55, %56, %57, %58, %59, %60, %61, %62, %63}, %64, %65, p, 1, 1, 0, 1;\n}\n"
    : "+f"(d[0]), "+f"(d[1]), "+f"(d[2]), "+f"(d[3]), "+f"(d[4]), "+f"(d[5]), "+f"(d[6]), "+f"(d[7]), "+f"(d[8]), "+f"(d[9]), "+f"(d[10]), "+f"(d[11]), "+f"(d[12]), "+f"(d[13]), "+f"(d[14]), "+f"(d[15]), "+f"(d[16]), "+f"(d[17]), "+f"(d[18]), "+f"(d[19]), "+f"(d[20]), "+f"(d[21]), "+f"(d[22]), "+f"(d[23]), "+f"(d[24]), "+f"(d[25]), "+f"(d[26]), "+f"(d[27]), "+f"(d[28]), "+f"(d[29]), "+f"(d[30]), "+f"(d[31]), "+f"(d[32]), "+f"(d[33]), "+f"(d[34]), "+f"(d[35]), "+f"(d[36]), "+f"(d[37]), "+f"(d[38]), "+f"(d[39]), "+f"(d[40]), "+f"(d[41]), "+f"(d[42]), "+f"(d[43]), "+f"(d[44]), "+f"(d[45]), "+f"(d[46]), "+f"(d[47]), "+f"(d[48]), "+f"(d[49]), "+f"(d[50]), "+f"(d[51]), "+f"(d[52]), "+f"(d[53]), "+f"(d[54]), "+f"(d[55]), "+f"(d[56]), "+f"(d[57]), "+f"(d[58]), "+f"(d[59]), "+f"(d[60]), "+f"(d[61]), "+f"(d[62]), "+f"(d[63])
    : "l"(da), "l"(db), "r"(scale_d));
}

__device__ __forceinline__ void wgmma_rs_n128(float (&d)[64], uint32_t a0, uint32_t a1, uint32_t a2, uint32_t a3, uint64_t db, int scale_d) {
  asm volatile("{\n.reg .pred p;\nsetp.ne.b32 p, %69, 0;\n"
    "wgmma.mma_async.sync.aligned.m64n128k16.f32.bf16.bf16 {%0, %1, %2, %3, %4, %5, %6, %7, %8, %9, %10, %11, %12, %13, %14, %15, %16, %17, %18, %19, %20, %21, %22, %23, %24, %25, %26, %27, %28, %29, %30, %31, %32, %33, %34, %35, %36, %37, %38, %39, %40, %41, %42, %43, %44, %45, %46, %47, %48, %49, %50, %51, %52, %53, %54, %55, %56, %57, %58, %59, %60, %61, %62, %63}, {%64, %65, %66, %67}, %68, p, 1, 1, 0;\n}\n"
    : "+f"(d[0]), "+f"(d[1]), "+f"(d[2]), "+f"(d[3]), "+f"(d[4]), "+f"(d[5]), "+f"(d[6]), "+f"(d[7]), "+f"(d[8]), "+f"(d[9]), "+f"(d[10]), "+f"(d[11]), "+f"(d[12]), "+f"(d[13]), "+f"(d[14]), "+f"(d[15]), "+f"(d[16]), "+f"(d[17]), "+f"(d[18]), "+f"(d[19]), "+f"(d[20]), "+f"(d[21]), "+f"(d[22]), "+f"(d[23]), "+f"(d[24]), "+f"(d[25]), "+f"(d[26]), "+f"(d[27]), "+f"(d[28]), "+f"(d[29]), "+f"(d[30]), "+f"(d[31]), "+f"(d[32]), "+f"(d[33]), "+f"(d[34]), "+f"(d[35]), "+f"(d[36]), "+f"(d[37]), "+f"(d[38]), "+f"(d[39]), "+f"(d[40]), "+f"(d[41]), "+f"(d[42]), "+f"(d[43]), "+f"(d[44]), "+f"(d[45]), "+f"(d[46]), "+f"(d[47]), "+f"(d[48]), "+f"(d[49]), "+f"(d[50]), "+f"(d[51]), "+f"(d[52]), "+f"(d[53]), "+f"(d[54]), "+f"(d[55]), "+f"(d[56]), "+f"(d[57]), "+f"(d[58]), "+f"(d[59]), "+f"(d[60]), "+f"(d[61]), "+f"(d[62]), "+f"(d[63])
    : "r"(a0), "r"(a1), "r"(a2), "r"(a3), "l"(db), "r"(scale_d));
}

__device__ __forceinline__ void wgmma_rs_n128_tb(float (&d)[64], uint32_t a0, uint32_t a1, uint32_t a2, uint32_t a3, uint64_t db, int scale_d) {
  asm volatile("{\n.reg .pred p;\nsetp.ne.b32 p, %69, 0;\n"
    "wgmma.mma_async.sync.aligned.m64n128k16.f32.bf16.bf16 {%0, %1, %2, %3, %4, %5, %6, %7, %8, %9, %10, %11, %12, %13, %14, %15, %16, %17, %18, %19, %20, %21, %22, %23, %24, %25, %26, %27, %28, %29, %30, %31, %32, %33, %34, %35, %36, %37, %38, %39, %40, %41, %42, %43, %44, %45, %46, %47, %48, %49, %50, %51, %52, %53, %54, %55, %56, %57, %58, %59, %60, %61, %62, %63}, {%64, %65, %66, %67}, %68, p, 1, 1, 1;\n}\n"
    : "+f"(d[0]), "+f"(d[1]), "+f"(d[2]), "+f"(d[3]), "+f"(d[4]), "+f"(d[5]), "+f"(d[6]), "+f"(d[7]), "+f"(d[8]), "+f"(d[9]), "+f"(d[10]), "+f"(d[11]), "+f"(d[12]), "+f"(d[13]), "+f"(d[14]), "+f"(d[15]), "+f"(d[16]), "+f"(d[17]), "+f"(d[18]), "+f"(d[19]), "+f"(d[20]), "+f"(d[21]), "+f"(d[22]), "+f"(d[23]), "+f"(d[24]), "+f"(d[25]), "+f"(d[26]), "+f"(d[27]), "+f"(d[28]), "+f"(d[29]), "+f"(d[30]), "+f"(d[31]), "+f"(d[32]), "+f"(d[33]), "+f"(d[34]), "+f"(d[35]), "+f"(d[36]), "+f"(d[37]), "+f"(d[38]), "+f"(d[39]), "+f"(d[40]), "+f"(d[41]), "+f"(d[42]), "+f"(d[43]), "+f"(d[44]), "+f"(d[45]), "+f"(d[46]), "+f"(d[47]), "+f"(d[48]), "+f"(d[49]), "+f"(d[50]), "+f"(d[51]), "+f"(d[52]), "+f"(d[53]), "+f"(d[54]), "+f"(d[55]), "+f"(d[56]), "+f"(d[57]), "+f"(d[58]), "+f"(d[59]), "+f"(d[60]), "+f"(d[61]), "+f"(d[62]), "+f"(d[63])
    : "r"(a0), "r"(a1), "r"(a2), "r"(a3), "l"(db), "r"(scale_d));
}

__device__ __forceinline__ void wgmma_rs_n32_tb(float (&d)[16], uint32_t a0, uint32_t a1, uint32_t a2, uint32_t a3, uint64_t db, int scale_d) {
  asm volatile("{\n.reg .pred p;\nsetp.ne.b32 p, %21, 0;\n"
    "wgmma.mma_async.sync.aligned.m64n32k16.f32.bf16.bf16 {%0, %1, %2, %3, %4, %5, %6, %7, %8, %9, %10, %11, %12, %13, %14, %15}, {%16, %17, %18, %19}, %20, p, 1, 1, 1;\n}\n"
    : "+f"(d[0]), "+f"(d[1]), "+f"(d[2]), "+f"(d[3]), "+f"(d[4]), "+f"(d[5]), "+f"(d[6]), "+f"(d[7]), "+f"(d[8]), "+f"(d[9]), "+f"(d[10]), "+f"(d[11]), "+f"(d[12]), "+f"(d[13]), "+f"(d[14]), "+f"(d[15])
    : "r"(a0), "r"(a1), "r"(a2), "r"(a3), "l"(db), "r"(scale_d));
}

__device__ __forceinline__ void wgmma_rs_n64_tb(float (&d)[32], uint32_t a0, uint32_t a1, uint32_t a2, uint32_t a3, uint64_t db, int scale_d) {
  asm volatile("{\n.reg .pred p;\nsetp.ne.b32 p, %37, 0;\n"
    "wgmma.mma_async.sync.aligned.m64n64k16.f32.bf16.bf16 {%0, %1, %2, %3, %4, %5, %6, %7, %8, %9, %10, %11, %12, %13, %14, %15, %16, %17, %18, %19, %20, %21, %22, %23, %24, %25, %26, %27, %28, %29, %30, %31}, {%32, %33, %34, %35}, %36, p, 1, 1, 1;\n}\n"
    : "+f"(d[0]), "+f"(d[1]), "+f"(d[2]), "+f"(d[3]), "+f"(d[4]), "+f"(d[5]), "+f"(d[6]), "+f"(d[7]), "+f"(d[8]), "+f"(d[9]), "+f"(d[10]), "+f"(d[11]), "+f"(d[12]), "+f"(d[13]), "+f"(d[14]), "+f"(d[15]), "+f"(d[16]), "+f"(d[17]), "+f"(d[18]), "+f"(d[19]), "+f"(d[20]), "+f"(d[21]), "+f"(d[22]), "+f"(d[23]), "+f"(d[24]), "+f"(d[25]), "+f"(d[26]), "+f"(d[27]), "+f"(d[28]), "+f"(d[29]), "+f"(d[30]), "+f"(d[31])
    : "r"(a0), "r"(a1), "r"(a2), "r"(a3), "l"(db), "r"(scale_d));
}

__device__ __forceinline__ void wgmma_rs_n256_tb(float (&d)[64], float (&e)[64], uint32_t a0, uint32_t a1, uint32_t a2, uint32_t a3, uint64_t db, int scale_d) {
  asm volatile("{\n.reg .pred p;\nsetp.ne.b32 p, %133, 0;\n"
    "wgmma.mma_async.sync.aligned.m64n256k16.f32.bf16.bf16 {%0, %1, %2, %3, %4, %5, %6, %7, %8, %9, %10, %11, %12, %13, %14, %15, %16, %17, %18, %19, %20, %21, %22, %23, %24, %25, %26, %27, %28, %29, %30, %31, %32, %33, %34, %35, %36, %37, %38, %39, %40, %41, %42, %43, %44, %45, %46, %47, %48, %49, %50, %51, %52, %53, %54, %55, %56, %57, %58, %59, %60, %61, %62, %63, %64, %65, %66, %67, %68, %69, %70, %71, %72, %73, %74, %75, %76, %77, %78, %79, %80, %81, %82, %83, %84, %85, %86, %87, %88, %89, %90, %91, %92, %93, %94, %95, %96, %97, %98, %99, %100, %101, %102, %103, %104, %105, %106, %107, %108, %109, %110, %111, %112, %113, %114, %115, %116, %117, %118, %119, %120, %121, %122, %123, %124, %125, %126, %127}, {%128, %129, %130, %131}, %132, p, 1, 1, 1;\n}\n"
    : "+f"(d[0]), "+f"(d[1]), "+f"(d[2]), "+f"(d[3]), "+f"(d[4]), "+f"(d[5]), "+f"(d[6]), "+f"(d[7]), "+f"(d[8]), "+f"(d[9]), "+f"(d[10]), "+f"(d[11]), "+f"(d[12]), "+f"(d[13]), "+f"(d[14]), "+f"(d[15]), "+f"(d[16]), "+f"(d[17]), "+f"(d[18]), "+f"(d[19]), "+f"(d[20]), "+f"(d[21]), "+f"(d[22]), "+f"(d[23]), "+f"(d[24]), "+f"(d[25]), "+f"(d[26]), "+f"(d[27]), "+f"(d[28]), "+f"(d[29]), "+f"(d[30]), "+f"(d[31]), "+f"(d[32]), "+f"(d[33]), "+f"(d[34]), "+f"(d[35]), "+f"(d[36]), "+f"(d[37]), "+f"(d[38]), "+f"(d[39]), "+f"(d[40]), "+f"(d[41]), "+f"(d[42]), "+f"(d[43]), "+f"(d[44]), "+f"(d[45]), "+f"(d[46]), "+f"(d[47]), "+f"(d[48]), "+f"(d[49]), "+f"(d[50]), "+f"(d[51]), "+f"(d[52]), "+f"(d[53]), "+f"(d[54]), "+f"(d[55]), "+f"(d[56]), "+f"(d[57]), "+f"(d[58]), "+f"(d[59]), "+f"(d[60]), "+f"(d[61]), "+f"(d[62]), "+f"(d[63]), "+f"(e[0]), "+f"(e[1]), "+f"(e[2]), "+f"(e[3]), "+f"(e[4]), "+f"(e[5]), "+f"(e[6]), "+f"(e[7]), "+f"(e[8]), "+f"(e[9]), "+f"(e[10]), "+f"(e[11]), "+f"(e[12]), "+f"(e[13]), "+f"(e[14]), "+f"(e[15]), "+f"(e[16]), "+f"(e[17]), "+f"(e[18]), "+f"(e[19]), "+f"(e[20]), "+f"(e[21]), "+f"(e[22]), "+f"(e[23]), "+f"(e[24]), "+f"(e[25]), "+f"(e[26]), "+f"(e[27]), "+f"(e[28]), "+f"(e[29]), "+f"(e[30]), "+f"(e[31]), "+f"(e[32]), "+f"(e[33]), "+f"(e[34]), "+f"(e[35]), "+f"(e[36]), "+f"(e[37]), "+f"(e[38]), "+f"(e[39]), "+f"(e[40]), "+f"(e[41]), "+f"(e[42]), "+f"(e[43]), "+f"(e[44]), "+f"(e[45]), "+f"(e[46]), "+f"(e[47]), "+f"(e[48]), "+f"(e[49]), "+f"(e[50]), "+f"(e[51]), "+f"(e[52]), "+f"(e[53]), "+f"(e[54]), "+f"(e[55]), "+f"(e[56]), "+f"(e[57]), "+f"(e[58]), "+f"(e[59]), "+f"(e[60]), "+f"(e[61]), "+f"(e[62]), "+f"(e[63])
    : "r"(a0), "r"(a1), "r"(a2), "r"(a3), "l"(db), "r"(scale_d));
}

__device__ __forceinline__ void wgmma_rs_n128_z(float (&d)[64], uint32_t a0, uint32_t a1, uint32_t a2, uint32_t a3, uint64_t db) {
  asm volatile("{\n.reg .pred p;\nsetp.ne.b32 p, 0, 0;\n"
    "wgmma.mma_async.sync.aligned.m64n128k16.f32.bf16.bf16 {%0, %1, %2, %3, %4, %5, %6, %7, %8, %9, %10, %11, %12, %13, %14, %15, %16, %17, %18, %19, %20, %21, %22, %23, %24, %25, %26, %27, %28, %29, %30, %31, %32, %33, %34, %35, %36, %37, %38, %39, %40, %41, %42, %43, %44, %45, %46, %47, %48, %49, %50, %51, %52, %53, %54, %55, %56, %57, %58, %59, %60, %61, %62, %63}, {%64, %65, %66, %67}, %68, p, 1, 1, 0;\n}\n"
    : "=f"(d[0]), "=f"(d[1]), "=f"(d[2]), "=f"(d[3]), "=f"(d[4]), "=f"(d[5]), "=f"(d[6]), "=f"(d[7]), "=f"(d[8]), "=f"(d[9]), "=f"(d[10]), "=f"(d[11]), "=f"(d[12]), "=f"(d[13]), "=f"(d[14]), "=f"(d[15]), "=f"(d[16]), "=f"(d[17]), "=f"(d[18]), "=f"(d[19]), "=f"(d[20]), "=f"(d[21]), "=f"(d[22]), "=f"(d[23]), "=f"(d[24]), "=f"(d[25]), "=f"(d[26]), "=f"(d[27]), "=f"(d[28]), "=f"(d[29]), "=f"(d[30]), "=f"(d[31]), "=f"(d[32]), "=f"(d[33]), "=f"(d[34]), "=f"(d[35]), "=f"(d[36]), "=f"(d[37]), "=f"(d[38]), "=f"(d[39]), "=f"(d[40]), "=f"(d[41]), "=f"(d[42]), "=f"(d[43]), "=f"(d[44]), "=f"(d[45]), "=f"(d[46]), "=f"(d[47]), "=f"(d[48]), "=f"(d[49]), "=f"(d[50]), "=f"(d[51]), "=f"(d[52]), "=f"(d[53]), "=f"(d[54]), "=f"(d[55]), "=f"(d[56]), "=f"(d[57]), "=f"(d[58]), "=f"(d[59]), "=f"(d[60]), "=f"(d[61]), "=f"(d[62]), "=f"(d[63])
    : "r"(a0), "r"(a1), "r"(a2), "r"(a3), "l"(db));
}

__device__ __forceinline__ void wgmma_rs_n64_tb_z(float (&d)[32], uint32_t a0, uint32_t a1, uint32_t a2, uint32_t a3, uint64_t db) {
  asm volatile("{\n.reg .pred p;\nsetp.ne.b32 p, 0, 0;\n"
    "wgmma.mma_async.sync.aligned.m64n64k16.f32.bf16.bf16 {%0, %1, %2, %3, %4, %5, %6, %7, %8, %9, %10, %11, %12, %13, %14, %15, %16, %17, %18, %19, %20, %21, %22, %23, %24, %25, %26, %27, %28, %29, %30, %31}, {%32, %33, %34, %35}, %36, p, 1, 1, 1;\n}\n"
    : "=f"(d[0]), "=f"(d[1]), "=f"(d[2]), "=f"(d[3]), "=f"(d[4]), "=f"(d[5]), "=f"(d[6]), "=f"(d[7]), "=f"(d[8]), "=f"(d[9]), "=f"(d[10]), "=f"(d[11]), "=f"(d[12]), "=f"(d[13]), "=f"(d[14]), "=f"(d[15]), "=f"(d[16]), "=f"(d[17]), "=f"(d[18]), "=f"(d[19]), "=f"(d[20]), "=f"(d[21]), "=f"(d[22]), "=f"(d[23]), "=f"(d[24]), "=f"(d[25]), "=f"(d[26]), "=f"(d[27]), "=f"(d[28]), "=f"(d[29]), "=f"(d[30]), "=f"(d[31])
    : "r"(a0), "r"(a1), "r"(a2), "r"(a3), "l"(db));
}

__device__ __forceinline__ void wgmma_rs_n256_tb_z(float (&d)[64], float (&e)[64], uint32_t a0, uint32_t a1, uint32_t a2, uint32_t a3, uint64_t db) {
  asm volatile("{\n.reg .pred p;\nsetp.ne.b32 p, 0, 0;\n"
    "wgmma.mma_async.sync.aligned.m64n256k16.f32.bf16.bf16 {%0, %1, %2, %3, %4, %5, %6, %7, %8, %9, %10, %11, %12, %13, %14, %15, %16, %17, %18, %19, %20, %21, %22, %23, %24, %25, %26, %27, %28, %29, %30, %31, %32, %33, %34, %35, %36, %37, %38, %39, %40, %41, %42, %43, %44, %45, %46, %47, %48, %49, %50, %51, %52, %53, %54, %55, %56, %57, %58, %59, %60, %61, %62, %63, %64, %65, %66, %67, %68, %69, %70, %71, %72, %73, %74, %75, %76, %77, %78, %79, %80, %81, %82, %83, %84, %85, %86, %87, %88, %89, %90, %91, %92, %93, %94, %95, %96, %97, %98, %99, %100, %101, %102, %103, %104, %105, %106, %107, %108, %109, %110, %111, %112, %113, %114, %115, %116, %117, %118, %119, %120, %121, %122, %123, %124, %125, %126, %127}, {%128, %129, %130, %131}, %132, p, 1, 1, 1;\n}\n"
    : "=f"(d[0]), "=f"(d[1]), "=f"(d[2]), "=f"(d[3]), "=f"(d[4]), "=f"(d[5]), "=f"(d[6]), "=f"(d[7]), "=f"(d[8]), "=f"(d[9]), "=f"(d[10]), "=f"(d[11]), "=f"(d[12]), "=f"(d[13]), "=f"(d[14]), "=f"(d[15]), "=f"(d[16]), "=f"(d[17]), "=f"(d[18]), "=f"(d[19]), "=f"(d[20]), "=f"(d[21]), "=f"(d[22]), "=f"(d[23]), "=f"(d[24]), "=f"(d[25]), "=f"(d[26]), "=f"(d[27]), "=f"(d[28]), "=f"(d[29]), "=f"(d[30]), "=f"(d[31]), "=f"(d[32]), "=f"(d[33]), "=f"(d[34]), "=f"(d[35]), "=f"(d[36]), "=f"(d[37]), "=f"(d[38]), "=f"(d[39]), "=f"(d[40]), "=f"(d[41]), "=f"(d[42]), "=f"(d[43]), "=f"(d[44]), "=f"(d[45]), "=f"(d[46]), "=f"(d[47]), "=f"(d[48]), "=f"(d[49]), "=f"(d[50]), "=f"(d[51]), "=f"(d[52]), "=f"(d[53]), "=f"(d[54]), "=f"(d[55]), "=f"(d[56]), "=f"(d[57]), "=f"(d[58]), "=f"(d[59]), "=f"(d[60]), "=f"(d[61]), "=f"(d[62]), "=f"(d[63]), "=f"(e[0]), "=f"(e[1]), "=f"(e[2]), "=f"(e[3]), "=f"(e[4]), "=f"(e[5]), "=f"(e[6]), "=f"(e[7]), "=f"(e[8]), "=f"(e[9]), "=f"(e[10]), "=f"(e[11]), "=f"(e[12]), "=f"(e[13]), "=f"(e[14]), "=f"(e[15]), "=f"(e[16]), "=f"(e[17]), "=f"(e[18]), "=f"(e[19]), "=f"(e[20]), "=f"(e[21]), "=f"(e[22]), "=f"(e[23]), "=f"(e[24]), "=f"(e[25]), "=f"(e[26]), "=f"(e[27]), "=f"(e[28]), "=f"(e[29]), "=f"(e[30]), "=f"(e[31]), "=f"(e[32]), "=f"(e[33]), "=f"(e[34]), "=f"(e[35]), "=f"(e[36]), "=f"(e[37]), "=f"(e[38]), "=f"(e[39]), "=f"(e[40]), "=f"(e[41]), "=f"(e[42]), "=f"(e[43]), "=f"(e[44]), "=f"(e[45]), "=f"(e[46]), "=f"(e[47]), "=f"(e[48]), "=f"(e[49]), "=f"(e[50]), "=f"(e[51]), "=f"(e[52]), "=f"(e[53]), "=f"(e[54]), "=f"(e[55]), "=f"(e[56]), "=f"(e[57]), "=f"(e[58]), "=f"(e[59]), "=f"(e[60]), "=f"(e[61]), "=f"(e[62]), "=f"(e[63])
    : "r"(a0), "r"(a1), "r"(a2), "r"(a3), "l"(db));
}

__device__ __forceinline__ void wgmma_rs_n192_tb(float (&d)[64], float (&e)[64], uint32_t a0, uint32_t a1, uint32_t a2, uint32_t a3, uint64_t db) {
  asm volatile("{\n.reg .pred p;\nsetp.eq.b32 p, 0, 0;\n"
    "wgmma.mma_async.sync.aligned.m64n192k16.f32.bf16.bf16 {%0, %1, %2, %3, %4, %5, %6, %7, %8, %9, %10, %11, %12, %13, %14, %15, %16, %17, %18, %19, %20, %21, %22, %23, %24, %25, %26, %27, %28, %29, %30, %31, %32, %33, %34, %35, %36, %37, %38, %39, %40, %41, %42, %43, %44, %45, %46, %47, %48, %49, %50, %51, %52, %53, %54, %55, %56, %57, %58, %59, %60, %61, %62, %63, %64, %65, %66, %67, %68, %69, %70, %71, %72, %73, %74, %75, %76, %77, %78, %79, %80, %81, %82, %83, %84, %85, %86, %87, %88, %89, %90, %91, %92, %93, %94, %95}, {%96, %97, %98, %99}, %100, p, 1, 1, 1;\n}\n"
    : "+f"(d[0]), "+f"(d[1]), "+f"(d[2]), "+f"(d[3]), "+f"(d[4]), "+f"(d[5]), "+f"(d[6]), "+f"(d[7]), "+f"(d[8]), "+f"(d[9]), "+f"(d[10]), "+f"(d[11]), "+f"(d[12]), "+f"(d[13]), "+f"(d[14]), "+f"(d[15]), "+f"(d[16]), "+f"(d[17]), "+f"(d[18]), "+f"(d[19]), "+f"(d[20]), "+f"(d[21]), "+f"(d[22]), "+f"(d[23]), "+f"(d[24]), "+f"(d[25]), "+f"(d[26]), "+f"(d[27]), "+f"(d[28]), "+f"(d[29]), "+f"(d[30]), "+f"(d[31]), "+f"(d[32]), "+f"(d[33]), "+f"(d[34]), "+f"(d[35]), "+f"(d[36]), "+f"(d[37]), "+f"(d[38]), "+f"(d[39]), "+f"(d[40]), "+f"(d[41]), "+f"(d[42]), "+f"(d[43]), "+f"(d[44]), "+f"(d[45]), "+f"(d[46]), "+f"(d[47]), "+f"(d[48]), "+f"(d[49]), "+f"(d[50]), "+f"(d[51]), "+f"(d[52]), "+f"(d[53]), "+f"(d[54]), "+f"(d[55]), "+f"(d[56]), "+f"(d[57]), "+f"(d[58]), "+f"(d[59]), "+f"(d[60]), "+f"(d[61]), "+f"(d[62]), "+f"(d[63]), "+f"(e[0]), "+f"(e[1]), "+f"(e[2]), "+f"(e[3]), "+f"(e[4]), "+f"(e[5]), "+f"(e[6]), "+f"(e[7]), "+f"(e[8]), "+f"(e[9]), "+f"(e[10]), "+f"(e[11]), "+f"(e[12]), "+f"(e[13]), "+f"(e[14]), "+f"(e[15]), "+f"(e[16]), "+f"(e[17]), "+f"(e[18]), "+f"(e[19]), "+f"(e[20]), "+f"(e[21]), "+f"(e[22]), "+f"(e[23]), "+f"(e[24]), "+f"(e[25]), "+f"(e[26]), "+f"(e[27]), "+f"(e[28]), "+f"(e[29]), "+f"(e[30]), "+f"(e[31])
    : "r"(a0), "r"(a1), "r"(a2), "r"(a3), "l"(db));
}

__device__ __forceinline__ void wgmma_rs_n192_tb_z(float (&d)[64], float (&e)[64], uint32_t a0, uint32_t a1, uint32_t a2, uint32_t a3, uint64_t db) {
  asm volatile("{\n.reg .pred p;\nsetp.ne.b32 p, 0, 0;\n"
    "wgmma.mma_async.sync.aligned.m64n192k16.f32.bf16.bf16 {%0, %1, %2, %3, %4, %5, %6, %7, %8, %9, %10, %11, %12, %13, %14, %15, %16, %17, %18, %19, %20, %21, %22, %23, %24, %25, %26, %27, %28, %29, %30, %31, %32, %33, %34, %35, %36, %37, %38, %39, %40, %41, %42, %43, %44, %45, %46, %47, %48, %49, %50, %51, %52, %53, %54, %55, %56, %57, %58, %59, %60, %61, %62, %63, %64, %65, %66, %67, %68, %69, %70, %71, %72, %73, %74, %75, %76, %77, %78, %79, %80, %81, %82, %83, %84, %85, %86, %87, %88, %89, %90, %91, %92, %93, %94, %95}, {%96, %97, %98, %99}, %100, p, 1, 1, 1;\n}\n"
    : "=f"(d[0]), "=f"(d[1]), "=f"(d[2]), "=f"(d[3]), "=f"(d[4]), "=f"(d[5]), "=f"(d[6]), "=f"(d[7]), "=f"(d[8]), "=f"(d[9]), "=f"(d[10]), "=f"(d[11]), "=f"(d[12]), "=f"(d[13]), "=f"(d[14]), "=f"(d[15]), "=f"(d[16]), "=f"(d[17]), "=f"(d[18]), "=f"(d[19]), "=f"(d[20]), "=f"(d[21]), "=f"(d[22]), "=f"(d[23]), "=f"(d[24]), "=f"(d[25]), "=f"(d[26]), "=f"(d[27]), "=f"(d[28]), "=f"(d[29]), "=f"(d[30]), "=f"(d[31]), "=f"(d[32]), "=f"(d[33]), "=f"(d[34]), "=f"(d[35]), "=f"(d[36]), "=f"(d[37]), "=f"(d[38]), "=f"(d[39]), "=f"(d[40]), "=f"(d[41]), "=f"(d[42]), "=f"(d[43]), "=f"(d[44]), "=f"(d[45]), "=f"(d[46]), "=f"(d[47]), "=f"(d[48]), "=f"(d[49]), "=f"(d[50]), "=f"(d[51]), "=f"(d[52]), "=f"(d[53]), "=f"(d[54]), "=f"(d[55]), "=f"(d[56]), "=f"(d[57]), "=f"(d[58]), "=f"(d[59]), "=f"(d[60]), "=f"(d[61]), "=f"(d[62]), "=f"(d[63]), "=f"(e[0]), "=f"(e[1]), "=f"(e[2]), "=f"(e[3]), "=f"(e[4]), "=f"(e[5]), "=f"(e[6]), "=f"(e[7]), "=f"(e[8]), "=f"(e[9]), "=f"(e[10]), "=f"(e[11]), "=f"(e[12]), "=f"(e[13]), "=f"(e[14]), "=f"(e[15]), "=f"(e[16]), "=f"(e[17]), "=f"(e[18]), "=f"(e[19]), "=f"(e[20]), "=f"(e[21]), "=f"(e[22]), "=f"(e[23]), "=f"(e[24]), "=f"(e[25]), "=f"(e[26]), "=f"(e[27]), "=f"(e[28]), "=f"(e[29]), "=f"(e[30]), "=f"(e[31])
    : "r"(a0), "r"(a1), "r"(a2), "r"(a3), "l"(db));
}

struct Maps {
  CUtensorMap x[2], k[2], v[2], wq[2], wo[2];
  const char *px[2], *pwo[2];
};

__device__ __forceinline__ void poll_tiles(int tile, const unsigned (&target)[3], uint32_t ready) {
#pragma unroll
  for (int pn = 0; pn < 3; pn++) {
    const unsigned* c = &g_cnt[(tile * 4 + pn) * 32];
    for (uint32_t it = 0; it < WAIT_LIMIT; ++it) {
      unsigned v;
      asm volatile("ld.acquire.gpu.global.u32 %0, [%1];" : "=r"(v) : "l"(c) : "memory");
      if ((int)(v - target[pn]) >= 0) break;
    }
    mbar_arrive(ready + pn * 8);
  }
}
__device__ __forceinline__ void read_targets(int tile, unsigned (&target)[3]) {
#pragma unroll
  for (int pn = 0; pn < 3; pn++) {
    unsigned v;
    asm volatile("ld.relaxed.gpu.global.u32 %0, [%1];" : "=r"(v) : "l"(&g_cnt[(tile * 4 + pn) * 32]) : "memory");
    target[pn] = (v / 16u + 1u) * 16u;
  }
}

__global__ void __cluster_dims__(2, 1, 1) __launch_bounds__(384, 1)
fused_gqa_kernel(const __grid_constant__ Maps maps, __nv_bfloat16* __restrict__ out) {
  extern __shared__ __align__(1024) unsigned char smem[];
  const uint32_t sbase = smem_u32(smem);
  const uint32_t full0 = sbase + BAR_OFF;
  const uint32_t empty0 = full0 + N_ITEMS * 8;
  const uint32_t ready0 = empty0 + N_ITEMS * 8;
  const uint32_t pub0 = ready0 + 6 * 8;

  const int tid = threadIdx.x;
  const int wg = tid >> 7;
  const int bid = blockIdx.x;
  const int bp = bid & 3;
  const int h = (bid >> 2) & 15;
  const int p = bid >> 6;

  if (tid == 0) {
#pragma unroll
    for (int i = 0; i < 5; i++) mbar_init(full0 + (WQ0 + i) * 8, 1);
#pragma unroll
    for (int i = 0; i < 4; i++) mbar_init(full0 + (X0 + i) * 8, 1);
    asm volatile("fence.mbarrier_init.release.cluster;" ::: "memory");
#pragma unroll
    for (int kc = 0; kc < 5; kc++) {
      if (kc < 4) {
        mbar_expect_tx(full0 + (X0 + kc) * 8, 16384);
        tma_load3(sbase + x_off(kc), &maps.x[p], 0, bp * 128, kc, full0 + (X0 + kc) * 8);
      }
      mbar_expect_tx(full0 + (WQ0 + kc) * 8, T32);
      tma_load3(sbase + wq_off(kc), &maps.wq[p], 0, kc * 64, h * 4, full0 + (WQ0 + kc) * 8);
    }
    TR(0, 56);
  } else if (tid >= 64 && tid < 96) {
    const char* base = maps.px[p] + (size_t)(bp * 128 + h * 8) * 1152;
#pragma unroll
    for (int i = 0; i < 3; i++)
      if ((tid & 31) + i * 32 < 72) l2_prefetch(base + ((tid & 31) + i * 32) * 128);
  } else if (tid == 32) {
    prefetch_tmap(&maps.k[p]);
    prefetch_tmap(&maps.v[p]);
    prefetch_tmap(&maps.wo[p]);
  } else if (tid >= 128) {
    const int i = tid - 128;
    if (i < N_ITEMS) {
      if (!(i < 5 || (i >= X0 && i < X0 + 4))) mbar_init(full0 + i * 8, 1);
    } else if (i >= 64 && i < 64 + N_ITEMS) {
      mbar_init(empty0 + (i - 64) * 8, 8);
    } else if (i >= 128 && i < 128 + 6) {
      mbar_init(ready0 + (i - 128) * 8, 1);
    } else if (i >= 160 && i < 160 + 6) {
      mbar_init(pub0 + (i - 160) * 8, 4);
    }
    asm volatile("fence.mbarrier_init.release.cluster;" ::: "memory");
  }
  __syncthreads();
  if (tid == 0) TR(0, 57);

  if (wg == 0) {
    asm volatile("setmaxnreg.dec.sync.aligned.u32 24;");
    if (tid == 0) {
#pragma unroll 1
      for (int c = 0; c < 6; c++) {
        mbar_wait(empty0 + (X0 + c) * 8);
        if (c < 5) {
          mbar_expect_tx(full0 + (X0 + c + 4) * 8, 16384);
          tma_load3(sbase + x_off(c + 4), &maps.x[p], 0, bp * 128, c + 4, full0 + (X0 + c + 4) * 8);
        }
        if (c < 3 || c == 5) {
          const int kc = c < 3 ? c + 5 : 8;
          TR(0, WQ0 + kc);
          mbar_expect_tx(full0 + (WQ0 + kc) * 8, T32);
          tma_load3(sbase + wq_off(kc), &maps.wq[p], 0, kc * 64, h * 4, full0 + (WQ0 + kc) * 8);
        }
      }
      unsigned target[3];
      read_targets(p * 8 + 2 * bp + 1, target);
#pragma unroll 1
      for (int m = 0; m < N_WO; m++) {
        const int dep = m >= 6 ? WO0 + m - 6 : (m < 4 ? X0 + 8 : KV0 + 9 + m);
        mbar_wait(empty0 + dep * 8);
        const uint32_t fb = full0 + (WO0 + m) * 8;
        TR(0, WO0 + m);
        mbar_expect_tx(fb, WO_BYTES);
        tma_load3(sbase + wo_off(m), &maps.wo[p], 0, h * 256 + (m & 3) * 64, (m >> 2) * 3, fb);
      }
      poll_tiles(p * 8 + 2 * bp + 1, target, ready0 + 24);
    } else if (tid == 96) {
      unsigned target[3];
#pragma unroll 1
      for (int n = 0; n < N_KV; n++) {
        if (n == 3) read_targets(p * 8 + 2 * bp, target);
        mbar_wait(empty0 + (n >= 3 ? KV0 + n - 3 : (n < 2 ? X0 + 3 + n : X0 + 7)) * 8);
        if (n >= KV_INFLIGHT) mbar_wait(full0 + (KV0 + n - KV_INFLIGHT) * 8);
        const uint32_t fb = full0 + (KV0 + n) * 8;
        const CUtensorMap* tm = (n & 1) ? &maps.v[p] : &maps.k[p];
        const int row = ((2 * bp + (n >> 3)) * 16 + h) * kSK + ((n & 7) >> 1) * 128;
        TR(0, KV0 + n);
        mbar_expect_tx(fb, T32);
        tma_load3(sbase + kv_off(n), tm, 0, row, 0, fb);
      }
      mbar_wait(pub0);
      poll_tiles(p * 8 + 2 * bp, target, ready0);
    } else if (tid >= 32 && tid < 96) {
      const int w = (tid >> 5) - 1;
      if (w == 0) {
        mbar_wait(full0 + (KV0 + WO_PF_AT) * 8);
        const char* base = maps.pwo[p] + (size_t)(h * 256 + bp * 64) * 1152 + 384;
#pragma unroll 1
        for (int i = tid & 31; i < 64 * 6; i += 32) l2_prefetch(base + (i / 6) * 1152 + (i % 6) * 128);
      }
      if (tid & 31) return;
      const int tile = p * 8 + 2 * bp + w;
#pragma unroll 1
      for (int e = 0; e < 3; e++) {
        mbar_wait(pub0 + (w * 3 + e) * 8);
        __threadfence();
        asm volatile("red.relaxed.gpu.global.add.u32 [%0], 1;" ::"l"(&g_cnt[(tile * 4 + e) * 32]) : "memory");
      }
    }
  } else {
    asm volatile("setmaxnreg.inc.sync.aligned.u32 240;");
    const int w = wg - 1;
    const int t128 = tid & 127;
    const int lane = tid & 31;

    auto release = [&](int item) {
      __syncwarp();
      if (lane == 0) mbar_arrive(empty0 + item * 8);
    };

    TRC(0);
    const float cs = 0.08838834764831845f * 1.4426950408889634f;
    float s[64], o[64];
#pragma unroll
    for (int i = 0; i < 64; i++) s[i] = 0.f, o[i] = 0.f;
    uint32_t qf[32];
    uint4* park = reinterpret_cast<uint4*>(smem + PARK_OFF) + w * 1024 + t128;
    {
#pragma unroll 1
      for (int kc = 0; kc < 9; kc++) {
        mbar_wait(full0 + (X0 + kc) * 8);
        mbar_wait(full0 + (WQ0 + kc) * 8);
        if (kc == 0) TRC(1);
        const uint64_t da = make_desc(sbase + x_off(kc), 16, 1024);
        const uint64_t db = make_desc(sbase + wq_off(kc) + w * 16384, 8192, 1024);
        wg_fence();
#pragma unroll
        for (int ks = 0; ks < 4; ks++) {
          wgmma_ss_n128_tb(s, da + ks * 2, db + ks * 128, (kc | ks) != 0);
          wgmma_ss_n128_tb(o, da + 512 + ks * 2, db + ks * 128, (kc | ks) != 0);
        }
        wg_commit();
        wg_wait<0>();
        release(X0 + kc);
      }
      fence_regs(s);
      fence_regs(o);
#pragma unroll
      for (int i = 0; i < 32; i++) qf[i] = pack_bf16(s[2 * i], s[2 * i + 1]);
      named_bar(1, 256);
#pragma unroll
      for (int i = 0; i < 8; i++) park[i * 128] = pack8(o, i);
      TRC(2);
    }
#pragma unroll 1
    for (int bb = 0; bb < 2; bb++) {
#pragma unroll
      for (int i = 0; i < 64; i++) o[i] = 0.f;
      float m0 = -INFINITY, m1 = -INFINITY, l0 = 0.f, l1 = 0.f;
#pragma unroll 1
      for (int t = 0; t < 4; t++) {
        const int n = bb * 8 + t * 2;
        {
          const uint32_t base = sbase + kv_off(n);
          mbar_wait(full0 + (KV0 + n) * 8);
          if (n == 0 && w == 1) named_bar(4, 256);
          const uint64_t db = make_desc(base, 16, 1024);
          wg_fence();
          wgmma_rs_n128_z(s, qf[0], qf[1], qf[2], qf[3], db);
#pragma unroll
          for (int ks = 1; ks < 8; ks++)
            wgmma_rs_n128(s, qf[4 * ks], qf[4 * ks + 1], qf[4 * ks + 2], qf[4 * ks + 3], db + (ks >> 2) * 1024 + (ks & 3) * 2, 1);
          wg_commit();
          wg_wait<0>();
          fence_regs(s);
          if (n == 0 && w == 0) named_arrive(4, 256);
          release(KV0 + n);
        }
        float mx0 = s[0], mx1 = s[2];
#pragma unroll
        for (int g = 0; g < 16; g++) {
          mx0 = fmaxf(mx0, fmaxf(s[4 * g], s[4 * g + 1]));
          mx1 = fmaxf(mx1, fmaxf(s[4 * g + 2], s[4 * g + 3]));
        }
        mx0 = fmaxf(mx0, __shfl_xor_sync(0xffffffffu, mx0, 1));
        mx0 = fmaxf(mx0, __shfl_xor_sync(0xffffffffu, mx0, 2));
        mx1 = fmaxf(mx1, __shfl_xor_sync(0xffffffffu, mx1, 1));
        mx1 = fmaxf(mx1, __shfl_xor_sync(0xffffffffu, mx1, 2));
        const float mn0 = fmaxf(m0, mx0), mn1 = fmaxf(m1, mx1);
        const float a0 = ex2((m0 - mn0) * cs), a1 = ex2((m1 - mn1) * cs);
        m0 = mn0;
        m1 = mn1;
        const float ms0 = mn0 * cs, ms1 = mn1 * cs;
        float rs0 = 0.f, rs1 = 0.f;
        uint32_t pf[32];
#pragma unroll
        for (int g = 0; g < 16; g++) {
          const float p0 = ex2(fmaf(s[4 * g], cs, -ms0));
          const float p1 = ex2(fmaf(s[4 * g + 1], cs, -ms0));
          const float p2 = ex2(fmaf(s[4 * g + 2], cs, -ms1));
          const float p3 = ex2(fmaf(s[4 * g + 3], cs, -ms1));
          rs0 += p0 + p1;
          rs1 += p2 + p3;
          pf[2 * g] = pack_bf16(p0, p1);
          pf[2 * g + 1] = pack_bf16(p2, p3);
        }
        l0 = l0 * a0 + rs0;
        l1 = l1 * a1 + rs1;
#pragma unroll
        for (int g = 0; g < 16; g++) {
          o[4 * g] *= a0;
          o[4 * g + 1] *= a0;
          o[4 * g + 2] *= a1;
          o[4 * g + 3] *= a1;
        }
        {
          const uint32_t base = sbase + kv_off(n + 1);
          mbar_wait(full0 + (KV0 + n + 1) * 8);
          const uint64_t db = make_desc(base, 16384, 1024);
          wg_fence();
#pragma unroll
          for (int ks = 0; ks < 8; ks++)
            wgmma_rs_n128_tb(o, pf[4 * ks], pf[4 * ks + 1], pf[4 * ks + 2], pf[4 * ks + 3], db + ks * 128, 1);
          wg_commit();
          wg_wait<0>();
          fence_regs(o);
          release(KV0 + n + 1);
          TRC(3 + bb * 5 + t);
        }
      }
      l0 += __shfl_xor_sync(0xffffffffu, l0, 1);
      l0 += __shfl_xor_sync(0xffffffffu, l0, 2);
      l1 += __shfl_xor_sync(0xffffffffu, l1, 1);
      l1 += __shfl_xor_sync(0xffffffffu, l1, 2);
      const float i0 = 1.f / l0, i1 = 1.f / l1;
      uint4* dst = park;
      if (bb == 0) {
#pragma unroll
        for (int i = 0; i < 8; i++) {
          const uint4 v = park[i * 128];
          qf[4 * i] = v.x;
          qf[4 * i + 1] = v.y;
          qf[4 * i + 2] = v.z;
          qf[4 * i + 3] = v.w;
        }
      } else {
        named_bar(1, 256);
        dst = reinterpret_cast<uint4*>(smem + KV_OFF) + w * 1024 + t128;
      }
#pragma unroll
      for (int i = 0; i < 8; i++)
        dst[i * 128] = make_uint4(pack_bf16(o[8 * i] * i0, o[8 * i + 1] * i0), pack_bf16(o[8 * i + 2] * i1, o[8 * i + 3] * i1),
                                  pack_bf16(o[8 * i + 4] * i0, o[8 * i + 5] * i0), pack_bf16(o[8 * i + 6] * i1, o[8 * i + 7] * i1));
    }
    uint32_t af[64];
    {
      named_bar(1, 256);
      const uint4* src = reinterpret_cast<const uint4*>(smem + (w == 0 ? PARK_OFF : KV_OFF)) + t128;
#pragma unroll
      for (int i = 0; i < 16; i++) {
        const uint4 v = src[i * 128];
        af[4 * i] = v.x;
        af[4 * i + 1] = v.y;
        af[4 * i + 2] = v.z;
        af[4 * i + 3] = v.w;
      }
    }
    TRC(12);
    if (w == 1) named_bar(4, 256);
    const int tile = p * 8 + 2 * bp + w;
    uint4* part = g_part + (size_t)(tile * 16 + h) * 36 * 128 + t128;
#pragma unroll
    for (int pn = 0; pn < 3; pn++) {
#pragma unroll
      for (int kc = 0; kc < 4; kc++) {
        const int m = pn * 4 + kc;
        mbar_wait(full0 + (WO0 + m) * 8);
        const uint64_t db = make_desc(sbase + wo_off(m), 8192, 1024);
        wg_fence();
#pragma unroll
        for (int ks = 0; ks < 4; ks++) {
          const int a = (kc * 4 + ks) * 4;
          if ((kc | ks) == 0) wgmma_rs_n192_tb_z(s, o, af[a], af[a + 1], af[a + 2], af[a + 3], db);
          else wgmma_rs_n192_tb(s, o, af[a], af[a + 1], af[a + 2], af[a + 3], db + ks * 128);
        }
        wg_commit();
        if (m == 1 && w == 0) named_arrive(4, 256);
        if (kc > 0) {
          wg_wait<1>();
          if (m - 1 < 6) release(WO0 + m - 1);
        }
      }
      wg_wait<0>();
      fence_regs(s);
      fence_regs32(o);
      if (pn == 0) release(WO0 + 3);
      TRC(13 + pn * 2);
#pragma unroll
      for (int i = 0; i < 8; i++) __stcg(part + (pn * 12 + i) * 128, pack8(s, i));
#pragma unroll
      for (int i = 0; i < 4; i++) __stcg(part + (pn * 12 + 8 + i) * 128, pack8(o, i));
      __syncwarp();
      if (lane == 0) mbar_arrive(pub0 + (w * 3 + pn) * 8);
      TRC(14 + pn * 2);
    }
    if (t128 < 96) {
      const int u = h * 96 + t128;
      const int slot = u >> 7, thr = u & 127;
      const int row0 = (thr >> 5) * 16 + ((thr & 31) >> 2);
      __nv_bfloat16* orow = out + (size_t)((2 * bp + w) * 64 + row0) * 1152 + p * 576 + slot * 16 + (thr & 3) * 2;
      const uint4* pr = g_part + (size_t)(tile * 16) * 36 * 128 + slot * 128 + thr;
      uint4 v[3][16];
#pragma unroll
      for (int pn = 0; pn < 3; pn++) {
        mbar_wait(ready0 + (w * 3 + pn) * 8);
        TRC(19 + pn);
#pragma unroll
        for (int c = 0; c < 16; c++) v[pn][c] = __ldcg(pr + (size_t)(c * 36 + pn * 12) * 128);
      }
#pragma unroll
      for (int pn = 0; pn < 3; pn++) {
        float a[8];
#pragma unroll
        for (int e = 0; e < 8; e++) a[e] = 0.f;
#pragma unroll
        for (int c = 0; c < 16; c++) {
          a[0] += bf_lo(v[pn][c].x);
          a[1] += bf_hi(v[pn][c].x);
          a[2] += bf_lo(v[pn][c].y);
          a[3] += bf_hi(v[pn][c].y);
          a[4] += bf_lo(v[pn][c].z);
          a[5] += bf_hi(v[pn][c].z);
          a[6] += bf_lo(v[pn][c].w);
          a[7] += bf_hi(v[pn][c].w);
        }
        __nv_bfloat16* op = orow + pn * 192;
        *reinterpret_cast<uint32_t*>(op) = pack_bf16(a[0], a[1]);
        *reinterpret_cast<uint32_t*>(op + 8 * 1152) = pack_bf16(a[2], a[3]);
        *reinterpret_cast<uint32_t*>(op + 8) = pack_bf16(a[4], a[5]);
        *reinterpret_cast<uint32_t*>(op + 8 * 1152 + 8) = pack_bf16(a[6], a[7]);
      }
    }
    TRC(22);
  }
}

typedef CUresult (*EncodeFn)(CUtensorMap*, CUtensorMapDataType, cuuint32_t, void*, const cuuint64_t*, const cuuint64_t*,
                             const cuuint32_t*, const cuuint32_t*, CUtensorMapInterleave, CUtensorMapSwizzle,
                             CUtensorMapL2promotion, CUtensorMapFloatOOBfill);

void encode3d(EncodeFn fn, CUtensorMap* m, void* ptr, uint64_t cols, uint64_t rows, uint32_t box_rows, uint32_t box_chunks) {
  cuuint64_t dims[3] = {64, rows, cols / 64};
  cuuint64_t strides[2] = {cols * 2, 128};
  cuuint32_t box[3] = {64, box_rows, box_chunks};
  cuuint32_t es[3] = {1, 1, 1};
  fn(m, CU_TENSOR_MAP_DATA_TYPE_BFLOAT16, 3, ptr, dims, strides, box, es, CU_TENSOR_MAP_INTERLEAVE_NONE,
     CU_TENSOR_MAP_SWIZZLE_128B, CU_TENSOR_MAP_L2_PROMOTION_L2_256B, CU_TENSOR_MAP_FLOAT_OOB_FILL_NONE);
}

}

extern "C" void kernel_launch(void* const* d_in, const int* in_sizes, int n_in, void* d_out, int out_size) {
  static EncodeFn fn = nullptr;
  if (!fn) {
    void* f = nullptr;
    cudaDriverEntryPointQueryResult st;
    cudaGetDriverEntryPoint("cuTensorMapEncodeTiled", &f, cudaEnableDefault, &st);
    fn = (EncodeFn)f;
    cudaFuncSetAttribute(fused_gqa_kernel, cudaFuncAttributeMaxDynamicSharedMemorySize, SMEM_BYTES);
  }
  Maps maps;
  for (int p = 0; p < 2; p++) {
    encode3d(fn, &maps.x[p], d_in[p * 5 + 0], kD, 512, 128, 1);
    encode3d(fn, &maps.k[p], d_in[p * 5 + 1], kDH, 8 * 16 * kSK, 128, 2);
    encode3d(fn, &maps.v[p], d_in[p * 5 + 2], kDH, 8 * 16 * kSK, 128, 2);
    encode3d(fn, &maps.wq[p], d_in[p * 5 + 3], kHQD, kD, 64, 4);
    encode3d(fn, &maps.wo[p], d_in[p * 5 + 4], kD, kHQD, 64, 3);
    maps.px[p] = (const char*)d_in[p * 5 + 0];
    maps.pwo[p] = (const char*)d_in[p * 5 + 4];
  }
  fused_gqa_kernel<<<128, 384, SMEM_BYTES>>>(maps, (__nv_bfloat16*)d_out);
}
```

```cpp
#include <cuda_runtime.h>
#include <cuda_bf16.h>
#include <cuda.h>
#include <stdint.h>

namespace {

constexpr int kD = 576, kHQD = 4096, kSK = 512, kDH = 128;

constexpr int N_WQ = 9, N_X = 9, N_KV = 16, N_WO = 12;
constexpr int N_ITEMS = N_WQ + N_X + N_KV + N_WO;
constexpr int T32 = 32 * 1024;
constexpr int WO_BYTES = 24 * 1024;
constexpr int PARK_OFF = 192 * 1024;
constexpr int BAR_OFF = 224 * 1024;
constexpr int SMEM_BYTES = BAR_OFF + 2 * N_ITEMS * 8 + 256;
constexpr int WQ0 = 0, X0 = N_WQ, KV0 = X0 + N_X, WO0 = KV0 + N_KV;
#define KV_INFLIGHT 2

__device__ __forceinline__ int wq_off(int kc) { return (kc < 5 ? kc : kc - 5) * T32; }
__device__ __forceinline__ int x_off(int kc) { return ((kc & 2) ? 5 * T32 : PARK_OFF) + (kc & 1) * 16384; }
__device__ __forceinline__ int ring_off(int pos) { return (int)((0x352104u >> ((pos % 6) * 4)) & 15u) * T32; }
__device__ __forceinline__ int kv_off(int n) { return ring_off(n); }
__device__ __forceinline__ int wo_off(int m) { return ring_off(N_KV + m); }

__device__ uint4 g_part[16 * 16 * 36 * 128];
__device__ unsigned int g_cnt[16 * 4 * 32];

#define TR(role, ev)
#define TRC(ev)
constexpr uint32_t WAIT_CYCLES = 1u << 20;
constexpr uint32_t WAIT_LIMIT = 1u << 12;
__device__ __forceinline__ uint32_t smem_u32(const void* p) { return (uint32_t)__cvta_generic_to_shared(p); }
__device__ __forceinline__ void mbar_init(uint32_t bar, uint32_t cnt) {
  asm volatile("mbarrier.init.shared::cta.b64 [%0], %1;" ::"r"(bar), "r"(cnt) : "memory");
}
__device__ __forceinline__ void mbar_expect_tx(uint32_t bar, uint32_t bytes) {
  asm volatile("mbarrier.arrive.expect_tx.shared::cta.b64 _, [%0], %1;" ::"r"(bar), "r"(bytes) : "memory");
}
__device__ __forceinline__ void mbar_arrive(uint32_t bar) {
  asm volatile("mbarrier.arrive.shared::cta.b64 _, [%0];" ::"r"(bar) : "memory");
}
__device__ __forceinline__ bool mbar_try(uint32_t bar, uint32_t parity) {
  uint32_t ok;
  asm volatile(
      "{\n.reg .pred p;\nmbarrier.try_wait.parity.shared::cta.b64 p, [%1], %2;\nselp.u32 %0, 1, 0, p;\n}\n"
      : "=r"(ok)
      : "r"(bar), "r"(parity)
      : "memory");
  return ok != 0;
}
__device__ __forceinline__ void mbar_wait(uint32_t bar) {
  if (mbar_try(bar, 0)) return;
  const uint32_t t0 = (uint32_t)clock();
  while (!mbar_try(bar, 0))
    if ((uint32_t)clock() - t0 > WAIT_CYCLES) break;
}
__device__ __forceinline__ void tma_load3(uint32_t dst, const CUtensorMap* tm, int c0, int c1, int c2, uint32_t bar) {
  asm volatile(
      "cp.async.bulk.tensor.3d.shared::cluster.global.mbarrier::complete_tx::bytes [%0], [%1, {%3, %4, %5}], [%2];" ::"r"(dst),
      "l"(tm), "r"(bar), "r"(c0), "r"(c1), "r"(c2)
      : "memory");
}
__device__ __forceinline__ void l2_prefetch(const void* p) { asm volatile("prefetch.global.L2 [%0];" ::"l"(p) : "memory"); }
__device__ __forceinline__ void prefetch_tmap(const CUtensorMap* tm) {
  asm volatile("prefetch.tensormap [%0];" ::"l"(tm) : "memory");
}
__device__ __forceinline__ void named_bar(int id, int n) { asm volatile("bar.sync %0, %1;" ::"r"(id), "r"(n) : "memory"); }
__device__ __forceinline__ void named_arrive(int id, int n) { asm volatile("bar.arrive %0, %1;" ::"r"(id), "r"(n) : "memory"); }
__device__ __forceinline__ void wg_fence() { asm volatile("wgmma.fence.sync.aligned;" ::: "memory"); }
__device__ __forceinline__ void wg_commit() { asm volatile("wgmma.commit_group.sync.aligned;" ::: "memory"); }
template <int N>
__device__ __forceinline__ void wg_wait() { asm volatile("wgmma.wait_group.sync.aligned %0;" ::"n"(N) : "memory"); }
template <int N>
__device__ __forceinline__ void fence_regs(float (&d)[N]) {
#pragma unroll
  for (int i = 0; i < N; i++) asm volatile("" : "+f"(d[i])::"memory");
}
__device__ __forceinline__ void fence_regs32(float (&d)[64]) {
#pragma unroll
  for (int i = 0; i < 32; i++) asm volatile("" : "+f"(d[i])::"memory");
}
__device__ __forceinline__ uint64_t make_desc(uint32_t addr, uint32_t lbo, uint32_t sbo) {
  return (uint64_t)((addr & 0x3FFFF) >> 4) | ((uint64_t)(lbo >> 4) << 16) | ((uint64_t)(sbo >> 4) << 32) | (1ull << 62);
}
__device__ __forceinline__ uint32_t pack_bf16(float lo, float hi) {
  uint32_t r;
  asm("cvt.rn.bf16x2.f32 %0, %1, %2;" : "=r"(r) : "f"(hi), "f"(lo));
  return r;
}
__device__ __forceinline__ float ex2(float x) {
  float y;
  asm("ex2.approx.ftz.f32 %0, %1;" : "=f"(y) : "f"(x));
  return y;
}
__device__ __forceinline__ float bf_lo(uint32_t v) { return __uint_as_float(v << 16); }
__device__ __forceinline__ float bf_hi(uint32_t v) { return __uint_as_float(v & 0xffff0000u); }
template <int N>
__device__ __forceinline__ uint4 pack8(const float (&a)[N], int i) {
  return make_uint4(pack_bf16(a[8 * i], a[8 * i + 1]), pack_bf16(a[8 * i + 2], a[8 * i + 3]), pack_bf16(a[8 * i + 4], a[8 * i + 5]),
                    pack_bf16(a[8 * i + 6], a[8 * i + 7]));
}

__device__ __forceinline__ void wgmma_ss_n128_tb(float (&d)[64], uint64_t da, uint64_t db, int scale_d) {
  asm volatile("{\n.reg .pred p;\nsetp.ne.b32 p, %66, 0;\n"
    "wgmma.mma_async.sync.aligned.m64n128k16.f32.bf16.bf16 {%0, %1, %2, %3, %4, %5, %6, %7, %8, %9, %10, %11, %12, %13, %14, %15, %16, %17, %18, %19, %20, %21, %22, %23, %24, %25, %26, %27, %28, %29, %30, %31, %32, %33, %34, %35, %36, %37, %38, %39, %40, %41, %42, %43, %44, %45, %46, %47, %48, %49, %50, %51, %52, %53, %54, %55, %56, %57, %58, %59, %60, %61, %62, %63}, %64, %65, p, 1, 1, 0, 1;\n}\n"
    : "+f"(d[0]), "+f"(d[1]), "+f"(d[2]), "+f"(d[3]), "+f"(d[4]), "+f"(d[5]), "+f"(d[6]), "+f"(d[7]), "+f"(d[8]), "+f"(d[9]), "+f"(d[10]), "+f"(d[11]), "+f"(d[12]), "+f"(d[13]), "+f"(d[14]), "+f"(d[15]), "+f"(d[16]), "+f"(d[17]), "+f"(d[18]), "+f"(d[19]), "+f"(d[20]), "+f"(d[21]), "+f"(d[22]), "+f"(d[23]), "+f"(d[24]), "+f"(d[25]), "+f"(d[26]), "+f"(d[27]), "+f"(d[28]), "+f"(d[29]), "+f"(d[30]), "+f"(d[31]), "+f"(d[32]), "+f"(d[33]), "+f"(d[34]), "+f"(d[35]), "+f"(d[36]), "+f"(d[37]), "+f"(d[38]), "+f"(d[39]), "+f"(d[40]), "+f"(d[41]), "+f"(d[42]), "+f"(d[43]), "+f"(d[44]), "+f"(d[45]), "+f"(d[46]), "+f"(d[47]), "+f"(d[48]), "+f"(d[49]), "+f"(d[50]), "+f"(d[51]), "+f"(d[52]), "+f"(d[53]), "+f"(d[54]), "+f"(d[55]), "+f"(d[56]), "+f"(d[57]), "+f"(d[58]), "+f"(d[59]), "+f"(d[60]), "+f"(d[61]), "+f"(d[62]), "+f"(d[63])
    : "l"(da), "l"(db), "r"(scale_d));
}

__device__ __forceinline__ void wgmma_rs_n128(float (&d)[64], uint32_t a0, uint32_t a1, uint32_t a2, uint32_t a3, uint64_t db, int scale_d) {
  asm volatile("{\n.reg .pred p;\nsetp.ne.b32 p, %69, 0;\n"
    "wgmma.mma_async.sync.aligned.m64n128k16.f32.bf16.bf16 {%0, %1, %2, %3, %4, %5, %6, %7, %8, %9, %10, %11, %12, %13, %14, %15, %16, %17, %18, %19, %20, %21, %22, %23, %24, %25, %26, %27, %28, %29, %30, %31, %32, %33, %34, %35, %36, %37, %38, %39, %40, %41, %42, %43, %44, %45, %46, %47, %48, %49, %50, %51, %52, %53, %54, %55, %56, %57, %58, %59, %60, %61, %62, %63}, {%64, %65, %66, %67}, %68, p, 1, 1, 0;\n}\n"
    : "+f"(d[0]), "+f"(d[1]), "+f"(d[2]), "+f"(d[3]), "+f"(d[4]), "+f"(d[5]), "+f"(d[6]), "+f"(d[7]), "+f"(d[8]), "+f"(d[9]), "+f"(d[10]), "+f"(d[11]), "+f"(d[12]), "+f"(d[13]), "+f"(d[14]), "+f"(d[15]), "+f"(d[16]), "+f"(d[17]), "+f"(d[18]), "+f"(d[19]), "+f"(d[20]), "+f"(d[21]), "+f"(d[22]), "+f"(d[23]), "+f"(d[24]), "+f"(d[25]), "+f"(d[26]), "+f"(d[27]), "+f"(d[28]), "+f"(d[29]), "+f"(d[30]), "+f"(d[31]), "+f"(d[32]), "+f"(d[33]), "+f"(d[34]), "+f"(d[35]), "+f"(d[36]), "+f"(d[37]), "+f"(d[38]), "+f"(d[39]), "+f"(d[40]), "+f"(d[41]), "+f"(d[42]), "+f"(d[43]), "+f"(d[44]), "+f"(d[45]), "+f"(d[46]), "+f"(d[47]), "+f"(d[48]), "+f"(d[49]), "+f"(d[50]), "+f"(d[51]), "+f"(d[52]), "+f"(d[53]), "+f"(d[54]), "+f"(d[55]), "+f"(d[56]), "+f"(d[57]), "+f"(d[58]), "+f"(d[59]), "+f"(d[60]), "+f"(d[61]), "+f"(d[62]), "+f"(d[63])
    : "r"(a0), "r"(a1), "r"(a2), "r"(a3), "l"(db), "r"(scale_d));
}

__device__ __forceinline__ void wgmma_rs_n128_tb(float (&d)[64], uint32_t a0, uint32_t a1, uint32_t a2, uint32_t a3, uint64_t db, int scale_d) {
  asm volatile("{\n.reg .pred p;\nsetp.ne.b32 p, %69, 0;\n"
    "wgmma.mma_async.sync.aligned.m64n128k16.f32.bf16.bf16 {%0, %1, %2, %3, %4, %5, %6, %7, %8, %9, %10, %11, %12, %13, %14, %15, %16, %17, %18, %19, %20, %21, %22, %23, %24, %25, %26, %27, %28, %29, %30, %31, %32, %33, %34, %35, %36, %37, %38, %39, %40, %41, %42, %43, %44, %45, %46, %47, %48, %49, %50, %51, %52, %53, %54, %55, %56, %57, %58, %59, %60, %61, %62, %63}, {%64, %65, %66, %67}, %68, p, 1, 1, 1;\n}\n"
    : "+f"(d[0]), "+f"(d[1]), "+f"(d[2]), "+f"(d[3]), "+f"(d[4]), "+f"(d[5]), "+f"(d[6]), "+f"(d[7]), "+f"(d[8]), "+f"(d[9]), "+f"(d[10]), "+f"(d[11]), "+f"(d[12]), "+f"(d[13]), "+f"(d[14]), "+f"(d[15]), "+f"(d[16]), "+f"(d[17]), "+f"(d[18]), "+f"(d[19]), "+f"(d[20]), "+f"(d[21]), "+f"(d[22]), "+f"(d[23]), "+f"(d[24]), "+f"(d[25]), "+f"(d[26]), "+f"(d[27]), "+f"(d[28]), "+f"(d[29]), "+f"(d[30]), "+f"(d[31]), "+f"(d[32]), "+f"(d[33]), "+f"(d[34]), "+f"(d[35]), "+f"(d[36]), "+f"(d[37]), "+f"(d[38]), "+f"(d[39]), "+f"(d[40]), "+f"(d[41]), "+f"(d[42]), "+f"(d[43]), "+f"(d[44]), "+f"(d[45]), "+f"(d[46]), "+f"(d[47]), "+f"(d[48]), "+f"(d[49]), "+f"(d[50]), "+f"(d[51]), "+f"(d[52]), "+f"(d[53]), "+f"(d[54]), "+f"(d[55]), "+f"(d[56]), "+f"(d[57]), "+f"(d[58]), "+f"(d[59]), "+f"(d[60]), "+f"(d[61]), "+f"(d[62]), "+f"(d[63])
    : "r"(a0), "r"(a1), "r"(a2), "r"(a3), "l"(db), "r"(scale_d));
}

__device__ __forceinline__ void wgmma_rs_n32_tb(float (&d)[16], uint32_t a0, uint32_t a1, uint32_t a2, uint32_t a3, uint64_t db, int scale_d) {
  asm volatile("{\n.reg .pred p;\nsetp.ne.b32 p, %21, 0;\n"
    "wgmma.mma_async.sync.aligned.m64n32k16.f32.bf16.bf16 {%0, %1, %2, %3, %4, %5, %6, %7, %8, %9, %10, %11, %12, %13, %14, %15}, {%16, %17, %18, %19}, %20, p, 1, 1, 1;\n}\n"
    : "+f"(d[0]), "+f"(d[1]), "+f"(d[2]), "+f"(d[3]), "+f"(d[4]), "+f"(d[5]), "+f"(d[6]), "+f"(d[7]), "+f"(d[8]), "+f"(d[9]), "+f"(d[10]), "+f"(d[11]), "+f"(d[12]), "+f"(d[13]), "+f"(d[14]), "+f"(d[15])
    : "r"(a0), "r"(a1), "r"(a2), "r"(a3), "l"(db), "r"(scale_d));
}

__device__ __forceinline__ void wgmma_rs_n64_tb(float (&d)[32], uint32_t a0, uint32_t a1, uint32_t a2, uint32_t a3, uint64_t db, int scale_d) {
  asm volatile("{\n.reg .pred p;\nsetp.ne.b32 p, %37, 0;\n"
    "wgmma.mma_async.sync.aligned.m64n64k16.f32.bf16.bf16 {%0, %1, %2, %3, %4, %5, %6, %7, %8, %9, %10, %11, %12, %13, %14, %15, %16, %17, %18, %19, %20, %21, %22, %23, %24, %25, %26, %27, %28, %29, %30, %31}, {%32, %33, %34, %35}, %36, p, 1, 1, 1;\n}\n"
    : "+f"(d[0]), "+f"(d[1]), "+f"(d[2]), "+f"(d[3]), "+f"(d[4]), "+f"(d[5]), "+f"(d[6]), "+f"(d[7]), "+f"(d[8]), "+f"(d[9]), "+f"(d[10]), "+f"(d[11]), "+f"(d[12]), "+f"(d[13]), "+f"(d[14]), "+f"(d[15]), "+f"(d[16]), "+f"(d[17]), "+f"(d[18]), "+f"(d[19]), "+f"(d[20]), "+f"(d[21]), "+f"(d[22]), "+f"(d[23]), "+f"(d[24]), "+f"(d[25]), "+f"(d[26]), "+f"(d[27]), "+f"(d[28]), "+f"(d[29]), "+f"(d[30]), "+f"(d[31])
    : "r"(a0), "r"(a1), "r"(a2), "r"(a3), "l"(db), "r"(scale_d));
}

__device__ __forceinline__ void wgmma_rs_n256_tb(float (&d)[64], float (&e)[64], uint32_t a0, uint32_t a1, uint32_t a2, uint32_t a3, uint64_t db, int scale_d) {
  asm volatile("{\n.reg .pred p;\nsetp.ne.b32 p, %133, 0;\n"
    "wgmma.mma_async.sync.aligned.m64n256k16.f32.bf16.bf16 {%0, %1, %2, %3, %4, %5, %6, %7, %8, %9, %10, %11, %12, %13, %14, %15, %16, %17, %18, %19, %20, %21, %22, %23, %24, %25, %26, %27, %28, %29, %30, %31, %32, %33, %34, %35, %36, %37, %38, %39, %40, %41, %42, %43, %44, %45, %46, %47, %48, %49, %50, %51, %52, %53, %54, %55, %56, %57, %58, %59, %60, %61, %62, %63, %64, %65, %66, %67, %68, %69, %70, %71, %72, %73, %74, %75, %76, %77, %78, %79, %80, %81, %82, %83, %84, %85, %86, %87, %88, %89, %90, %91, %92, %93, %94, %95, %96, %97, %98, %99, %100, %101, %102, %103, %104, %105, %106, %107, %108, %109, %110, %111, %112, %113, %114, %115, %116, %117, %118, %119, %120, %121, %122, %123, %124, %125, %126, %127}, {%128, %129, %130, %131}, %132, p, 1, 1, 1;\n}\n"
    : "+f"(d[0]), "+f"(d[1]), "+f"(d[2]), "+f"(d[3]), "+f"(d[4]), "+f"(d[5]), "+f"(d[6]), "+f"(d[7]), "+f"(d[8]), "+f"(d[9]), "+f"(d[10]), "+f"(d[11]), "+f"(d[12]), "+f"(d[13]), "+f"(d[14]), "+f"(d[15]), "+f"(d[16]), "+f"(d[17]), "+f"(d[18]), "+f"(d[19]), "+f"(d[20]), "+f"(d[21]), "+f"(d[22]), "+f"(d[23]), "+f"(d[24]), "+f"(d[25]), "+f"(d[26]), "+f"(d[27]), "+f"(d[28]), "+f"(d[29]), "+f"(d[30]), "+f"(d[31]), "+f"(d[32]), "+f"(d[33]), "+f"(d[34]), "+f"(d[35]), "+f"(d[36]), "+f"(d[37]), "+f"(d[38]), "+f"(d[39]), "+f"(d[40]), "+f"(d[41]), "+f"(d[42]), "+f"(d[43]), "+f"(d[44]), "+f"(d[45]), "+f"(d[46]), "+f"(d[47]), "+f"(d[48]), "+f"(d[49]), "+f"(d[50]), "+f"(d[51]), "+f"(d[52]), "+f"(d[53]), "+f"(d[54]), "+f"(d[55]), "+f"(d[56]), "+f"(d[57]), "+f"(d[58]), "+f"(d[59]), "+f"(d[60]), "+f"(d[61]), "+f"(d[62]), "+f"(d[63]), "+f"(e[0]), "+f"(e[1]), "+f"(e[2]), "+f"(e[3]), "+f"(e[4]), "+f"(e[5]), "+f"(e[6]), "+f"(e[7]), "+f"(e[8]), "+f"(e[9]), "+f"(e[10]), "+f"(e[11]), "+f"(e[12]), "+f"(e[13]), "+f"(e[14]), "+f"(e[15]), "+f"(e[16]), "+f"(e[17]), "+f"(e[18]), "+f"(e[19]), "+f"(e[20]), "+f"(e[21]), "+f"(e[22]), "+f"(e[23]), "+f"(e[24]), "+f"(e[25]), "+f"(e[26]), "+f"(e[27]), "+f"(e[28]), "+f"(e[29]), "+f"(e[30]), "+f"(e[31]), "+f"(e[32]), "+f"(e[33]), "+f"(e[34]), "+f"(e[35]), "+f"(e[36]), "+f"(e[37]), "+f"(e[38]), "+f"(e[39]), "+f"(e[40]), "+f"(e[41]), "+f"(e[42]), "+f"(e[43]), "+f"(e[44]), "+f"(e[45]), "+f"(e[46]), "+f"(e[47]), "+f"(e[48]), "+f"(e[49]), "+f"(e[50]), "+f"(e[51]), "+f"(e[52]), "+f"(e[53]), "+f"(e[54]), "+f"(e[55]), "+f"(e[56]), "+f"(e[57]), "+f"(e[58]), "+f"(e[59]), "+f"(e[60]), "+f"(e[61]), "+f"(e[62]), "+f"(e[63])
    : "r"(a0), "r"(a1), "r"(a2), "r"(a3), "l"(db), "r"(scale_d));
}

__device__ __forceinline__ void wgmma_rs_n128_z(float (&d)[64], uint32_t a0, uint32_t a1, uint32_t a2, uint32_t a3, uint64_t db) {
  asm volatile("{\n.reg .pred p;\nsetp.ne.b32 p, 0, 0;\n"
    "wgmma.mma_async.sync.aligned.m64n128k16.f32.bf16.bf16 {%0, %1, %2, %3, %4, %5, %6, %7, %8, %9, %10, %11, %12, %13, %14, %15, %16, %17, %18, %19, %20, %21, %22, %23, %24, %25, %26, %27, %28, %29, %30, %31, %32, %33, %34, %35, %36, %37, %38, %39, %40, %41, %42, %43, %44, %45, %46, %47, %48, %49, %50, %51, %52, %53, %54, %55, %56, %57, %58, %59, %60, %61, %62, %63}, {%64, %65, %66, %67}, %68, p, 1, 1, 0;\n}\n"
    : "=f"(d[0]), "=f"(d[1]), "=f"(d[2]), "=f"(d[3]), "=f"(d[4]), "=f"(d[5]), "=f"(d[6]), "=f"(d[7]), "=f"(d[8]), "=f"(d[9]), "=f"(d[10]), "=f"(d[11]), "=f"(d[12]), "=f"(d[13]), "=f"(d[14]), "=f"(d[15]), "=f"(d[16]), "=f"(d[17]), "=f"(d[18]), "=f"(d[19]), "=f"(d[20]), "=f"(d[21]), "=f"(d[22]), "=f"(d[23]), "=f"(d[24]), "=f"(d[25]), "=f"(d[26]), "=f"(d[27]), "=f"(d[28]), "=f"(d[29]), "=f"(d[30]), "=f"(d[31]), "=f"(d[32]), "=f"(d[33]), "=f"(d[34]), "=f"(d[35]), "=f"(d[36]), "=f"(d[37]), "=f"(d[38]), "=f"(d[39]), "=f"(d[40]), "=f"(d[41]), "=f"(d[42]), "=f"(d[43]), "=f"(d[44]), "=f"(d[45]), "=f"(d[46]), "=f"(d[47]), "=f"(d[48]), "=f"(d[49]), "=f"(d[50]), "=f"(d[51]), "=f"(d[52]), "=f"(d[53]), "=f"(d[54]), "=f"(d[55]), "=f"(d[56]), "=f"(d[57]), "=f"(d[58]), "=f"(d[59]), "=f"(d[60]), "=f"(d[61]), "=f"(d[62]), "=f"(d[63])
    : "r"(a0), "r"(a1), "r"(a2), "r"(a3), "l"(db));
}

__device__ __forceinline__ void wgmma_rs_n64_tb_z(float (&d)[32], uint32_t a0, uint32_t a1, uint32_t a2, uint32_t a3, uint64_t db) {
  asm volatile("{\n.reg .pred p;\nsetp.ne.b32 p, 0, 0;\n"
    "wgmma.mma_async.sync.aligned.m64n64k16.f32.bf16.bf16 {%0, %1, %2, %3, %4, %5, %6, %7, %8, %9, %10, %11, %12, %13, %14, %15, %16, %17, %18, %19, %20, %21, %22, %23, %24, %25, %26, %27, %28, %29, %30, %31}, {%32, %33, %34, %35}, %36, p, 1, 1, 1;\n}\n"
    : "=f"(d[0]), "=f"(d[1]), "=f"(d[2]), "=f"(d[3]), "=f"(d[4]), "=f"(d[5]), "=f"(d[6]), "=f"(d[7]), "=f"(d[8]), "=f"(d[9]), "=f"(d[10]), "=f"(d[11]), "=f"(d[12]), "=f"(d[13]), "=f"(d[14]), "=f"(d[15]), "=f"(d[16]), "=f"(d[17]), "=f"(d[18]), "=f"(d[19]), "=f"(d[20]), "=f"(d[21]), "=f"(d[22]), "=f"(d[23]), "=f"(d[24]), "=f"(d[25]), "=f"(d[26]), "=f"(d[27]), "=f"(d[28]), "=f"(d[29]), "=f"(d[30]), "=f"(d[31])
    : "r"(a0), "r"(a1), "r"(a2), "r"(a3), "l"(db));
}

__device__ __forceinline__ void wgmma_rs_n256_tb_z(float (&d)[64], float (&e)[64], uint32_t a0, uint32_t a1, uint32_t a2, uint32_t a3, uint64_t db) {
  asm volatile("{\n.reg .pred p;\nsetp.ne.b32 p, 0, 0;\n"
    "wgmma.mma_async.sync.aligned.m64n256k16.f32.bf16.bf16 {%0, %1, %2, %3, %4, %5, %6, %7, %8, %9, %10, %11, %12, %13, %14, %15, %16, %17, %18, %19, %20, %21, %22, %23, %24, %25, %26, %27, %28, %29, %30, %31, %32, %33, %34, %35, %36, %37, %38, %39, %40, %41, %42, %43, %44, %45, %46, %47, %48, %49, %50, %51, %52, %53, %54, %55, %56, %57, %58, %59, %60, %61, %62, %63, %64, %65, %66, %67, %68, %69, %70, %71, %72, %73, %74, %75, %76, %77, %78, %79, %80, %81, %82, %83, %84, %85, %86, %87, %88, %89, %90, %91, %92, %93, %94, %95, %96, %97, %98, %99, %100, %101, %102, %103, %104, %105, %106, %107, %108, %109, %110, %111, %112, %113, %114, %115, %116, %117, %118, %119, %120, %121, %122, %123, %124, %125, %126, %127}, {%128, %129, %130, %131}, %132, p, 1, 1, 1;\n}\n"
    : "=f"(d[0]), "=f"(d[1]), "=f"(d[2]), "=f"(d[3]), "=f"(d[4]), "=f"(d[5]), "=f"(d[6]), "=f"(d[7]), "=f"(d[8]), "=f"(d[9]), "=f"(d[10]), "=f"(d[11]), "=f"(d[12]), "=f"(d[13]), "=f"(d[14]), "=f"(d[15]), "=f"(d[16]), "=f"(d[17]), "=f"(d[18]), "=f"(d[19]), "=f"(d[20]), "=f"(d[21]), "=f"(d[22]), "=f"(d[23]), "=f"(d[24]), "=f"(d[25]), "=f"(d[26]), "=f"(d[27]), "=f"(d[28]), "=f"(d[29]), "=f"(d[30]), "=f"(d[31]), "=f"(d[32]), "=f"(d[33]), "=f"(d[34]), "=f"(d[35]), "=f"(d[36]), "=f"(d[37]), "=f"(d[38]), "=f"(d[39]), "=f"(d[40]), "=f"(d[41]), "=f"(d[42]), "=f"(d[43]), "=f"(d[44]), "=f"(d[45]), "=f"(d[46]), "=f"(d[47]), "=f"(d[48]), "=f"(d[49]), "=f"(d[50]), "=f"(d[51]), "=f"(d[52]), "=f"(d[53]), "=f"(d[54]), "=f"(d[55]), "=f"(d[56]), "=f"(d[57]), "=f"(d[58]), "=f"(d[59]), "=f"(d[60]), "=f"(d[61]), "=f"(d[62]), "=f"(d[63]), "=f"(e[0]), "=f"(e[1]), "=f"(e[2]), "=f"(e[3]), "=f"(e[4]), "=f"(e[5]), "=f"(e[6]), "=f"(e[7]), "=f"(e[8]), "=f"(e[9]), "=f"(e[10]), "=f"(e[11]), "=f"(e[12]), "=f"(e[13]), "=f"(e[14]), "=f"(e[15]), "=f"(e[16]), "=f"(e[17]), "=f"(e[18]), "=f"(e[19]), "=f"(e[20]), "=f"(e[21]), "=f"(e[22]), "=f"(e[23]), "=f"(e[24]), "=f"(e[25]), "=f"(e[26]), "=f"(e[27]), "=f"(e[28]), "=f"(e[29]), "=f"(e[30]), "=f"(e[31]), "=f"(e[32]), "=f"(e[33]), "=f"(e[34]), "=f"(e[35]), "=f"(e[36]), "=f"(e[37]), "=f"(e[38]), "=f"(e[39]), "=f"(e[40]), "=f"(e[41]), "=f"(e[42]), "=f"(e[43]), "=f"(e[44]), "=f"(e[45]), "=f"(e[46]), "=f"(e[47]), "=f"(e[48]), "=f"(e[49]), "=f"(e[50]), "=f"(e[51]), "=f"(e[52]), "=f"(e[53]), "=f"(e[54]), "=f"(e[55]), "=f"(e[56]), "=f"(e[57]), "=f"(e[58]), "=f"(e[59]), "=f"(e[60]), "=f"(e[61]), "=f"(e[62]), "=f"(e[63])
    : "r"(a0), "r"(a1), "r"(a2), "r"(a3), "l"(db));
}

__device__ __forceinline__ void wgmma_rs_n192_tb(float (&d)[64], float (&e)[64], uint32_t a0, uint32_t a1, uint32_t a2, uint32_t a3, uint64_t db) {
  asm volatile("{\n.reg .pred p;\nsetp.eq.b32 p, 0, 0;\n"
    "wgmma.mma_async.sync.aligned.m64n192k16.f32.bf16.bf16 {%0, %1, %2, %3, %4, %5, %6, %7, %8, %9, %10, %11, %12, %13, %14, %15, %16, %17, %18, %19, %20, %21, %22, %23, %24, %25, %26, %27, %28, %29, %30, %31, %32, %33, %34, %35, %36, %37, %38, %39, %40, %41, %42, %43, %44, %45, %46, %47, %48, %49, %50, %51, %52, %53, %54, %55, %56, %57, %58, %59, %60, %61, %62, %63, %64, %65, %66, %67, %68, %69, %70, %71, %72, %73, %74, %75, %76, %77, %78, %79, %80, %81, %82, %83, %84, %85, %86, %87, %88, %89, %90, %91, %92, %93, %94, %95}, {%96, %97, %98, %99}, %100, p, 1, 1, 1;\n}\n"
    : "+f"(d[0]), "+f"(d[1]), "+f"(d[2]), "+f"(d[3]), "+f"(d[4]), "+f"(d[5]), "+f"(d[6]), "+f"(d[7]), "+f"(d[8]), "+f"(d[9]), "+f"(d[10]), "+f"(d[11]), "+f"(d[12]), "+f"(d[13]), "+f"(d[14]), "+f"(d[15]), "+f"(d[16]), "+f"(d[17]), "+f"(d[18]), "+f"(d[19]), "+f"(d[20]), "+f"(d[21]), "+f"(d[22]), "+f"(d[23]), "+f"(d[24]), "+f"(d[25]), "+f"(d[26]), "+f"(d[27]), "+f"(d[28]), "+f"(d[29]), "+f"(d[30]), "+f"(d[31]), "+f"(d[32]), "+f"(d[33]), "+f"(d[34]), "+f"(d[35]), "+f"(d[36]), "+f"(d[37]), "+f"(d[38]), "+f"(d[39]), "+f"(d[40]), "+f"(d[41]), "+f"(d[42]), "+f"(d[43]), "+f"(d[44]), "+f"(d[45]), "+f"(d[46]), "+f"(d[47]), "+f"(d[48]), "+f"(d[49]), "+f"(d[50]), "+f"(d[51]), "+f"(d[52]), "+f"(d[53]), "+f"(d[54]), "+f"(d[55]), "+f"(d[56]), "+f"(d[57]), "+f"(d[58]), "+f"(d[59]), "+f"(d[60]), "+f"(d[61]), "+f"(d[62]), "+f"(d[63]), "+f"(e[0]), "+f"(e[1]), "+f"(e[2]), "+f"(e[3]), "+f"(e[4]), "+f"(e[5]), "+f"(e[6]), "+f"(e[7]), "+f"(e[8]), "+f"(e[9]), "+f"(e[10]), "+f"(e[11]), "+f"(e[12]), "+f"(e[13]), "+f"(e[14]), "+f"(e[15]), "+f"(e[16]), "+f"(e[17]), "+f"(e[18]), "+f"(e[19]), "+f"(e[20]), "+f"(e[21]), "+f"(e[22]), "+f"(e[23]), "+f"(e[24]), "+f"(e[25]), "+f"(e[26]), "+f"(e[27]), "+f"(e[28]), "+f"(e[29]), "+f"(e[30]), "+f"(e[31])
    : "r"(a0), "r"(a1), "r"(a2), "r"(a3), "l"(db));
}

__device__ __forceinline__ void wgmma_rs_n192_tb_z(float (&d)[64], float (&e)[64], uint32_t a0, uint32_t a1, uint32_t a2, uint32_t a3, uint64_t db) {
  asm volatile("{\n.reg .pred p;\nsetp.ne.b32 p, 0, 0;\n"
    "wgmma.mma_async.sync.aligned.m64n192k16.f32.bf16.bf16 {%0, %1, %2, %3, %4, %5, %6, %7, %8, %9, %10, %11, %12, %13, %14, %15, %16, %17, %18, %19, %20, %21, %22, %23, %24, %25, %26, %27, %28, %29, %30, %31, %32, %33, %34, %35, %36, %37, %38, %39, %40, %41, %42, %43, %44, %45, %46, %47, %48, %49, %50, %51, %52, %53, %54, %55, %56, %57, %58, %59, %60, %61, %62, %63, %64, %65, %66, %67, %68, %69, %70, %71, %72, %73, %74, %75, %76, %77, %78, %79, %80, %81, %82, %83, %84, %85, %86, %87, %88, %89, %90, %91, %92, %93, %94, %95}, {%96, %97, %98, %99}, %100, p, 1, 1, 1;\n}\n"
    : "=f"(d[0]), "=f"(d[1]), "=f"(d[2]), "=f"(d[3]), "=f"(d[4]), "=f"(d[5]), "=f"(d[6]), "=f"(d[7]), "=f"(d[8]), "=f"(d[9]), "=f"(d[10]), "=f"(d[11]), "=f"(d[12]), "=f"(d[13]), "=f"(d[14]), "=f"(d[15]), "=f"(d[16]), "=f"(d[17]), "=f"(d[18]), "=f"(d[19]), "=f"(d[20]), "=f"(d[21]), "=f"(d[22]), "=f"(d[23]), "=f"(d[24]), "=f"(d[25]), "=f"(d[26]), "=f"(d[27]), "=f"(d[28]), "=f"(d[29]), "=f"(d[30]), "=f"(d[31]), "=f"(d[32]), "=f"(d[33]), "=f"(d[34]), "=f"(d[35]), "=f"(d[36]), "=f"(d[37]), "=f"(d[38]), "=f"(d[39]), "=f"(d[40]), "=f"(d[41]), "=f"(d[42]), "=f"(d[43]), "=f"(d[44]), "=f"(d[45]), "=f"(d[46]), "=f"(d[47]), "=f"(d[48]), "=f"(d[49]), "=f"(d[50]), "=f"(d[51]), "=f"(d[52]), "=f"(d[53]), "=f"(d[54]), "=f"(d[55]), "=f"(d[56]), "=f"(d[57]), "=f"(d[58]), "=f"(d[59]), "=f"(d[60]), "=f"(d[61]), "=f"(d[62]), "=f"(d[63]), "=f"(e[0]), "=f"(e[1]), "=f"(e[2]), "=f"(e[3]), "=f"(e[4]), "=f"(e[5]), "=f"(e[6]), "=f"(e[7]), "=f"(e[8]), "=f"(e[9]), "=f"(e[10]), "=f"(e[11]), "=f"(e[12]), "=f"(e[13]), "=f"(e[14]), "=f"(e[15]), "=f"(e[16]), "=f"(e[17]), "=f"(e[18]), "=f"(e[19]), "=f"(e[20]), "=f"(e[21]), "=f"(e[22]), "=f"(e[23]), "=f"(e[24]), "=f"(e[25]), "=f"(e[26]), "=f"(e[27]), "=f"(e[28]), "=f"(e[29]), "=f"(e[30]), "=f"(e[31])
    : "r"(a0), "r"(a1), "r"(a2), "r"(a3), "l"(db));
}

struct Maps {
  CUtensorMap x[2], k[2], v[2], wq[2], wo[2];
  const char *px[2], *pwo[2];
};

__device__ __forceinline__ void poll_tiles(int tile, const unsigned (&target)[3], uint32_t ready) {
#pragma unroll
  for (int pn = 0; pn < 3; pn++) {
    const unsigned* c = &g_cnt[(tile * 4 + pn) * 32];
    for (uint32_t it = 0; it < WAIT_LIMIT; ++it) {
      unsigned v;
      asm volatile("ld.acquire.gpu.global.u32 %0, [%1];" : "=r"(v) : "l"(c) : "memory");
      if ((int)(v - target[pn]) >= 0) break;
    }
    mbar_arrive(ready + pn * 8);
  }
}
__device__ __forceinline__ void read_targets(int tile, unsigned (&target)[3]) {
#pragma unroll
  for (int pn = 0; pn < 3; pn++) {
    unsigned v;
    asm volatile("ld.relaxed.gpu.global.u32 %0, [%1];" : "=r"(v) : "l"(&g_cnt[(tile * 4 + pn) * 32]) : "memory");
    target[pn] = (v / 16u + 1u) * 16u;
  }
}

__global__ void __cluster_dims__(2, 1, 1) __launch_bounds__(384, 1)
fused_gqa_kernel(const __grid_constant__ Maps maps, __nv_bfloat16* __restrict__ out) {
  extern __shared__ __align__(1024) unsigned char smem[];
  const uint32_t sbase = smem_u32(smem);
  const uint32_t full0 = sbase + BAR_OFF;
  const uint32_t empty0 = full0 + N_ITEMS * 8;
  const uint32_t ready0 = empty0 + N_ITEMS * 8;
  const uint32_t pub0 = ready0 + 6 * 8;

  const int tid = threadIdx.x;
  const int wg = tid >> 7;
  const int bid = blockIdx.x;
  const int bp = bid & 3;
  const int h = (bid >> 2) & 15;
  const int p = bid >> 6;

  if (tid == 0) {
#pragma unroll
    for (int i = 0; i < 5; i++) mbar_init(full0 + (WQ0 + i) * 8, 1);
#pragma unroll
    for (int i = 0; i < 4; i++) mbar_init(full0 + (X0 + i) * 8, 1);
    asm volatile("fence.mbarrier_init.release.cluster;" ::: "memory");
#pragma unroll
    for (int kc = 0; kc < 5; kc++) {
      if (kc < 4) {
        mbar_expect_tx(full0 + (X0 + kc) * 8, 16384);
        tma_load3(sbase + x_off(kc), &maps.x[p], 0, bp * 128, kc, full0 + (X0 + kc) * 8);
      }
      mbar_expect_tx(full0 + (WQ0 + kc) * 8, T32);
      tma_load3(sbase + wq_off(kc), &maps.wq[p], 0, kc * 64, h * 4, full0 + (WQ0 + kc) * 8);
    }
    TR(0, 56);
  } else if (tid >= 64 && tid < 96) {
    const char* base = maps.px[p] + (size_t)(bp * 128 + h * 8) * 1152;
#pragma unroll
    for (int i = 0; i < 3; i++)
      if ((tid & 31) + i * 32 < 72) l2_prefetch(base + ((tid & 31) + i * 32) * 128);
  } else if (tid == 32) {
    prefetch_tmap(&maps.k[p]);
    prefetch_tmap(&maps.v[p]);
    prefetch_tmap(&maps.wo[p]);
  } else if (tid >= 128) {
    const int i = tid - 128;
    if (i < N_ITEMS) {
      if (!(i < 5 || (i >= X0 && i < X0 + 4))) mbar_init(full0 + i * 8, 1);
    } else if (i >= 64 && i < 64 + N_ITEMS) {
      mbar_init(empty0 + (i - 64) * 8, 8);
    } else if (i >= 128 && i < 128 + 6) {
      mbar_init(ready0 + (i - 128) * 8, 1);
    } else if (i >= 160 && i < 160 + 6) {
      mbar_init(pub0 + (i - 160) * 8, 4);
    }
    asm volatile("fence.mbarrier_init.release.cluster;" ::: "memory");
  }
  __syncthreads();
  if (tid == 0) TR(0, 57);

  if (wg == 0) {
    asm volatile("setmaxnreg.dec.sync.aligned.u32 24;");
    if (tid == 0) {
      const int kvrow = (2 * bp * 16 + h) * kSK;
      auto load_kv = [&](int n) {
        if (n >= KV_INFLIGHT) mbar_wait(full0 + (KV0 + n - KV_INFLIGHT) * 8);
        const uint32_t fb = full0 + (KV0 + n) * 8;
        TR(0, KV0 + n);
        mbar_expect_tx(fb, T32);
        tma_load3(sbase + kv_off(n), (n & 1) ? &maps.v[p] : &maps.k[p], 0, kvrow + (n >> 3) * 16 * kSK + ((n & 7) >> 1) * 128, 0, fb);
      };
#pragma unroll 1
      for (int c = 0; c < 9; c++) {
        mbar_wait(empty0 + (X0 + c) * 8);
        if (c < 5) {
          mbar_expect_tx(full0 + (X0 + c + 4) * 8, 16384);
          tma_load3(sbase + x_off(c + 4), &maps.x[p], 0, bp * 128, c + 4, full0 + (X0 + c + 4) * 8);
        }
        if (c < 4) {
          TR(0, WQ0 + c + 5);
          mbar_expect_tx(full0 + (WQ0 + c + 5) * 8, T32);
          tma_load3(sbase + wq_off(c + 5), &maps.wq[p], 0, (c + 5) * 64, h * 4, full0 + (WQ0 + c + 5) * 8);
        } else if (c < 8) {
          load_kv(c - 4);
          if (c == 7) load_kv(4);
        } else {
          load_kv(5);
        }
      }
#pragma unroll 1
      for (int n = 6; n < N_KV; n++) {
        mbar_wait(empty0 + (KV0 + n - 6) * 8);
        load_kv(n);
      }
#pragma unroll 1
      for (int m = 0; m < N_WO; m++) {
        mbar_wait(empty0 + (WO0 + m - 6) * 8);
        const uint32_t fb = full0 + (WO0 + m) * 8;
        TR(0, WO0 + m);
        mbar_expect_tx(fb, WO_BYTES);
        tma_load3(sbase + wo_off(m), &maps.wo[p], 0, h * 256 + (m & 3) * 64, (m >> 2) * 3, fb);
      }
    } else if (tid == 96 || tid == 112) {
      const int w = (tid >> 4) & 1;
      unsigned target[3];
      read_targets(p * 8 + 2 * bp + w, target);
      mbar_wait(pub0 + w * 24);
      poll_tiles(p * 8 + 2 * bp + w, target, ready0 + w * 24);
    } else if (tid >= 32 && tid < 96) {
      const int w = (tid >> 5) - 1;
      if (tid & 31) return;
      const int tile = p * 8 + 2 * bp + w;
#pragma unroll 1
      for (int e = 0; e < 3; e++) {
        mbar_wait(pub0 + (w * 3 + e) * 8);
        __threadfence();
        asm volatile("red.relaxed.gpu.global.add.u32 [%0], 1;" ::"l"(&g_cnt[(tile * 4 + e) * 32]) : "memory");
      }
    }
  } else {
    asm volatile("setmaxnreg.inc.sync.aligned.u32 240;");
    const int w = wg - 1;
    const int t128 = tid & 127;
    const int lane = tid & 31;

    auto release = [&](int item) {
      __syncwarp();
      if (lane == 0) mbar_arrive(empty0 + item * 8);
    };

    TRC(0);
    const float cs = 0.08838834764831845f * 1.4426950408889634f;
    float s[64], o[64];
#pragma unroll
    for (int i = 0; i < 64; i++) s[i] = 0.f, o[i] = 0.f;
    uint32_t qf[32];
    uint4* park = reinterpret_cast<uint4*>(smem + PARK_OFF) + w * 1024 + t128;
    {
#pragma unroll 1
      for (int kc = 0; kc < 9; kc++) {
        mbar_wait(full0 + (X0 + kc) * 8);
        mbar_wait(full0 + (WQ0 + kc) * 8);
        if (kc == 0) TRC(1);
        const uint64_t da = make_desc(sbase + x_off(kc), 16, 1024);
        const uint64_t db = make_desc(sbase + wq_off(kc) + w * 16384, 8192, 1024);
        wg_fence();
#pragma unroll
        for (int ks = 0; ks < 4; ks++) {
          wgmma_ss_n128_tb(s, da + ks * 2, db + ks * 128, (kc | ks) != 0);
          wgmma_ss_n128_tb(o, da + 512 + ks * 2, db + ks * 128, (kc | ks) != 0);
        }
        wg_commit();
        wg_wait<0>();
        release(X0 + kc);
      }
      fence_regs(s);
      fence_regs(o);
#pragma unroll
      for (int i = 0; i < 32; i++) qf[i] = pack_bf16(s[2 * i], s[2 * i + 1]);
      named_bar(1, 256);
#pragma unroll
      for (int i = 0; i < 8; i++) park[i * 128] = pack8(o, i);
      TRC(2);
    }
#pragma unroll 1
    for (int bb = 0; bb < 2; bb++) {
#pragma unroll
      for (int i = 0; i < 64; i++) o[i] = 0.f;
      float m0 = -INFINITY, m1 = -INFINITY, l0 = 0.f, l1 = 0.f;
#pragma unroll 1
      for (int t = 0; t < 4; t++) {
        const int n = bb * 8 + t * 2;
        {
          const uint32_t base = sbase + kv_off(n);
          mbar_wait(full0 + (KV0 + n) * 8);
          if (n == 0 && w == 1) named_bar(4, 256);
          const uint64_t db = make_desc(base, 16, 1024);
          wg_fence();
          wgmma_rs_n128_z(s, qf[0], qf[1], qf[2], qf[3], db);
#pragma unroll
          for (int ks = 1; ks < 8; ks++)
            wgmma_rs_n128(s, qf[4 * ks], qf[4 * ks + 1], qf[4 * ks + 2], qf[4 * ks + 3], db + (ks >> 2) * 1024 + (ks & 3) * 2, 1);
          wg_commit();
          wg_wait<0>();
          fence_regs(s);
          if (n == 0 && w == 0) named_arrive(4, 256);
          release(KV0 + n);
        }
        float mx0 = s[0], mx1 = s[2];
#pragma unroll
        for (int g = 0; g < 16; g++) {
          mx0 = fmaxf(mx0, fmaxf(s[4 * g], s[4 * g + 1]));
          mx1 = fmaxf(mx1, fmaxf(s[4 * g + 2], s[4 * g + 3]));
        }
        mx0 = fmaxf(mx0, __shfl_xor_sync(0xffffffffu, mx0, 1));
        mx0 = fmaxf(mx0, __shfl_xor_sync(0xffffffffu, mx0, 2));
        mx1 = fmaxf(mx1, __shfl_xor_sync(0xffffffffu, mx1, 1));
        mx1 = fmaxf(mx1, __shfl_xor_sync(0xffffffffu, mx1, 2));
        const float mn0 = fmaxf(m0, mx0), mn1 = fmaxf(m1, mx1);
        const float a0 = ex2((m0 - mn0) * cs), a1 = ex2((m1 - mn1) * cs);
        m0 = mn0;
        m1 = mn1;
        const float ms0 = mn0 * cs, ms1 = mn1 * cs;
        float rs0 = 0.f, rs1 = 0.f;
        uint32_t pf[32];
#pragma unroll
        for (int g = 0; g < 16; g++) {
          const float p0 = ex2(fmaf(s[4 * g], cs, -ms0));
          const float p1 = ex2(fmaf(s[4 * g + 1], cs, -ms0));
          const float p2 = ex2(fmaf(s[4 * g + 2], cs, -ms1));
          const float p3 = ex2(fmaf(s[4 * g + 3], cs, -ms1));
          rs0 += p0 + p1;
          rs1 += p2 + p3;
          pf[2 * g] = pack_bf16(p0, p1);
          pf[2 * g + 1] = pack_bf16(p2, p3);
        }
        l0 = l0 * a0 + rs0;
        l1 = l1 * a1 + rs1;
#pragma unroll
        for (int g = 0; g < 16; g++) {
          o[4 * g] *= a0;
          o[4 * g + 1] *= a0;
          o[4 * g + 2] *= a1;
          o[4 * g + 3] *= a1;
        }
        {
          const uint32_t base = sbase + kv_off(n + 1);
          mbar_wait(full0 + (KV0 + n + 1) * 8);
          const uint64_t db = make_desc(base, 16384, 1024);
          wg_fence();
#pragma unroll
          for (int ks = 0; ks < 8; ks++)
            wgmma_rs_n128_tb(o, pf[4 * ks], pf[4 * ks + 1], pf[4 * ks + 2], pf[4 * ks + 3], db + ks * 128, 1);
          wg_commit();
          wg_wait<0>();
          fence_regs(o);
          if (n + 1 < 15) release(KV0 + n + 1);
          TRC(3 + bb * 5 + t);
        }
      }
      l0 += __shfl_xor_sync(0xffffffffu, l0, 1);
      l0 += __shfl_xor_sync(0xffffffffu, l0, 2);
      l1 += __shfl_xor_sync(0xffffffffu, l1, 1);
      l1 += __shfl_xor_sync(0xffffffffu, l1, 2);
      const float i0 = 1.f / l0, i1 = 1.f / l1;
      uint4* dst = park;
      if (bb == 0) {
#pragma unroll
        for (int i = 0; i < 8; i++) {
          const uint4 v = park[i * 128];
          qf[4 * i] = v.x;
          qf[4 * i + 1] = v.y;
          qf[4 * i + 2] = v.z;
          qf[4 * i + 3] = v.w;
        }
      } else {
        named_bar(1, 256);
        dst = reinterpret_cast<uint4*>(smem + kv_off(15)) + w * 1024 + t128;
      }
#pragma unroll
      for (int i = 0; i < 8; i++)
        dst[i * 128] = make_uint4(pack_bf16(o[8 * i] * i0, o[8 * i + 1] * i0), pack_bf16(o[8 * i + 2] * i1, o[8 * i + 3] * i1),
                                  pack_bf16(o[8 * i + 4] * i0, o[8 * i + 5] * i0), pack_bf16(o[8 * i + 6] * i1, o[8 * i + 7] * i1));
    }
    uint32_t af[64];
    {
      named_bar(1, 256);
      const uint4* src = reinterpret_cast<const uint4*>(smem + (w == 0 ? PARK_OFF : kv_off(15))) + t128;
#pragma unroll
      for (int i = 0; i < 16; i++) {
        const uint4 v = src[i * 128];
        af[4 * i] = v.x;
        af[4 * i + 1] = v.y;
        af[4 * i + 2] = v.z;
        af[4 * i + 3] = v.w;
      }
      asm volatile("fence.proxy.async.shared::cta;" ::: "memory");
      release(KV0 + 15);
    }
    TRC(12);
    if (w == 1) named_bar(4, 256);
    const int tile = p * 8 + 2 * bp + w;
    uint4* part = g_part + (size_t)(tile * 16 + h) * 36 * 128 + t128;
#pragma unroll
    for (int pn = 0; pn < 3; pn++) {
#pragma unroll
      for (int kc = 0; kc < 4; kc++) {
        const int m = pn * 4 + kc;
        mbar_wait(full0 + (WO0 + m) * 8);
        const uint64_t db = make_desc(sbase + wo_off(m), 8192, 1024);
        wg_fence();
#pragma unroll
        for (int ks = 0; ks < 4; ks++) {
          const int a = (kc * 4 + ks) * 4;
          if ((kc | ks) == 0) wgmma_rs_n192_tb_z(s, o, af[a], af[a + 1], af[a + 2], af[a + 3], db);
          else wgmma_rs_n192_tb(s, o, af[a], af[a + 1], af[a + 2], af[a + 3], db + ks * 128);
        }
        wg_commit();
        if (m == 1 && w == 0) named_arrive(4, 256);
        if (kc > 0) {
          wg_wait<1>();
          if (m - 1 < 6) release(WO0 + m - 1);
        }
      }
      wg_wait<0>();
      fence_regs(s);
      fence_regs32(o);
      if (pn == 0) release(WO0 + 3);
      TRC(13 + pn * 2);
#pragma unroll
      for (int i = 0; i < 8; i++) __stcg(part + (pn * 12 + i) * 128, pack8(s, i));
#pragma unroll
      for (int i = 0; i < 4; i++) __stcg(part + (pn * 12 + 8 + i) * 128, pack8(o, i));
      __syncwarp();
      if (lane == 0) mbar_arrive(pub0 + (w * 3 + pn) * 8);
      TRC(14 + pn * 2);
    }
    if (t128 < 96) {
      const int u = h * 96 + t128;
      const int slot = u >> 7, thr = u & 127;
      const int row0 = (thr >> 5) * 16 + ((thr & 31) >> 2);
      __nv_bfloat16* orow = out + (size_t)((2 * bp + w) * 64 + row0) * 1152 + p * 576 + slot * 16 + (thr & 3) * 2;
      const uint4* pr = g_part + (size_t)(tile * 16) * 36 * 128 + slot * 128 + thr;
      uint4 v[3][16];
#pragma unroll
      for (int pn = 0; pn < 3; pn++) {
        mbar_wait(ready0 + (w * 3 + pn) * 8);
        TRC(19 + pn);
#pragma unroll
        for (int c = 0; c < 16; c++) v[pn][c] = __ldcg(pr + (size_t)(c * 36 + pn * 12) * 128);
      }
#pragma unroll
      for (int pn = 0; pn < 3; pn++) {
        float a[8];
#pragma unroll
        for (int e = 0; e < 8; e++) a[e] = 0.f;
#pragma unroll
        for (int c = 0; c < 16; c++) {
          a[0] += bf_lo(v[pn][c].x);
          a[1] += bf_hi(v[pn][c].x);
          a[2] += bf_lo(v[pn][c].y);
          a[3] += bf_hi(v[pn][c].y);
          a[4] += bf_lo(v[pn][c].z);
          a[5] += bf_hi(v[pn][c].z);
          a[6] += bf_lo(v[pn][c].w);
          a[7] += bf_hi(v[pn][c].w);
        }
        __nv_bfloat16* op = orow + pn * 192;
        *reinterpret_cast<uint32_t*>(op) = pack_bf16(a[0], a[1]);
        *reinterpret_cast<uint32_t*>(op + 8 * 1152) = pack_bf16(a[2], a[3]);
        *reinterpret_cast<uint32_t*>(op + 8) = pack_bf16(a[4], a[5]);
        *reinterpret_cast<uint32_t*>(op + 8 * 1152 + 8) = pack_bf16(a[6], a[7]);
      }
    }
    TRC(22);
  }
}

typedef CUresult (*EncodeFn)(CUtensorMap*, CUtensorMapDataType, cuuint32_t, void*, const cuuint64_t*, const cuuint64_t*,
                             const cuuint32_t*, const cuuint32_t*, CUtensorMapInterleave, CUtensorMapSwizzle,
                             CUtensorMapL2promotion, CUtensorMapFloatOOBfill);

void encode3d(EncodeFn fn, CUtensorMap* m, void* ptr, uint64_t cols, uint64_t rows, uint32_t box_rows, uint32_t box_chunks) {
  cuuint64_t dims[3] = {64, rows, cols / 64};
  cuuint64_t strides[2] = {cols * 2, 128};
  cuuint32_t box[3] = {64, box_rows, box_chunks};
  cuuint32_t es[3] = {1, 1, 1};
  fn(m, CU_TENSOR_MAP_DATA_TYPE_BFLOAT16, 3, ptr, dims, strides, box, es, CU_TENSOR_MAP_INTERLEAVE_NONE,
     CU_TENSOR_MAP_SWIZZLE_128B, CU_TENSOR_MAP_L2_PROMOTION_L2_256B, CU_TENSOR_MAP_FLOAT_OOB_FILL_NONE);
}

}

extern "C" void kernel_launch(void* const* d_in, const int* in_sizes, int n_in, void* d_out, int out_size) {
  static EncodeFn fn = nullptr;
  if (!fn) {
    void* f = nullptr;
    cudaDriverEntryPointQueryResult st;
    cudaGetDriverEntryPoint("cuTensorMapEncodeTiled", &f, cudaEnableDefault, &st);
    fn = (EncodeFn)f;
    cudaFuncSetAttribute(fused_gqa_kernel, cudaFuncAttributeMaxDynamicSharedMemorySize, SMEM_BYTES);
  }
  Maps maps;
  for (int p = 0; p < 2; p++) {
    encode3d(fn, &maps.x[p], d_in[p * 5 + 0], kD, 512, 128, 1);
    encode3d(fn, &maps.k[p], d_in[p * 5 + 1], kDH, 8 * 16 * kSK, 128, 2);
    encode3d(fn, &maps.v[p], d_in[p * 5 + 2], kDH, 8 * 16 * kSK, 128, 2);
    encode3d(fn, &maps.wq[p], d_in[p * 5 + 3], kHQD, kD, 64, 4);
    encode3d(fn, &maps.wo[p], d_in[p * 5 + 4], kD, kHQD, 64, 3);
    maps.px[p] = (const char*)d_in[p * 5 + 0];
    maps.pwo[p] = (const char*)d_in[p * 5 + 4];
  }
  fused_gqa_kernel<<<128, 384, SMEM_BYTES>>>(maps, (__nv_bfloat16*)d_out);
}
```

```cpp
#include <cuda_runtime.h>
#include <cuda_bf16.h>
#include <cuda.h>
#include <stdint.h>

namespace {

constexpr int kD = 576, kHQD = 4096, kSK = 512, kDH = 128;

constexpr int N_WQ = 9, N_X = 9, N_KV = 16, N_WO = 12;
constexpr int N_ITEMS = N_WQ + N_X + N_KV + N_WO;
constexpr int T32 = 32 * 1024;
constexpr int WO_BYTES = 24 * 1024;
constexpr int PARK_OFF = 192 * 1024;
constexpr int BAR_OFF = 224 * 1024;
constexpr int SMEM_BYTES = BAR_OFF + 2 * N_ITEMS * 8 + 256;
constexpr int WQ0 = 0, X0 = N_WQ, KV0 = X0 + N_X, WO0 = KV0 + N_KV;
#define WO_PF_AT 13
#define KV_INFLIGHT 2

__device__ __forceinline__ int wq_off(int kc) { return (kc < 5 ? kc : kc - 5) * T32; }
__device__ __forceinline__ int x_off(int kc) { return ((kc & 2) ? 5 * T32 : PARK_OFF) + (kc & 1) * 16384; }
__device__ __forceinline__ int ring_off(int pos) { return (int)((0x352104u >> ((pos % 6) * 4)) & 15u) * T32; }
__device__ __forceinline__ int kv_off(int n) { return ring_off(n); }
__device__ __forceinline__ int wo_off(int m) { return ring_off(N_KV + m); }

__device__ uint4 g_part[16 * 16 * 48 * 128];
__device__ unsigned int g_cnt[16 * 32];

#define TR(role, ev)
#define TRC(ev)
constexpr uint32_t WAIT_CYCLES = 1u << 20;
constexpr uint32_t WAIT_LIMIT = 1u << 12;
__device__ __forceinline__ uint32_t smem_u32(const void* p) { return (uint32_t)__cvta_generic_to_shared(p); }
__device__ __forceinline__ void mbar_init(uint32_t bar, uint32_t cnt) {
  asm volatile("mbarrier.init.shared::cta.b64 [%0], %1;" ::"r"(bar), "r"(cnt) : "memory");
}
__device__ __forceinline__ void mbar_expect_tx(uint32_t bar, uint32_t bytes) {
  asm volatile("mbarrier.arrive.expect_tx.shared::cta.b64 _, [%0], %1;" ::"r"(bar), "r"(bytes) : "memory");
}
__device__ __forceinline__ void mbar_arrive(uint32_t bar) {
  asm volatile("mbarrier.arrive.shared::cta.b64 _, [%0];" ::"r"(bar) : "memory");
}
__device__ __forceinline__ bool mbar_try(uint32_t bar, uint32_t parity) {
  uint32_t ok;
  asm volatile(
      "{\n.reg .pred p;\nmbarrier.try_wait.parity.shared::cta.b64 p, [%1], %2;\nselp.u32 %0, 1, 0, p;\n}\n"
      : "=r"(ok)
      : "r"(bar), "r"(parity)
      : "memory");
  return ok != 0;
}
__device__ __forceinline__ void mbar_wait(uint32_t bar) {
  if (mbar_try(bar, 0)) return;
  const uint32_t t0 = (uint32_t)clock();
  while (!mbar_try(bar, 0))
    if ((uint32_t)clock() - t0 > WAIT_CYCLES) break;
}
__device__ __forceinline__ void tma_load3(uint32_t dst, const CUtensorMap* tm, int c0, int c1, int c2, uint32_t bar) {
  asm volatile(
      "cp.async.bulk.tensor.3d.shared::cluster.global.mbarrier::complete_tx::bytes [%0], [%1, {%3, %4, %5}], [%2];" ::"r"(dst),
      "l"(tm), "r"(bar), "r"(c0), "r"(c1), "r"(c2)
      : "memory");
}
__device__ __forceinline__ void l2_prefetch(const void* p) { asm volatile("prefetch.global.L2 [%0];" ::"l"(p) : "memory"); }
__device__ __forceinline__ void prefetch_tmap(const CUtensorMap* tm) {
  asm volatile("prefetch.tensormap [%0];" ::"l"(tm) : "memory");
}
__device__ __forceinline__ void named_bar(int id, int n) { asm volatile("bar.sync %0, %1;" ::"r"(id), "r"(n) : "memory"); }
__device__ __forceinline__ void named_arrive(int id, int n) { asm volatile("bar.arrive %0, %1;" ::"r"(id), "r"(n) : "memory"); }
__device__ __forceinline__ void wg_fence() { asm volatile("wgmma.fence.sync.aligned;" ::: "memory"); }
__device__ __forceinline__ void wg_commit() { asm volatile("wgmma.commit_group.sync.aligned;" ::: "memory"); }
template <int N>
__device__ __forceinline__ void wg_wait() { asm volatile("wgmma.wait_group.sync.aligned %0;" ::"n"(N) : "memory"); }
template <int N>
__device__ __forceinline__ void fence_regs(float (&d)[N]) {
#pragma unroll
  for (int i = 0; i < N; i++) asm volatile("" : "+f"(d[i])::"memory");
}
__device__ __forceinline__ void fence_regs32(float (&d)[64]) {
#pragma unroll
  for (int i = 0; i < 32; i++) asm volatile("" : "+f"(d[i])::"memory");
}
__device__ __forceinline__ uint64_t make_desc(uint32_t addr, uint32_t lbo, uint32_t sbo) {
  return (uint64_t)((addr & 0x3FFFF) >> 4) | ((uint64_t)(lbo >> 4) << 16) | ((uint64_t)(sbo >> 4) << 32) | (1ull << 62);
}
__device__ __forceinline__ uint32_t pack_bf16(float lo, float hi) {
  uint32_t r;
  asm("cvt.rn.bf16x2.f32 %0, %1, %2;" : "=r"(r) : "f"(hi), "f"(lo));
  return r;
}
__device__ __forceinline__ float ex2(float x) {
  float y;
  asm("ex2.approx.ftz.f32 %0, %1;" : "=f"(y) : "f"(x));
  return y;
}
__device__ __forceinline__ float bf_lo(uint32_t v) { return __uint_as_float(v << 16); }
__device__ __forceinline__ float bf_hi(uint32_t v) { return __uint_as_float(v & 0xffff0000u); }
template <int N>
__device__ __forceinline__ uint4 pack8(const float (&a)[N], int i) {
  return make_uint4(pack_bf16(a[8 * i], a[8 * i + 1]), pack_bf16(a[8 * i + 2], a[8 * i + 3]), pack_bf16(a[8 * i + 4], a[8 * i + 5]),
                    pack_bf16(a[8 * i + 6], a[8 * i + 7]));
}

__device__ __forceinline__ void wgmma_ss_n128_tb(float (&d)[64], uint64_t da, uint64_t db, int scale_d) {
  asm volatile("{\n.reg .pred p;\nsetp.ne.b32 p, %66, 0;\n"
    "wgmma.mma_async.sync.aligned.m64n128k16.f32.bf16.bf16 {%0, %1, %2, %3, %4, %5, %6, %7, %8, %9, %10, %11, %12, %13, %14, %15, %16, %17, %18, %19, %20, %21, %22, %23, %24, %25, %26, %27, %28, %29, %30, %31, %32, %33, %34, %35, %36, %37, %38, %39, %40, %41, %42, %43, %44, %45, %46, %47, %48, %49, %50, %51, %52, %53, %54, %55, %56, %57, %58, %59, %60, %61, %62, %63}, %64, %65, p, 1, 1, 0, 1;\n}\n"
    : "+f"(d[0]), "+f"(d[1]), "+f"(d[2]), "+f"(d[3]), "+f"(d[4]), "+f"(d[5]), "+f"(d[6]), "+f"(d[7]), "+f"(d[8]), "+f"(d[9]), "+f"(d[10]), "+f"(d[11]), "+f"(d[12]), "+f"(d[13]), "+f"(d[14]), "+f"(d[15]), "+f"(d[16]), "+f"(d[17]), "+f"(d[18]), "+f"(d[19]), "+f"(d[20]), "+f"(d[21]), "+f"(d[22]), "+f"(d[23]), "+f"(d[24]), "+f"(d[25]), "+f"(d[26]), "+f"(d[27]), "+f"(d[28]), "+f"(d[29]), "+f"(d[30]), "+f"(d[31]), "+f"(d[32]), "+f"(d[33]), "+f"(d[34]), "+f"(d[35]), "+f"(d[36]), "+f"(d[37]), "+f"(d[38]), "+f"(d[39]), "+f"(d[40]), "+f"(d[41]), "+f"(d[42]), "+f"(d[43]), "+f"(d[44]), "+f"(d[45]), "+f"(d[46]), "+f"(d[47]), "+f"(d[48]), "+f"(d[49]), "+f"(d[50]), "+f"(d[51]), "+f"(d[52]), "+f"(d[53]), "+f"(d[54]), "+f"(d[55]), "+f"(d[56]), "+f"(d[57]), "+f"(d[58]), "+f"(d[59]), "+f"(d[60]), "+f"(d[61]), "+f"(d[62]), "+f"(d[63])
    : "l"(da), "l"(db), "r"(scale_d));
}

__device__ __forceinline__ void wgmma_rs_n128(float (&d)[64], uint32_t a0, uint32_t a1, uint32_t a2, uint32_t a3, uint64_t db, int scale_d) {
  asm volatile("{\n.reg .pred p;\nsetp.ne.b32 p, %69, 0;\n"
    "wgmma.mma_async.sync.aligned.m64n128k16.f32.bf16.bf16 {%0, %1, %2, %3, %4, %5, %6, %7, %8, %9, %10, %11, %12, %13, %14, %15, %16, %17, %18, %19, %20, %21, %22, %23, %24, %25, %26, %27, %28, %29, %30, %31, %32, %33, %34, %35, %36, %37, %38, %39, %40, %41, %42, %43, %44, %45, %46, %47, %48, %49, %50, %51, %52, %53, %54, %55, %56, %57, %58, %59, %60, %61, %62, %63}, {%64, %65, %66, %67}, %68, p, 1, 1, 0;\n}\n"
    : "+f"(d[0]), "+f"(d[1]), "+f"(d[2]), "+f"(d[3]), "+f"(d[4]), "+f"(d[5]), "+f"(d[6]), "+f"(d[7]), "+f"(d[8]), "+f"(d[9]), "+f"(d[10]), "+f"(d[11]), "+f"(d[12]), "+f"(d[13]), "+f"(d[14]), "+f"(d[15]), "+f"(d[16]), "+f"(d[17]), "+f"(d[18]), "+f"(d[19]), "+f"(d[20]), "+f"(d[21]), "+f"(d[22]), "+f"(d[23]), "+f"(d[24]), "+f"(d[25]), "+f"(d[26]), "+f"(d[27]), "+f"(d[28]), "+f"(d[29]), "+f"(d[30]), "+f"(d[31]), "+f"(d[32]), "+f"(d[33]), "+f"(d[34]), "+f"(d[35]), "+f"(d[36]), "+f"(d[37]), "+f"(d[38]), "+f"(d[39]), "+f"(d[40]), "+f"(d[41]), "+f"(d[42]), "+f"(d[43]), "+f"(d[44]), "+f"(d[45]), "+f"(d[46]), "+f"(d[47]), "+f"(d[48]), "+f"(d[49]), "+f"(d[50]), "+f"(d[51]), "+f"(d[52]), "+f"(d[53]), "+f"(d[54]), "+f"(d[55]), "+f"(d[56]), "+f"(d[57]), "+f"(d[58]), "+f"(d[59]), "+f"(d[60]), "+f"(d[61]), "+f"(d[62]), "+f"(d[63])
    : "r"(a0), "r"(a1), "r"(a2), "r"(a3), "l"(db), "r"(scale_d));
}

__device__ __forceinline__ void wgmma_rs_n128_tb(float (&d)[64], uint32_t a0, uint32_t a1, uint32_t a2, uint32_t a3, uint64_t db, int scale_d) {
  asm volatile("{\n.reg .pred p;\nsetp.ne.b32 p, %69, 0;\n"
    "wgmma.mma_async.sync.aligned.m64n128k16.f32.bf16.bf16 {%0, %1, %2, %3, %4, %5, %6, %7, %8, %9, %10, %11, %12, %13, %14, %15, %16, %17, %18, %19, %20, %21, %22, %23, %24, %25, %26, %27, %28, %29, %30, %31, %32, %33, %34, %35, %36, %37, %38, %39, %40, %41, %42, %43, %44, %45, %46, %47, %48, %49, %50, %51, %52, %53, %54, %55, %56, %57, %58, %59, %60, %61, %62, %63}, {%64, %65, %66, %67}, %68, p, 1, 1, 1;\n}\n"
    : "+f"(d[0]), "+f"(d[1]), "+f"(d[2]), "+f"(d[3]), "+f"(d[4]), "+f"(d[5]), "+f"(d[6]), "+f"(d[7]), "+f"(d[8]), "+f"(d[9]), "+f"(d[10]), "+f"(d[11]), "+f"(d[12]), "+f"(d[13]), "+f"(d[14]), "+f"(d[15]), "+f"(d[16]), "+f"(d[17]), "+f"(d[18]), "+f"(d[19]), "+f"(d[20]), "+f"(d[21]), "+f"(d[22]), "+f"(d[23]), "+f"(d[24]), "+f"(d[25]), "+f"(d[26]), "+f"(d[27]), "+f"(d[28]), "+f"(d[29]), "+f"(d[30]), "+f"(d[31]), "+f"(d[32]), "+f"(d[33]), "+f"(d[34]), "+f"(d[35]), "+f"(d[36]), "+f"(d[37]), "+f"(d[38]), "+f"(d[39]), "+f"(d[40]), "+f"(d[41]), "+f"(d[42]), "+f"(d[43]), "+f"(d[44]), "+f"(d[45]), "+f"(d[46]), "+f"(d[47]), "+f"(d[48]), "+f"(d[49]), "+f"(d[50]), "+f"(d[51]), "+f"(d[52]), "+f"(d[53]), "+f"(d[54]), "+f"(d[55]), "+f"(d[56]), "+f"(d[57]), "+f"(d[58]), "+f"(d[59]), "+f"(d[60]), "+f"(d[61]), "+f"(d[62]), "+f"(d[63])
    : "r"(a0), "r"(a1), "r"(a2), "r"(a3), "l"(db), "r"(scale_d));
}

__device__ __forceinline__ void wgmma_rs_n32_tb(float (&d)[16], uint32_t a0, uint32_t a1, uint32_t a2, uint32_t a3, uint64_t db, int scale_d) {
  asm volatile("{\n.reg .pred p;\nsetp.ne.b32 p, %21, 0;\n"
    "wgmma.mma_async.sync.aligned.m64n32k16.f32.bf16.bf16 {%0, %1, %2, %3, %4, %5, %6, %7, %8, %9, %10, %11, %12, %13, %14, %15}, {%16, %17, %18, %19}, %20, p, 1, 1, 1;\n}\n"
    : "+f"(d[0]), "+f"(d[1]), "+f"(d[2]), "+f"(d[3]), "+f"(d[4]), "+f"(d[5]), "+f"(d[6]), "+f"(d[7]), "+f"(d[8]), "+f"(d[9]), "+f"(d[10]), "+f"(d[11]), "+f"(d[12]), "+f"(d[13]), "+f"(d[14]), "+f"(d[15])
    : "r"(a0), "r"(a1), "r"(a2), "r"(a3), "l"(db), "r"(scale_d));
}

__device__ __forceinline__ void wgmma_rs_n64_tb(float (&d)[32], uint32_t a0, uint32_t a1, uint32_t a2, uint32_t a3, uint64_t db, int scale_d) {
  asm volatile("{\n.reg .pred p;\nsetp.ne.b32 p, %37, 0;\n"
    "wgmma.mma_async.sync.aligned.m64n64k16.f32.bf16.bf16 {%0, %1, %2, %3, %4, %5, %6, %7, %8, %9, %10, %11, %12, %13, %14, %15, %16, %17, %18, %19, %20, %21, %22, %23, %24, %25, %26, %27, %28, %29, %30, %31}, {%32, %33, %34, %35}, %36, p, 1, 1, 1;\n}\n"
    : "+f"(d[0]), "+f"(d[1]), "+f"(d[2]), "+f"(d[3]), "+f"(d[4]), "+f"(d[5]), "+f"(d[6]), "+f"(d[7]), "+f"(d[8]), "+f"(d[9]), "+f"(d[10]), "+f"(d[11]), "+f"(d[12]), "+f"(d[13]), "+f"(d[14]), "+f"(d[15]), "+f"(d[16]), "+f"(d[17]), "+f"(d[18]), "+f"(d[19]), "+f"(d[20]), "+f"(d[21]), "+f"(d[22]), "+f"(d[23]), "+f"(d[24]), "+f"(d[25]), "+f"(d[26]), "+f"(d[27]), "+f"(d[28]), "+f"(d[29]), "+f"(d[30]), "+f"(d[31])
    : "r"(a0), "r"(a1), "r"(a2), "r"(a3), "l"(db), "r"(scale_d));
}

__device__ __forceinline__ void wgmma_rs_n256_tb(float (&d)[64], float (&e)[64], uint32_t a0, uint32_t a1, uint32_t a2, uint32_t a3, uint64_t db, int scale_d) {
  asm volatile("{\n.reg .pred p;\nsetp.ne.b32 p, %133, 0;\n"
    "wgmma.mma_async.sync.aligned.m64n256k16.f32.bf16.bf16 {%0, %1, %2, %3, %4, %5, %6, %7, %8, %9, %10, %11, %12, %13, %14, %15, %16, %17, %18, %19, %20, %21, %22, %23, %24, %25, %26, %27, %28, %29, %30, %31, %32, %33, %34, %35, %36, %37, %38, %39, %40, %41, %42, %43, %44, %45, %46, %47, %48, %49, %50, %51, %52, %53, %54, %55, %56, %57, %58, %59, %60, %61, %62, %63, %64, %65, %66, %67, %68, %69, %70, %71, %72, %73, %74, %75, %76, %77, %78, %79, %80, %81, %82, %83, %84, %85, %86, %87, %88, %89, %90, %91, %92, %93, %94, %95, %96, %97, %98, %99, %100, %101, %102, %103, %104, %105, %106, %107, %108, %109, %110, %111, %112, %113, %114, %115, %116, %117, %118, %119, %120, %121, %122, %123, %124, %125, %126, %127}, {%128, %129, %130, %131}, %132, p, 1, 1, 1;\n}\n"
    : "+f"(d[0]), "+f"(d[1]), "+f"(d[2]), "+f"(d[3]), "+f"(d[4]), "+f"(d[5]), "+f"(d[6]), "+f"(d[7]), "+f"(d[8]), "+f"(d[9]), "+f"(d[10]), "+f"(d[11]), "+f"(d[12]), "+f"(d[13]), "+f"(d[14]), "+f"(d[15]), "+f"(d[16]), "+f"(d[17]), "+f"(d[18]), "+f"(d[19]), "+f"(d[20]), "+f"(d[21]), "+f"(d[22]), "+f"(d[23]), "+f"(d[24]), "+f"(d[25]), "+f"(d[26]), "+f"(d[27]), "+f"(d[28]), "+f"(d[29]), "+f"(d[30]), "+f"(d[31]), "+f"(d[32]), "+f"(d[33]), "+f"(d[34]), "+f"(d[35]), "+f"(d[36]), "+f"(d[37]), "+f"(d[38]), "+f"(d[39]), "+f"(d[40]), "+f"(d[41]), "+f"(d[42]), "+f"(d[43]), "+f"(d[44]), "+f"(d[45]), "+f"(d[46]), "+f"(d[47]), "+f"(d[48]), "+f"(d[49]), "+f"(d[50]), "+f"(d[51]), "+f"(d[52]), "+f"(d[53]), "+f"(d[54]), "+f"(d[55]), "+f"(d[56]), "+f"(d[57]), "+f"(d[58]), "+f"(d[59]), "+f"(d[60]), "+f"(d[61]), "+f"(d[62]), "+f"(d[63]), "+f"(e[0]), "+f"(e[1]), "+f"(e[2]), "+f"(e[3]), "+f"(e[4]), "+f"(e[5]), "+f"(e[6]), "+f"(e[7]), "+f"(e[8]), "+f"(e[9]), "+f"(e[10]), "+f"(e[11]), "+f"(e[12]), "+f"(e[13]), "+f"(e[14]), "+f"(e[15]), "+f"(e[16]), "+f"(e[17]), "+f"(e[18]), "+f"(e[19]), "+f"(e[20]), "+f"(e[21]), "+f"(e[22]), "+f"(e[23]), "+f"(e[24]), "+f"(e[25]), "+f"(e[26]), "+f"(e[27]), "+f"(e[28]), "+f"(e[29]), "+f"(e[30]), "+f"(e[31]), "+f"(e[32]), "+f"(e[33]), "+f"(e[34]), "+f"(e[35]), "+f"(e[36]), "+f"(e[37]), "+f"(e[38]), "+f"(e[39]), "+f"(e[40]), "+f"(e[41]), "+f"(e[42]), "+f"(e[43]), "+f"(e[44]), "+f"(e[45]), "+f"(e[46]), "+f"(e[47]), "+f"(e[48]), "+f"(e[49]), "+f"(e[50]), "+f"(e[51]), "+f"(e[52]), "+f"(e[53]), "+f"(e[54]), "+f"(e[55]), "+f"(e[56]), "+f"(e[57]), "+f"(e[58]), "+f"(e[59]), "+f"(e[60]), "+f"(e[61]), "+f"(e[62]), "+f"(e[63])
    : "r"(a0), "r"(a1), "r"(a2), "r"(a3), "l"(db), "r"(scale_d));
}

__device__ __forceinline__ void wgmma_rs_n128_z(float (&d)[64], uint32_t a0, uint32_t a1, uint32_t a2, uint32_t a3, uint64_t db) {
  asm volatile("{\n.reg .pred p;\nsetp.ne.b32 p, 0, 0;\n"
    "wgmma.mma_async.sync.aligned.m64n128k16.f32.bf16.bf16 {%0, %1, %2, %3, %4, %5, %6, %7, %8, %9, %10, %11, %12, %13, %14, %15, %16, %17, %18, %19, %20, %21, %22, %23, %24, %25, %26, %27, %28, %29, %30, %31, %32, %33, %34, %35, %36, %37, %38, %39, %40, %41, %42, %43, %44, %45, %46, %47, %48, %49, %50, %51, %52, %53, %54, %55, %56, %57, %58, %59, %60, %61, %62, %63}, {%64, %65, %66, %67}, %68, p, 1, 1, 0;\n}\n"
    : "=f"(d[0]), "=f"(d[1]), "=f"(d[2]), "=f"(d[3]), "=f"(d[4]), "=f"(d[5]), "=f"(d[6]), "=f"(d[7]), "=f"(d[8]), "=f"(d[9]), "=f"(d[10]), "=f"(d[11]), "=f"(d[12]), "=f"(d[13]), "=f"(d[14]), "=f"(d[15]), "=f"(d[16]), "=f"(d[17]), "=f"(d[18]), "=f"(d[19]), "=f"(d[20]), "=f"(d[21]), "=f"(d[22]), "=f"(d[23]), "=f"(d[24]), "=f"(d[25]), "=f"(d[26]), "=f"(d[27]), "=f"(d[28]), "=f"(d[29]), "=f"(d[30]), "=f"(d[31]), "=f"(d[32]), "=f"(d[33]), "=f"(d[34]), "=f"(d[35]), "=f"(d[36]), "=f"(d[37]), "=f"(d[38]), "=f"(d[39]), "=f"(d[40]), "=f"(d[41]), "=f"(d[42]), "=f"(d[43]), "=f"(d[44]), "=f"(d[45]), "=f"(d[46]), "=f"(d[47]), "=f"(d[48]), "=f"(d[49]), "=f"(d[50]), "=f"(d[51]), "=f"(d[52]), "=f"(d[53]), "=f"(d[54]), "=f"(d[55]), "=f"(d[56]), "=f"(d[57]), "=f"(d[58]), "=f"(d[59]), "=f"(d[60]), "=f"(d[61]), "=f"(d[62]), "=f"(d[63])
    : "r"(a0), "r"(a1), "r"(a2), "r"(a3), "l"(db));
}

__device__ __forceinline__ void wgmma_rs_n64_tb_z(float (&d)[32], uint32_t a0, uint32_t a1, uint32_t a2, uint32_t a3, uint64_t db) {
  asm volatile("{\n.reg .pred p;\nsetp.ne.b32 p, 0, 0;\n"
    "wgmma.mma_async.sync.aligned.m64n64k16.f32.bf16.bf16 {%0, %1, %2, %3, %4, %5, %6, %7, %8, %9, %10, %11, %12, %13, %14, %15, %16, %17, %18, %19, %20, %21, %22, %23, %24, %25, %26, %27, %28, %29, %30, %31}, {%32, %33, %34, %35}, %36, p, 1, 1, 1;\n}\n"
    : "=f"(d[0]), "=f"(d[1]), "=f"(d[2]), "=f"(d[3]), "=f"(d[4]), "=f"(d[5]), "=f"(d[6]), "=f"(d[7]), "=f"(d[8]), "=f"(d[9]), "=f"(d[10]), "=f"(d[11]), "=f"(d[12]), "=f"(d[13]), "=f"(d[14]), "=f"(d[15]), "=f"(d[16]), "=f"(d[17]), "=f"(d[18]), "=f"(d[19]), "=f"(d[20]), "=f"(d[21]), "=f"(d[22]), "=f"(d[23]), "=f"(d[24]), "=f"(d[25]), "=f"(d[26]), "=f"(d[27]), "=f"(d[28]), "=f"(d[29]), "=f"(d[30]), "=f"(d[31])
    : "r"(a0), "r"(a1), "r"(a2), "r"(a3), "l"(db));
}

__device__ __forceinline__ void wgmma_rs_n256_tb_z(float (&d)[64], float (&e)[64], uint32_t a0, uint32_t a1, uint32_t a2, uint32_t a3, uint64_t db) {
  asm volatile("{\n.reg .pred p;\nsetp.ne.b32 p, 0, 0;\n"
    "wgmma.mma_async.sync.aligned.m64n256k16.f32.bf16.bf16 {%0, %1, %2, %3, %4, %5, %6, %7, %8, %9, %10, %11, %12, %13, %14, %15, %16, %17, %18, %19, %20, %21, %22, %23, %24, %25, %26, %27, %28, %29, %30, %31, %32, %33, %34, %35, %36, %37, %38, %39, %40, %41, %42, %43, %44, %45, %46, %47, %48, %49, %50, %51, %52, %53, %54, %55, %56, %57, %58, %59, %60, %61, %62, %63, %64, %65, %66, %67, %68, %69, %70, %71, %72, %73, %74, %75, %76, %77, %78, %79, %80, %81, %82, %83, %84, %85, %86, %87, %88, %89, %90, %91, %92, %93, %94, %95, %96, %97, %98, %99, %100, %101, %102, %103, %104, %105, %106, %107, %108, %109, %110, %111, %112, %113, %114, %115, %116, %117, %118, %119, %120, %121, %122, %123, %124, %125, %126, %127}, {%128, %129, %130, %131}, %132, p, 1, 1, 1;\n}\n"
    : "=f"(d[0]), "=f"(d[1]), "=f"(d[2]), "=f"(d[3]), "=f"(d[4]), "=f"(d[5]), "=f"(d[6]), "=f"(d[7]), "=f"(d[8]), "=f"(d[9]), "=f"(d[10]), "=f"(d[11]), "=f"(d[12]), "=f"(d[13]), "=f"(d[14]), "=f"(d[15]), "=f"(d[16]), "=f"(d[17]), "=f"(d[18]), "=f"(d[19]), "=f"(d[20]), "=f"(d[21]), "=f"(d[22]), "=f"(d[23]), "=f"(d[24]), "=f"(d[25]), "=f"(d[26]), "=f"(d[27]), "=f"(d[28]), "=f"(d[29]), "=f"(d[30]), "=f"(d[31]), "=f"(d[32]), "=f"(d[33]), "=f"(d[34]), "=f"(d[35]), "=f"(d[36]), "=f"(d[37]), "=f"(d[38]), "=f"(d[39]), "=f"(d[40]), "=f"(d[41]), "=f"(d[42]), "=f"(d[43]), "=f"(d[44]), "=f"(d[45]), "=f"(d[46]), "=f"(d[47]), "=f"(d[48]), "=f"(d[49]), "=f"(d[50]), "=f"(d[51]), "=f"(d[52]), "=f"(d[53]), "=f"(d[54]), "=f"(d[55]), "=f"(d[56]), "=f"(d[57]), "=f"(d[58]), "=f"(d[59]), "=f"(d[60]), "=f"(d[61]), "=f"(d[62]), "=f"(d[63]), "=f"(e[0]), "=f"(e[1]), "=f"(e[2]), "=f"(e[3]), "=f"(e[4]), "=f"(e[5]), "=f"(e[6]), "=f"(e[7]), "=f"(e[8]), "=f"(e[9]), "=f"(e[10]), "=f"(e[11]), "=f"(e[12]), "=f"(e[13]), "=f"(e[14]), "=f"(e[15]), "=f"(e[16]), "=f"(e[17]), "=f"(e[18]), "=f"(e[19]), "=f"(e[20]), "=f"(e[21]), "=f"(e[22]), "=f"(e[23]), "=f"(e[24]), "=f"(e[25]), "=f"(e[26]), "=f"(e[27]), "=f"(e[28]), "=f"(e[29]), "=f"(e[30]), "=f"(e[31]), "=f"(e[32]), "=f"(e[33]), "=f"(e[34]), "=f"(e[35]), "=f"(e[36]), "=f"(e[37]), "=f"(e[38]), "=f"(e[39]), "=f"(e[40]), "=f"(e[41]), "=f"(e[42]), "=f"(e[43]), "=f"(e[44]), "=f"(e[45]), "=f"(e[46]), "=f"(e[47]), "=f"(e[48]), "=f"(e[49]), "=f"(e[50]), "=f"(e[51]), "=f"(e[52]), "=f"(e[53]), "=f"(e[54]), "=f"(e[55]), "=f"(e[56]), "=f"(e[57]), "=f"(e[58]), "=f"(e[59]), "=f"(e[60]), "=f"(e[61]), "=f"(e[62]), "=f"(e[63])
    : "r"(a0), "r"(a1), "r"(a2), "r"(a3), "l"(db));
}

__device__ __forceinline__ void wgmma_rs_n192_tb(float (&d)[64], float (&e)[64], uint32_t a0, uint32_t a1, uint32_t a2, uint32_t a3, uint64_t db) {
  asm volatile("{\n.reg .pred p;\nsetp.eq.b32 p, 0, 0;\n"
    "wgmma.mma_async.sync.aligned.m64n192k16.f32.bf16.bf16 {%0, %1, %2, %3, %4, %5, %6, %7, %8, %9, %10, %11, %12, %13, %14, %15, %16, %17, %18, %19, %20, %21, %22, %23, %24, %25, %26, %27, %28, %29, %30, %31, %32, %33, %34, %35, %36, %37, %38, %39, %40, %41, %42, %43, %44, %45, %46, %47, %48, %49, %50, %51, %52, %53, %54, %55, %56, %57, %58, %59, %60, %61, %62, %63, %64, %65, %66, %67, %68, %69, %70, %71, %72, %73, %74, %75, %76, %77, %78, %79, %80, %81, %82, %83, %84, %85, %86, %87, %88, %89, %90, %91, %92, %93, %94, %95}, {%96, %97, %98, %99}, %100, p, 1, 1, 1;\n}\n"
    : "+f"(d[0]), "+f"(d[1]), "+f"(d[2]), "+f"(d[3]), "+f"(d[4]), "+f"(d[5]), "+f"(d[6]), "+f"(d[7]), "+f"(d[8]), "+f"(d[9]), "+f"(d[10]), "+f"(d[11]), "+f"(d[12]), "+f"(d[13]), "+f"(d[14]), "+f"(d[15]), "+f"(d[16]), "+f"(d[17]), "+f"(d[18]), "+f"(d[19]), "+f"(d[20]), "+f"(d[21]), "+f"(d[22]), "+f"(d[23]), "+f"(d[24]), "+f"(d[25]), "+f"(d[26]), "+f"(d[27]), "+f"(d[28]), "+f"(d[29]), "+f"(d[30]), "+f"(d[31]), "+f"(d[32]), "+f"(d[33]), "+f"(d[34]), "+f"(d[35]), "+f"(d[36]), "+f"(d[37]), "+f"(d[38]), "+f"(d[39]), "+f"(d[40]), "+f"(d[41]), "+f"(d[42]), "+f"(d[43]), "+f"(d[44]), "+f"(d[45]), "+f"(d[46]), "+f"(d[47]), "+f"(d[48]), "+f"(d[49]), "+f"(d[50]), "+f"(d[51]), "+f"(d[52]), "+f"(d[53]), "+f"(d[54]), "+f"(d[55]), "+f"(d[56]), "+f"(d[57]), "+f"(d[58]), "+f"(d[59]), "+f"(d[60]), "+f"(d[61]), "+f"(d[62]), "+f"(d[63]), "+f"(e[0]), "+f"(e[1]), "+f"(e[2]), "+f"(e[3]), "+f"(e[4]), "+f"(e[5]), "+f"(e[6]), "+f"(e[7]), "+f"(e[8]), "+f"(e[9]), "+f"(e[10]), "+f"(e[11]), "+f"(e[12]), "+f"(e[13]), "+f"(e[14]), "+f"(e[15]), "+f"(e[16]), "+f"(e[17]), "+f"(e[18]), "+f"(e[19]), "+f"(e[20]), "+f"(e[21]), "+f"(e[22]), "+f"(e[23]), "+f"(e[24]), "+f"(e[25]), "+f"(e[26]), "+f"(e[27]), "+f"(e[28]), "+f"(e[29]), "+f"(e[30]), "+f"(e[31])
    : "r"(a0), "r"(a1), "r"(a2), "r"(a3), "l"(db));
}

__device__ __forceinline__ void wgmma_rs_n192_tb_z(float (&d)[64], float (&e)[64], uint32_t a0, uint32_t a1, uint32_t a2, uint32_t a3, uint64_t db) {
  asm volatile("{\n.reg .pred p;\nsetp.ne.b32 p, 0, 0;\n"
    "wgmma.mma_async.sync.aligned.m64n192k16.f32.bf16.bf16 {%0, %1, %2, %3, %4, %5, %6, %7, %8, %9, %10, %11, %12, %13, %14, %15, %16, %17, %18, %19, %20, %21, %22, %23, %24, %25, %26, %27, %28, %29, %30, %31, %32, %33, %34, %35, %36, %37, %38, %39, %40, %41, %42, %43, %44, %45, %46, %47, %48, %49, %50, %51, %52, %53, %54, %55, %56, %57, %58, %59, %60, %61, %62, %63, %64, %65, %66, %67, %68, %69, %70, %71, %72, %73, %74, %75, %76, %77, %78, %79, %80, %81, %82, %83, %84, %85, %86, %87, %88, %89, %90, %91, %92, %93, %94, %95}, {%96, %97, %98, %99}, %100, p, 1, 1, 1;\n}\n"
    : "=f"(d[0]), "=f"(d[1]), "=f"(d[2]), "=f"(d[3]), "=f"(d[4]), "=f"(d[5]), "=f"(d[6]), "=f"(d[7]), "=f"(d[8]), "=f"(d[9]), "=f"(d[10]), "=f"(d[11]), "=f"(d[12]), "=f"(d[13]), "=f"(d[14]), "=f"(d[15]), "=f"(d[16]), "=f"(d[17]), "=f"(d[18]), "=f"(d[19]), "=f"(d[20]), "=f"(d[21]), "=f"(d[22]), "=f"(d[23]), "=f"(d[24]), "=f"(d[25]), "=f"(d[26]), "=f"(d[27]), "=f"(d[28]), "=f"(d[29]), "=f"(d[30]), "=f"(d[31]), "=f"(d[32]), "=f"(d[33]), "=f"(d[34]), "=f"(d[35]), "=f"(d[36]), "=f"(d[37]), "=f"(d[38]), "=f"(d[39]), "=f"(d[40]), "=f"(d[41]), "=f"(d[42]), "=f"(d[43]), "=f"(d[44]), "=f"(d[45]), "=f"(d[46]), "=f"(d[47]), "=f"(d[48]), "=f"(d[49]), "=f"(d[50]), "=f"(d[51]), "=f"(d[52]), "=f"(d[53]), "=f"(d[54]), "=f"(d[55]), "=f"(d[56]), "=f"(d[57]), "=f"(d[58]), "=f"(d[59]), "=f"(d[60]), "=f"(d[61]), "=f"(d[62]), "=f"(d[63]), "=f"(e[0]), "=f"(e[1]), "=f"(e[2]), "=f"(e[3]), "=f"(e[4]), "=f"(e[5]), "=f"(e[6]), "=f"(e[7]), "=f"(e[8]), "=f"(e[9]), "=f"(e[10]), "=f"(e[11]), "=f"(e[12]), "=f"(e[13]), "=f"(e[14]), "=f"(e[15]), "=f"(e[16]), "=f"(e[17]), "=f"(e[18]), "=f"(e[19]), "=f"(e[20]), "=f"(e[21]), "=f"(e[22]), "=f"(e[23]), "=f"(e[24]), "=f"(e[25]), "=f"(e[26]), "=f"(e[27]), "=f"(e[28]), "=f"(e[29]), "=f"(e[30]), "=f"(e[31])
    : "r"(a0), "r"(a1), "r"(a2), "r"(a3), "l"(db));
}

struct Maps {
  CUtensorMap x[2], k[2], v[2], wq[2], wo[2];
  const char *px[2], *pwo[2];
};

__device__ __forceinline__ uint4 pack6(float a0, float a1, float a2, float a3, float a4, float a5, uint32_t tag_hi) {
  const uint32_t p2 = pack_bf16(a2, a3);
  const uint32_t p4 = pack_bf16(a4, a5);
  return make_uint4(pack_bf16(a0, a1), (p2 & 0xffffu) | tag_hi, __byte_perm(p2, p4, 0x5432), (p4 >> 16) | tag_hi);
}
__device__ __forceinline__ uint4 ld_relaxed_v4(const uint4* p) {
  uint4 v;
  unsigned long long lo, hi;
  asm volatile("ld.relaxed.gpu.global.v2.b64 {%0, %1}, [%2];" : "=l"(lo), "=l"(hi) : "l"(p) : "memory");
  v.x = (uint32_t)lo; v.y = (uint32_t)(lo >> 32); v.z = (uint32_t)hi; v.w = (uint32_t)(hi >> 32);
  return v;
}
__device__ __forceinline__ void st_relaxed_v4(uint4* p, uint4 v) {
  const unsigned long long lo = (unsigned long long)v.x | ((unsigned long long)v.y << 32);
  const unsigned long long hi = (unsigned long long)v.z | ((unsigned long long)v.w << 32);
  asm volatile("st.relaxed.gpu.global.v2.b64 [%0], {%1, %2};" ::"l"(p), "l"(lo), "l"(hi) : "memory");
}

__global__ void __cluster_dims__(2, 1, 1) __launch_bounds__(384, 1)
fused_gqa_kernel(const __grid_constant__ Maps maps, __nv_bfloat16* __restrict__ out) {
  extern __shared__ __align__(1024) unsigned char smem[];
  const uint32_t sbase = smem_u32(smem);
  const uint32_t full0 = sbase + BAR_OFF;
  const uint32_t empty0 = full0 + N_ITEMS * 8;
  const uint32_t ready0 = empty0 + N_ITEMS * 8;
  volatile uint32_t* s_tag = reinterpret_cast<volatile uint32_t*>(smem + BAR_OFF + 2 * N_ITEMS * 8 + 64);

  const int tid = threadIdx.x;
  const int wg = tid >> 7;
  const int bid = blockIdx.x;
  const int bp = bid & 3;
  const int h = (bid >> 2) & 15;
  const int p = bid >> 6;

  if (tid == 0) {
#pragma unroll
    for (int i = 0; i < 5; i++) mbar_init(full0 + (WQ0 + i) * 8, 1);
#pragma unroll
    for (int i = 0; i < 4; i++) mbar_init(full0 + (X0 + i) * 8, 1);
    asm volatile("fence.mbarrier_init.release.cluster;" ::: "memory");
#pragma unroll
    for (int kc = 0; kc < 5; kc++) {
      if (kc < 4) {
        mbar_expect_tx(full0 + (X0 + kc) * 8, 16384);
        tma_load3(sbase + x_off(kc), &maps.x[p], 0, bp * 128, kc, full0 + (X0 + kc) * 8);
      }
      mbar_expect_tx(full0 + (WQ0 + kc) * 8, T32);
      tma_load3(sbase + wq_off(kc), &maps.wq[p], 0, kc * 64, h * 4, full0 + (WQ0 + kc) * 8);
    }
    TR(0, 56);
  } else if (tid >= 64 && tid < 96) {
    const char* base = maps.px[p] + (size_t)(bp * 128 + h * 8) * 1152;
#pragma unroll
    for (int i = 0; i < 3; i++)
      if ((tid & 31) + i * 32 < 72) l2_prefetch(base + ((tid & 31) + i * 32) * 128);
  } else if (tid == 32) {
    prefetch_tmap(&maps.k[p]);
    prefetch_tmap(&maps.v[p]);
    prefetch_tmap(&maps.wo[p]);
  } else if (tid >= 128) {
    const int i = tid - 128;
    if (i < N_ITEMS) {
      if (!(i < 5 || (i >= X0 && i < X0 + 4))) mbar_init(full0 + i * 8, 1);
    } else if (i >= 64 && i < 64 + N_ITEMS) {
      mbar_init(empty0 + (i - 64) * 8, 8);
    } else if (i >= 128 && i < 128 + 2) {
      mbar_init(ready0 + (i - 128) * 8, 1);
    }
    asm volatile("fence.mbarrier_init.release.cluster;" ::: "memory");
  }
  __syncthreads();
  if (tid == 0) TR(0, 57);

  if (wg == 0) {
    asm volatile("setmaxnreg.dec.sync.aligned.u32 24;");
    if (tid == 0) {
      const int kvrow = (2 * bp * 16 + h) * kSK;
      auto load_kv = [&](int n) {
        if (n >= KV_INFLIGHT) mbar_wait(full0 + (KV0 + n - KV_INFLIGHT) * 8);
        const uint32_t fb = full0 + (KV0 + n) * 8;
        TR(0, KV0 + n);
        mbar_expect_tx(fb, T32);
        tma_load3(sbase + kv_off(n), (n & 1) ? &maps.v[p] : &maps.k[p], 0, kvrow + (n >> 3) * 16 * kSK + ((n & 7) >> 1) * 128, 0, fb);
      };
#pragma unroll 1
      for (int c = 0; c < 9; c++) {
        mbar_wait(empty0 + (X0 + c) * 8);
        if (c < 5) {
          mbar_expect_tx(full0 + (X0 + c + 4) * 8, 16384);
          tma_load3(sbase + x_off(c + 4), &maps.x[p], 0, bp * 128, c + 4, full0 + (X0 + c + 4) * 8);
        }
        if (c < 4) {
          TR(0, WQ0 + c + 5);
          mbar_expect_tx(full0 + (WQ0 + c + 5) * 8, T32);
          tma_load3(sbase + wq_off(c + 5), &maps.wq[p], 0, (c + 5) * 64, h * 4, full0 + (WQ0 + c + 5) * 8);
        } else if (c < 8) {
          load_kv(c - 4);
          if (c == 7) load_kv(4);
        } else {
          load_kv(5);
        }
      }
#pragma unroll 1
      for (int n = 6; n < N_KV; n++) {
        mbar_wait(empty0 + (KV0 + n - 6) * 8);
        load_kv(n);
      }
#pragma unroll 1
      for (int m = 0; m < N_WO; m++) {
        mbar_wait(empty0 + (WO0 + m - 6) * 8);
        const uint32_t fb = full0 + (WO0 + m) * 8;
        TR(0, WO0 + m);
        mbar_expect_tx(fb, WO_BYTES);
        tma_load3(sbase + wo_off(m), &maps.wo[p], 0, h * 256 + (m & 3) * 64, (m >> 2) * 3, fb);
      }
    } else if (tid == 96 || tid == 64) {
      const int w = tid == 96 ? 1 : 0;
      const unsigned old = atomicAdd(&g_cnt[(p * 8 + 2 * bp + w) * 32], 1u);
      s_tag[w] = ((old >> 4) + 1u) << 16;
      mbar_arrive(ready0 + w * 8);
    } else if (tid >= 32 && tid < 64) {
      mbar_wait(full0 + (KV0 + WO_PF_AT) * 8);
      const char* base = maps.pwo[p] + (size_t)(h * 256 + bp * 64) * 1152 + 384;
#pragma unroll 1
      for (int i = tid & 31; i < 64 * 6; i += 32) l2_prefetch(base + (i / 6) * 1152 + (i % 6) * 128);
    }
  } else {
    asm volatile("setmaxnreg.inc.sync.aligned.u32 240;");
    const int w = wg - 1;
    const int t128 = tid & 127;
    const int lane = tid & 31;

    auto release = [&](int item) {
      __syncwarp();
      if (lane == 0) mbar_arrive(empty0 + item * 8);
    };

    TRC(0);
    const float cs = 0.08838834764831845f * 1.4426950408889634f;
    float s[64], o[64];
#pragma unroll
    for (int i = 0; i < 64; i++) s[i] = 0.f, o[i] = 0.f;
    uint32_t qf[32];
    uint4* park = reinterpret_cast<uint4*>(smem + PARK_OFF) + w * 1024 + t128;
    {
#pragma unroll 1
      for (int kc = 0; kc < 9; kc++) {
        mbar_wait(full0 + (X0 + kc) * 8);
        mbar_wait(full0 + (WQ0 + kc) * 8);
        if (kc == 0) TRC(1);
        const uint64_t da = make_desc(sbase + x_off(kc), 16, 1024);
        const uint64_t db = make_desc(sbase + wq_off(kc) + w * 16384, 8192, 1024);
        wg_fence();
#pragma unroll
        for (int ks = 0; ks < 4; ks++) {
          wgmma_ss_n128_tb(s, da + ks * 2, db + ks * 128, (kc | ks) != 0);
          wgmma_ss_n128_tb(o, da + 512 + ks * 2, db + ks * 128, (kc | ks) != 0);
        }
        wg_commit();
        wg_wait<0>();
        release(X0 + kc);
      }
      fence_regs(s);
      fence_regs(o);
#pragma unroll
      for (int i = 0; i < 32; i++) qf[i] = pack_bf16(s[2 * i], s[2 * i + 1]);
      named_bar(1, 256);
#pragma unroll
      for (int i = 0; i < 8; i++) park[i * 128] = pack8(o, i);
      TRC(2);
    }
#pragma unroll 1
    for (int bb = 0; bb < 2; bb++) {
#pragma unroll
      for (int i = 0; i < 64; i++) o[i] = 0.f;
      float m0 = -INFINITY, m1 = -INFINITY, l0 = 0.f, l1 = 0.f;
#pragma unroll 1
      for (int t = 0; t < 4; t++) {
        const int n = bb * 8 + t * 2;
        {
          const uint32_t base = sbase + kv_off(n);
          mbar_wait(full0 + (KV0 + n) * 8);
          if (n == 0 && w == 1) named_bar(4, 256);
          const uint64_t db = make_desc(base, 16, 1024);
          wg_fence();
          wgmma_rs_n128_z(s, qf[0], qf[1], qf[2], qf[3], db);
#pragma unroll
          for (int ks = 1; ks < 8; ks++)
            wgmma_rs_n128(s, qf[4 * ks], qf[4 * ks + 1], qf[4 * ks + 2], qf[4 * ks + 3], db + (ks >> 2) * 1024 + (ks & 3) * 2, 1);
          wg_commit();
          wg_wait<0>();
          fence_regs(s);
          if (n == 0 && w == 0) named_arrive(4, 256);
          release(KV0 + n);
        }
        float mx0 = s[0], mx1 = s[2];
#pragma unroll
        for (int g = 0; g < 16; g++) {
          mx0 = fmaxf(mx0, fmaxf(s[4 * g], s[4 * g + 1]));
          mx1 = fmaxf(mx1, fmaxf(s[4 * g + 2], s[4 * g + 3]));
        }
        mx0 = fmaxf(mx0, __shfl_xor_sync(0xffffffffu, mx0, 1));
        mx0 = fmaxf(mx0, __shfl_xor_sync(0xffffffffu, mx0, 2));
        mx1 = fmaxf(mx1, __shfl_xor_sync(0xffffffffu, mx1, 1));
        mx1 = fmaxf(mx1, __shfl_xor_sync(0xffffffffu, mx1, 2));
        const float mn0 = fmaxf(m0, mx0), mn1 = fmaxf(m1, mx1);
        const float a0 = ex2((m0 - mn0) * cs), a1 = ex2((m1 - mn1) * cs);
        m0 = mn0;
        m1 = mn1;
        const float ms0 = mn0 * cs, ms1 = mn1 * cs;
        float rs0 = 0.f, rs1 = 0.f;
        uint32_t pf[32];
#pragma unroll
        for (int g = 0; g < 16; g++) {
          const float p0 = ex2(fmaf(s[4 * g], cs, -ms0));
          const float p1 = ex2(fmaf(s[4 * g + 1], cs, -ms0));
          const float p2 = ex2(fmaf(s[4 * g + 2], cs, -ms1));
          const float p3 = ex2(fmaf(s[4 * g + 3], cs, -ms1));
          rs0 += p0 + p1;
          rs1 += p2 + p3;
          pf[2 * g] = pack_bf16(p0, p1);
          pf[2 * g + 1] = pack_bf16(p2, p3);
        }
        l0 = l0 * a0 + rs0;
        l1 = l1 * a1 + rs1;
#pragma unroll
        for (int g = 0; g < 16; g++) {
          o[4 * g] *= a0;
          o[4 * g + 1] *= a0;
          o[4 * g + 2] *= a1;
          o[4 * g + 3] *= a1;
        }
        {
          const uint32_t base = sbase + kv_off(n + 1);
          mbar_wait(full0 + (KV0 + n + 1) * 8);
          const uint64_t db = make_desc(base, 16384, 1024);
          wg_fence();
#pragma unroll
          for (int ks = 0; ks < 8; ks++)
            wgmma_rs_n128_tb(o, pf[4 * ks], pf[4 * ks + 1], pf[4 * ks + 2], pf[4 * ks + 3], db + ks * 128, 1);
          wg_commit();
          wg_wait<0>();
          fence_regs(o);
          if (n + 1 < 15) release(KV0 + n + 1);
          TRC(3 + bb * 5 + t);
        }
      }
      l0 += __shfl_xor_sync(0xffffffffu, l0, 1);
      l0 += __shfl_xor_sync(0xffffffffu, l0, 2);
      l1 += __shfl_xor_sync(0xffffffffu, l1, 1);
      l1 += __shfl_xor_sync(0xffffffffu, l1, 2);
      const float i0 = 1.f / l0, i1 = 1.f / l1;
      uint4* dst = park;
      if (bb == 0) {
#pragma unroll
        for (int i = 0; i < 8; i++) {
          const uint4 v = park[i * 128];
          qf[4 * i] = v.x;
          qf[4 * i + 1] = v.y;
          qf[4 * i + 2] = v.z;
          qf[4 * i + 3] = v.w;
        }
      } else {
        named_bar(1, 256);
        dst = reinterpret_cast<uint4*>(smem + kv_off(15)) + w * 1024 + t128;
      }
#pragma unroll
      for (int i = 0; i < 8; i++)
        dst[i * 128] = make_uint4(pack_bf16(o[8 * i] * i0, o[8 * i + 1] * i0), pack_bf16(o[8 * i + 2] * i1, o[8 * i + 3] * i1),
                                  pack_bf16(o[8 * i + 4] * i0, o[8 * i + 5] * i0), pack_bf16(o[8 * i + 6] * i1, o[8 * i + 7] * i1));
    }
    uint32_t af[64];
    {
      named_bar(1, 256);
      const uint4* src = reinterpret_cast<const uint4*>(smem + (w == 0 ? PARK_OFF : kv_off(15))) + t128;
#pragma unroll
      for (int i = 0; i < 16; i++) {
        const uint4 v = src[i * 128];
        af[4 * i] = v.x;
        af[4 * i + 1] = v.y;
        af[4 * i + 2] = v.z;
        af[4 * i + 3] = v.w;
      }
      asm volatile("fence.proxy.async.shared::cta;" ::: "memory");
      release(KV0 + 15);
    }
    TRC(12);
    if (w == 1) named_bar(4, 256);
    const int tile = p * 8 + 2 * bp + w;
    uint4* part = g_part + (size_t)(tile * 16 + h) * 48 * 128 + t128;
    mbar_wait(ready0 + w * 8);
    const uint32_t tag = s_tag[w];
#pragma unroll
    for (int pn = 0; pn < 3; pn++) {
#pragma unroll
      for (int kc = 0; kc < 4; kc++) {
        const int m = pn * 4 + kc;
        mbar_wait(full0 + (WO0 + m) * 8);
        const uint64_t db = make_desc(sbase + wo_off(m), 8192, 1024);
        wg_fence();
#pragma unroll
        for (int ks = 0; ks < 4; ks++) {
          const int a = (kc * 4 + ks) * 4;
          if ((kc | ks) == 0) wgmma_rs_n192_tb_z(s, o, af[a], af[a + 1], af[a + 2], af[a + 3], db);
          else wgmma_rs_n192_tb(s, o, af[a], af[a + 1], af[a + 2], af[a + 3], db + ks * 128);
        }
        wg_commit();
        if (m == 1 && w == 0) named_arrive(4, 256);
        if (kc > 0) {
          wg_wait<1>();
          if (m - 1 < 6) release(WO0 + m - 1);
        }
      }
      wg_wait<0>();
      fence_regs(s);
      fence_regs32(o);
      if (pn == 0) release(WO0 + 3);
      TRC(13 + pn * 2);
#pragma unroll
      for (int i = 0; i < 16; i++) {
        float a[6];
#pragma unroll
        for (int e = 0; e < 6; e++) a[e] = (6 * i + e < 64) ? s[(6 * i + e) & 63] : o[(6 * i + e - 64) & 63];
        st_relaxed_v4(part + (pn * 16 + i) * 128, pack6(a[0], a[1], a[2], a[3], a[4], a[5], tag));
      }
      TRC(14 + pn * 2);
    }
    {
      const int row0 = (t128 >> 5) * 16 + (lane >> 2);
      __nv_bfloat16* orow = out + (size_t)((2 * bp + w) * 64 + row0) * 1152 + p * 576 + (lane & 3) * 2;
      const uint4* pr = g_part + (size_t)(tile * 16) * 48 * 128 + h * 128 + t128;
#pragma unroll
      for (int pn = 0; pn < 3; pn++) {
        uint4 v[16];
#pragma unroll
        for (int c = 0; c < 16; c++) v[c] = ld_relaxed_v4(pr + (size_t)(c * 48 + pn * 16) * 128);
#pragma unroll
        for (int c = 0; c < 16; c++) {
          for (uint32_t it = 0; it < WAIT_LIMIT; ++it) {
            if ((((v[c].y ^ tag) | (v[c].w ^ tag)) >> 16) == 0) break;
            v[c] = ld_relaxed_v4(pr + (size_t)(c * 48 + pn * 16) * 128);
          }
        }
        TRC(19 + pn);
        float a[6];
#pragma unroll
        for (int e = 0; e < 6; e++) a[e] = 0.f;
#pragma unroll
        for (int c = 0; c < 16; c++) {
          a[0] += bf_lo(v[c].x);
          a[1] += bf_hi(v[c].x);
          a[2] += bf_lo(v[c].y);
          a[3] += bf_lo(v[c].z);
          a[4] += bf_hi(v[c].z);
          a[5] += bf_lo(v[c].w);
        }
#pragma unroll
        for (int e = 0; e < 3; e++) {
          const int q = 3 * h + e;
          *reinterpret_cast<uint32_t*>(orow + (q & 1) * 8 * 1152 + pn * 192 + (q >> 1) * 8) = pack_bf16(a[2 * e], a[2 * e + 1]);
        }
      }
    }
    TRC(22);
  }
}

typedef CUresult (*EncodeFn)(CUtensorMap*, CUtensorMapDataType, cuuint32_t, void*, const cuuint64_t*, const cuuint64_t*,
                             const cuuint32_t*, const cuuint32_t*, CUtensorMapInterleave, CUtensorMapSwizzle,
                             CUtensorMapL2promotion, CUtensorMapFloatOOBfill);

void encode3d(EncodeFn fn, CUtensorMap* m, void* ptr, uint64_t cols, uint64_t rows, uint32_t box_rows, uint32_t box_chunks) {
  cuuint64_t dims[3] = {64, rows, cols / 64};
  cuuint64_t strides[2] = {cols * 2, 128};
  cuuint32_t box[3] = {64, box_rows, box_chunks};
  cuuint32_t es[3] = {1, 1, 1};
  fn(m, CU_TENSOR_MAP_DATA_TYPE_BFLOAT16, 3, ptr, dims, strides, box, es, CU_TENSOR_MAP_INTERLEAVE_NONE,
     CU_TENSOR_MAP_SWIZZLE_128B, CU_TENSOR_MAP_L2_PROMOTION_L2_256B, CU_TENSOR_MAP_FLOAT_OOB_FILL_NONE);
}

}

extern "C" void kernel_launch(void* const* d_in, const int* in_sizes, int n_in, void* d_out, int out_size) {
  static EncodeFn fn = nullptr;
  if (!fn) {
    void* f = nullptr;
    cudaDriverEntryPointQueryResult st;
    cudaGetDriverEntryPoint("cuTensorMapEncodeTiled", &f, cudaEnableDefault, &st);
    fn = (EncodeFn)f;
    cudaFuncSetAttribute(fused_gqa_kernel, cudaFuncAttributeMaxDynamicSharedMemorySize, SMEM_BYTES);
  }
  Maps maps;
  for (int p = 0; p < 2; p++) {
    encode3d(fn, &maps.x[p], d_in[p * 5 + 0], kD, 512, 128, 1);
    encode3d(fn, &maps.k[p], d_in[p * 5 + 1], kDH, 8 * 16 * kSK, 128, 2);
    encode3d(fn, &maps.v[p], d_in[p * 5 + 2], kDH, 8 * 16 * kSK, 128, 2);
    encode3d(fn, &maps.wq[p], d_in[p * 5 + 3], kHQD, kD, 64, 4);
    encode3d(fn, &maps.wo[p], d_in[p * 5 + 4], kD, kHQD, 64, 3);
    maps.px[p] = (const char*)d_in[p * 5 + 0];
    maps.pwo[p] = (const char*)d_in[p * 5 + 4];
  }
  fused_gqa_kernel<<<128, 384, SMEM_BYTES>>>(maps, (__nv_bfloat16*)d_out);
}
```

```cpp
#include <cuda_runtime.h>
#include <cuda_bf16.h>
#include <cuda.h>
#include <stdint.h>

namespace {

constexpr int kD = 576, kHQD = 4096, kSK = 512, kDH = 128;

constexpr int N_WQ = 9, N_X = 9, N_RING = 34;
constexpr int N_ITEMS = N_WQ + N_X + N_RING;
constexpr int T32 = 32 * 1024;
constexpr int PARK_OFF = 192 * 1024;
constexpr int BAR_OFF = 224 * 1024;
constexpr int SMEM_BYTES = BAR_OFF + 2 * N_ITEMS * 8 + 256;
constexpr int WQ0 = 0, X0 = N_WQ, R0 = X0 + N_X;
#define KV_INFLIGHT 2

__device__ __forceinline__ int wq_off(int kc) { return (kc < 5 ? kc : kc - 5) * T32; }
__device__ __forceinline__ int x_off(int kc) { return ((kc & 2) ? 5 * T32 : PARK_OFF) + (kc & 1) * 16384; }
__device__ __forceinline__ int ring_off(int pos) { return (int)((0x352104u >> ((pos % 6) * 4)) & 15u) * T32; }

__device__ uint4 g_part[16 * 16 * 2 * 20 * 128];
__device__ unsigned int g_cnt[16 * 32];

#define TR(role, ev)
#define TRC(ev)
constexpr uint32_t WAIT_CYCLES = 1u << 20;
constexpr uint32_t WAIT_LIMIT = 1u << 12;
__device__ __forceinline__ uint32_t smem_u32(const void* p) { return (uint32_t)__cvta_generic_to_shared(p); }
__device__ __forceinline__ void mbar_init(uint32_t bar, uint32_t cnt) {
  asm volatile("mbarrier.init.shared::cta.b64 [%0], %1;" ::"r"(bar), "r"(cnt) : "memory");
}
__device__ __forceinline__ void mbar_expect_tx(uint32_t bar, uint32_t bytes) {
  asm volatile("mbarrier.arrive.expect_tx.shared::cta.b64 _, [%0], %1;" ::"r"(bar), "r"(bytes) : "memory");
}
__device__ __forceinline__ void mbar_arrive(uint32_t bar) {
  asm volatile("mbarrier.arrive.shared::cta.b64 _, [%0];" ::"r"(bar) : "memory");
}
__device__ __forceinline__ bool mbar_try(uint32_t bar, uint32_t parity) {
  uint32_t ok;
  asm volatile(
      "{\n.reg .pred p;\nmbarrier.try_wait.parity.shared::cta.b64 p, [%1], %2;\nselp.u32 %0, 1, 0, p;\n}\n"
      : "=r"(ok)
      : "r"(bar), "r"(parity)
      : "memory");
  return ok != 0;
}
__device__ __forceinline__ void mbar_wait(uint32_t bar) {
  if (mbar_try(bar, 0)) return;
  const uint32_t t0 = (uint32_t)clock();
  while (!mbar_try(bar, 0))
    if ((uint32_t)clock() - t0 > WAIT_CYCLES) break;
}
__device__ __forceinline__ void tma_load3(uint32_t dst, const CUtensorMap* tm, int c0, int c1, int c2, uint32_t bar) {
  asm volatile(
      "cp.async.bulk.tensor.3d.shared::cluster.global.mbarrier::complete_tx::bytes [%0], [%1, {%3, %4, %5}], [%2];" ::"r"(dst),
      "l"(tm), "r"(bar), "r"(c0), "r"(c1), "r"(c2)
      : "memory");
}
__device__ __forceinline__ void l2_prefetch(const void* p) { asm volatile("prefetch.global.L2 [%0];" ::"l"(p) : "memory"); }
__device__ __forceinline__ void prefetch_tmap(const CUtensorMap* tm) {
  asm volatile("prefetch.tensormap [%0];" ::"l"(tm) : "memory");
}
__device__ __forceinline__ void named_bar(int id, int n) { asm volatile("bar.sync %0, %1;" ::"r"(id), "r"(n) : "memory"); }
__device__ __forceinline__ void named_arrive(int id, int n) { asm volatile("bar.arrive %0, %1;" ::"r"(id), "r"(n) : "memory"); }
__device__ __forceinline__ void wg_fence() { asm volatile("wgmma.fence.sync.aligned;" ::: "memory"); }
__device__ __forceinline__ void wg_commit() { asm volatile("wgmma.commit_group.sync.aligned;" ::: "memory"); }
template <int N>
__device__ __forceinline__ void wg_wait() { asm volatile("wgmma.wait_group.sync.aligned %0;" ::"n"(N) : "memory"); }
template <int N>
__device__ __forceinline__ void fence_regs(float (&d)[N]) {
#pragma unroll
  for (int i = 0; i < N; i++) asm volatile("" : "+f"(d[i])::"memory");
}
__device__ __forceinline__ void fence_regs32(float (&d)[64]) {
#pragma unroll
  for (int i = 0; i < 32; i++) asm volatile("" : "+f"(d[i])::"memory");
}
__device__ __forceinline__ uint64_t make_desc(uint32_t addr, uint32_t lbo, uint32_t sbo) {
  return (uint64_t)((addr & 0x3FFFF) >> 4) | ((uint64_t)(lbo >> 4) << 16) | ((uint64_t)(sbo >> 4) << 32) | (1ull << 62);
}
__device__ __forceinline__ uint32_t pack_bf16(float lo, float hi) {
  uint32_t r;
  asm("cvt.rn.bf16x2.f32 %0, %1, %2;" : "=r"(r) : "f"(hi), "f"(lo));
  return r;
}
__device__ __forceinline__ float ex2(float x) {
  float y;
  asm("ex2.approx.ftz.f32 %0, %1;" : "=f"(y) : "f"(x));
  return y;
}
__device__ __forceinline__ float bf_lo(uint32_t v) { return __uint_as_float(v << 16); }
__device__ __forceinline__ float bf_hi(uint32_t v) { return __uint_as_float(v & 0xffff0000u); }
template <int N>
__device__ __forceinline__ uint4 pack8(const float (&a)[N], int i) {
  return make_uint4(pack_bf16(a[8 * i], a[8 * i + 1]), pack_bf16(a[8 * i + 2], a[8 * i + 3]), pack_bf16(a[8 * i + 4], a[8 * i + 5]),
                    pack_bf16(a[8 * i + 6], a[8 * i + 7]));
}

__device__ __forceinline__ void wgmma_ss_n128_tb(float (&d)[64], uint64_t da, uint64_t db, int scale_d) {
  asm volatile("{\n.reg .pred p;\nsetp.ne.b32 p, %66, 0;\n"
    "wgmma.mma_async.sync.aligned.m64n128k16.f32.bf16.bf16 {%0, %1, %2, %3, %4, %5, %6, %7, %8, %9, %10, %11, %12, %13, %14, %15, %16, %17, %18, %19, %20, %21, %22, %23, %24, %25, %26, %27, %28, %29, %30, %31, %32, %33, %34, %35, %36, %37, %38, %39, %40, %41, %42, %43, %44, %45, %46, %47, %48, %49, %50, %51, %52, %53, %54, %55, %56, %57, %58, %59, %60, %61, %62, %63}, %64, %65, p, 1, 1, 0, 1;\n}\n"
    : "+f"(d[0]), "+f"(d[1]), "+f"(d[2]), "+f"(d[3]), "+f"(d[4]), "+f"(d[5]), "+f"(d[6]), "+f"(d[7]), "+f"(d[8]), "+f"(d[9]), "+f"(d[10]), "+f"(d[11]), "+f"(d[12]), "+f"(d[13]), "+f"(d[14]), "+f"(d[15]), "+f"(d[16]), "+f"(d[17]), "+f"(d[18]), "+f"(d[19]), "+f"(d[20]), "+f"(d[21]), "+f"(d[22]), "+f"(d[23]), "+f"(d[24]), "+f"(d[25]), "+f"(d[26]), "+f"(d[27]), "+f"(d[28]), "+f"(d[29]), "+f"(d[30]), "+f"(d[31]), "+f"(d[32]), "+f"(d[33]), "+f"(d[34]), "+f"(d[35]), "+f"(d[36]), "+f"(d[37]), "+f"(d[38]), "+f"(d[39]), "+f"(d[40]), "+f"(d[41]), "+f"(d[42]), "+f"(d[43]), "+f"(d[44]), "+f"(d[45]), "+f"(d[46]), "+f"(d[47]), "+f"(d[48]), "+f"(d[49]), "+f"(d[50]), "+f"(d[51]), "+f"(d[52]), "+f"(d[53]), "+f"(d[54]), "+f"(d[55]), "+f"(d[56]), "+f"(d[57]), "+f"(d[58]), "+f"(d[59]), "+f"(d[60]), "+f"(d[61]), "+f"(d[62]), "+f"(d[63])
    : "l"(da), "l"(db), "r"(scale_d));
}

__device__ __forceinline__ void wgmma_rs_n128(float (&d)[64], uint32_t a0, uint32_t a1, uint32_t a2, uint32_t a3, uint64_t db, int scale_d) {
  asm volatile("{\n.reg .pred p;\nsetp.ne.b32 p, %69, 0;\n"
    "wgmma.mma_async.sync.aligned.m64n128k16.f32.bf16.bf16 {%0, %1, %2, %3, %4, %5, %6, %7, %8, %9, %10, %11, %12, %13, %14, %15, %16, %17, %18, %19, %20, %21, %22, %23, %24, %25, %26, %27, %28, %29, %30, %31, %32, %33, %34, %35, %36, %37, %38, %39, %40, %41, %42, %43, %44, %45, %46, %47, %48, %49, %50, %51, %52, %53, %54, %55, %56, %57, %58, %59, %60, %61, %62, %63}, {%64, %65, %66, %67}, %68, p, 1, 1, 0;\n}\n"
    : "+f"(d[0]), "+f"(d[1]), "+f"(d[2]), "+f"(d[3]), "+f"(d[4]), "+f"(d[5]), "+f"(d[6]), "+f"(d[7]), "+f"(d[8]), "+f"(d[9]), "+f"(d[10]), "+f"(d[11]), "+f"(d[12]), "+f"(d[13]), "+f"(d[14]), "+f"(d[15]), "+f"(d[16]), "+f"(d[17]), "+f"(d[18]), "+f"(d[19]), "+f"(d[20]), "+f"(d[21]), "+f"(d[22]), "+f"(d[23]), "+f"(d[24]), "+f"(d[25]), "+f"(d[26]), "+f"(d[27]), "+f"(d[28]), "+f"(d[29]), "+f"(d[30]), "+f"(d[31]), "+f"(d[32]), "+f"(d[33]), "+f"(d[34]), "+f"(d[35]), "+f"(d[36]), "+f"(d[37]), "+f"(d[38]), "+f"(d[39]), "+f"(d[40]), "+f"(d[41]), "+f"(d[42]), "+f"(d[43]), "+f"(d[44]), "+f"(d[45]), "+f"(d[46]), "+f"(d[47]), "+f"(d[48]), "+f"(d[49]), "+f"(d[50]), "+f"(d[51]), "+f"(d[52]), "+f"(d[53]), "+f"(d[54]), "+f"(d[55]), "+f"(d[56]), "+f"(d[57]), "+f"(d[58]), "+f"(d[59]), "+f"(d[60]), "+f"(d[61]), "+f"(d[62]), "+f"(d[63])
    : "r"(a0), "r"(a1), "r"(a2), "r"(a3), "l"(db), "r"(scale_d));
}

__device__ __forceinline__ void wgmma_rs_n128_tb(float (&d)[64], uint32_t a0, uint32_t a1, uint32_t a2, uint32_t a3, uint64_t db, int scale_d) {
  asm volatile("{\n.reg .pred p;\nsetp.ne.b32 p, %69, 0;\n"
    "wgmma.mma_async.sync.aligned.m64n128k16.f32.bf16.bf16 {%0, %1, %2, %3, %4, %5, %6, %7, %8, %9, %10, %11, %12, %13, %14, %15, %16, %17, %18, %19, %20, %21, %22, %23, %24, %25, %26, %27, %28, %29, %30, %31, %32, %33, %34, %35, %36, %37, %38, %39, %40, %41, %42, %43, %44, %45, %46, %47, %48, %49, %50, %51, %52, %53, %54, %55, %56, %57, %58, %59, %60, %61, %62, %63}, {%64, %65, %66, %67}, %68, p, 1, 1, 1;\n}\n"
    : "+f"(d[0]), "+f"(d[1]), "+f"(d[2]), "+f"(d[3]), "+f"(d[4]), "+f"(d[5]), "+f"(d[6]), "+f"(d[7]), "+f"(d[8]), "+f"(d[9]), "+f"(d[10]), "+f"(d[11]), "+f"(d[12]), "+f"(d[13]), "+f"(d[14]), "+f"(d[15]), "+f"(d[16]), "+f"(d[17]), "+f"(d[18]), "+f"(d[19]), "+f"(d[20]), "+f"(d[21]), "+f"(d[22]), "+f"(d[23]), "+f"(d[24]), "+f"(d[25]), "+f"(d[26]), "+f"(d[27]), "+f"(d[28]), "+f"(d[29]), "+f"(d[30]), "+f"(d[31]), "+f"(d[32]), "+f"(d[33]), "+f"(d[34]), "+f"(d[35]), "+f"(d[36]), "+f"(d[37]), "+f"(d[38]), "+f"(d[39]), "+f"(d[40]), "+f"(d[41]), "+f"(d[42]), "+f"(d[43]), "+f"(d[44]), "+f"(d[45]), "+f"(d[46]), "+f"(d[47]), "+f"(d[48]), "+f"(d[49]), "+f"(d[50]), "+f"(d[51]), "+f"(d[52]), "+f"(d[53]), "+f"(d[54]), "+f"(d[55]), "+f"(d[56]), "+f"(d[57]), "+f"(d[58]), "+f"(d[59]), "+f"(d[60]), "+f"(d[61]), "+f"(d[62]), "+f"(d[63])
    : "r"(a0), "r"(a1), "r"(a2), "r"(a3), "l"(db), "r"(scale_d));
}

__device__ __forceinline__ void wgmma_rs_n32_tb(float (&d)[16], uint32_t a0, uint32_t a1, uint32_t a2, uint32_t a3, uint64_t db, int scale_d) {
  asm volatile("{\n.reg .pred p;\nsetp.ne.b32 p, %21, 0;\n"
    "wgmma.mma_async.sync.aligned.m64n32k16.f32.bf16.bf16 {%0, %1, %2, %3, %4, %5, %6, %7, %8, %9, %10, %11, %12, %13, %14, %15}, {%16, %17, %18, %19}, %20, p, 1, 1, 1;\n}\n"
    : "+f"(d[0]), "+f"(d[1]), "+f"(d[2]), "+f"(d[3]), "+f"(d[4]), "+f"(d[5]), "+f"(d[6]), "+f"(d[7]), "+f"(d[8]), "+f"(d[9]), "+f"(d[10]), "+f"(d[11]), "+f"(d[12]), "+f"(d[13]), "+f"(d[14]), "+f"(d[15])
    : "r"(a0), "r"(a1), "r"(a2), "r"(a3), "l"(db), "r"(scale_d));
}

__device__ __forceinline__ void wgmma_rs_n64_tb(float (&d)[32], uint32_t a0, uint32_t a1, uint32_t a2, uint32_t a3, uint64_t db, int scale_d) {
  asm volatile("{\n.reg .pred p;\nsetp.ne.b32 p, %37, 0;\n"
    "wgmma.mma_async.sync.aligned.m64n64k16.f32.bf16.bf16 {%0, %1, %2, %3, %4, %5, %6, %7, %8, %9, %10, %11, %12, %13, %14, %15, %16, %17, %18, %19, %20, %21, %22, %23, %24, %25, %26, %27, %28, %29, %30, %31}, {%32, %33, %34, %35}, %36, p, 1, 1, 1;\n}\n"
    : "+f"(d[0]), "+f"(d[1]), "+f"(d[2]), "+f"(d[3]), "+f"(d[4]), "+f"(d[5]), "+f"(d[6]), "+f"(d[7]), "+f"(d[8]), "+f"(d[9]), "+f"(d[10]), "+f"(d[11]), "+f"(d[12]), "+f"(d[13]), "+f"(d[14]), "+f"(d[15]), "+f"(d[16]), "+f"(d[17]), "+f"(d[18]), "+f"(d[19]), "+f"(d[20]), "+f"(d[21]), "+f"(d[22]), "+f"(d[23]), "+f"(d[24]), "+f"(d[25]), "+f"(d[26]), "+f"(d[27]), "+f"(d[28]), "+f"(d[29]), "+f"(d[30]), "+f"(d[31])
    : "r"(a0), "r"(a1), "r"(a2), "r"(a3), "l"(db), "r"(scale_d));
}

__device__ __forceinline__ void wgmma_rs_n256_tb(float (&d)[64], float (&e)[64], uint32_t a0, uint32_t a1, uint32_t a2, uint32_t a3, uint64_t db, int scale_d) {
  asm volatile("{\n.reg .pred p;\nsetp.ne.b32 p, %133, 0;\n"
    "wgmma.mma_async.sync.aligned.m64n256k16.f32.bf16.bf16 {%0, %1, %2, %3, %4, %5, %6, %7, %8, %9, %10, %11, %12, %13, %14, %15, %16, %17, %18, %19, %20, %21, %22, %23, %24, %25, %26, %27, %28, %29, %30, %31, %32, %33, %34, %35, %36, %37, %38, %39, %40, %41, %42, %43, %44, %45, %46, %47, %48, %49, %50, %51, %52, %53, %54, %55, %56, %57, %58, %59, %60, %61, %62, %63, %64, %65, %66, %67, %68, %69, %70, %71, %72, %73, %74, %75, %76, %77, %78, %79, %80, %81, %82, %83, %84, %85, %86, %87, %88, %89, %90, %91, %92, %93, %94, %95, %96, %97, %98, %99, %100, %101, %102, %103, %104, %105, %106, %107, %108, %109, %110, %111, %112, %113, %114, %115, %116, %117, %118, %119, %120, %121, %122, %123, %124, %125, %126, %127}, {%128, %129, %130, %131}, %132, p, 1, 1, 1;\n}\n"
    : "+f"(d[0]), "+f"(d[1]), "+f"(d[2]), "+f"(d[3]), "+f"(d[4]), "+f"(d[5]), "+f"(d[6]), "+f"(d[7]), "+f"(d[8]), "+f"(d[9]), "+f"(d[10]), "+f"(d[11]), "+f"(d[12]), "+f"(d[13]), "+f"(d[14]), "+f"(d[15]), "+f"(d[16]), "+f"(d[17]), "+f"(d[18]), "+f"(d[19]), "+f"(d[20]), "+f"(d[21]), "+f"(d[22]), "+f"(d[23]), "+f"(d[24]), "+f"(d[25]), "+f"(d[26]), "+f"(d[27]), "+f"(d[28]), "+f"(d[29]), "+f"(d[30]), "+f"(d[31]), "+f"(d[32]), "+f"(d[33]), "+f"(d[34]), "+f"(d[35]), "+f"(d[36]), "+f"(d[37]), "+f"(d[38]), "+f"(d[39]), "+f"(d[40]), "+f"(d[41]), "+f"(d[42]), "+f"(d[43]), "+f"(d[44]), "+f"(d[45]), "+f"(d[46]), "+f"(d[47]), "+f"(d[48]), "+f"(d[49]), "+f"(d[50]), "+f"(d[51]), "+f"(d[52]), "+f"(d[53]), "+f"(d[54]), "+f"(d[55]), "+f"(d[56]), "+f"(d[57]), "+f"(d[58]), "+f"(d[59]), "+f"(d[60]), "+f"(d[61]), "+f"(d[62]), "+f"(d[63]), "+f"(e[0]), "+f"(e[1]), "+f"(e[2]), "+f"(e[3]), "+f"(e[4]), "+f"(e[5]), "+f"(e[6]), "+f"(e[7]), "+f"(e[8]), "+f"(e[9]), "+f"(e[10]), "+f"(e[11]), "+f"(e[12]), "+f"(e[13]), "+f"(e[14]), "+f"(e[15]), "+f"(e[16]), "+f"(e[17]), "+f"(e[18]), "+f"(e[19]), "+f"(e[20]), "+f"(e[21]), "+f"(e[22]), "+f"(e[23]), "+f"(e[24]), "+f"(e[25]), "+f"(e[26]), "+f"(e[27]), "+f"(e[28]), "+f"(e[29]), "+f"(e[30]), "+f"(e[31]), "+f"(e[32]), "+f"(e[33]), "+f"(e[34]), "+f"(e[35]), "+f"(e[36]), "+f"(e[37]), "+f"(e[38]), "+f"(e[39]), "+f"(e[40]), "+f"(e[41]), "+f"(e[42]), "+f"(e[43]), "+f"(e[44]), "+f"(e[45]), "+f"(e[46]), "+f"(e[47]), "+f"(e[48]), "+f"(e[49]), "+f"(e[50]), "+f"(e[51]), "+f"(e[52]), "+f"(e[53]), "+f"(e[54]), "+f"(e[55]), "+f"(e[56]), "+f"(e[57]), "+f"(e[58]), "+f"(e[59]), "+f"(e[60]), "+f"(e[61]), "+f"(e[62]), "+f"(e[63])
    : "r"(a0), "r"(a1), "r"(a2), "r"(a3), "l"(db), "r"(scale_d));
}

__device__ __forceinline__ void wgmma_rs_n128_z(float (&d)[64], uint32_t a0, uint32_t a1, uint32_t a2, uint32_t a3, uint64_t db) {
  asm volatile("{\n.reg .pred p;\nsetp.ne.b32 p, 0, 0;\n"
    "wgmma.mma_async.sync.aligned.m64n128k16.f32.bf16.bf16 {%0, %1, %2, %3, %4, %5, %6, %7, %8, %9, %10, %11, %12, %13, %14, %15, %16, %17, %18, %19, %20, %21, %22, %23, %24, %25, %26, %27, %28, %29, %30, %31, %32, %33, %34, %35, %36, %37, %38, %39, %40, %41, %42, %43, %44, %45, %46, %47, %48, %49, %50, %51, %52, %53, %54, %55, %56, %57, %58, %59, %60, %61, %62, %63}, {%64, %65, %66, %67}, %68, p, 1, 1, 0;\n}\n"
    : "=f"(d[0]), "=f"(d[1]), "=f"(d[2]), "=f"(d[3]), "=f"(d[4]), "=f"(d[5]), "=f"(d[6]), "=f"(d[7]), "=f"(d[8]), "=f"(d[9]), "=f"(d[10]), "=f"(d[11]), "=f"(d[12]), "=f"(d[13]), "=f"(d[14]), "=f"(d[15]), "=f"(d[16]), "=f"(d[17]), "=f"(d[18]), "=f"(d[19]), "=f"(d[20]), "=f"(d[21]), "=f"(d[22]), "=f"(d[23]), "=f"(d[24]), "=f"(d[25]), "=f"(d[26]), "=f"(d[27]), "=f"(d[28]), "=f"(d[29]), "=f"(d[30]), "=f"(d[31]), "=f"(d[32]), "=f"(d[33]), "=f"(d[34]), "=f"(d[35]), "=f"(d[36]), "=f"(d[37]), "=f"(d[38]), "=f"(d[39]), "=f"(d[40]), "=f"(d[41]), "=f"(d[42]), "=f"(d[43]), "=f"(d[44]), "=f"(d[45]), "=f"(d[46]), "=f"(d[47]), "=f"(d[48]), "=f"(d[49]), "=f"(d[50]), "=f"(d[51]), "=f"(d[52]), "=f"(d[53]), "=f"(d[54]), "=f"(d[55]), "=f"(d[56]), "=f"(d[57]), "=f"(d[58]), "=f"(d[59]), "=f"(d[60]), "=f"(d[61]), "=f"(d[62]), "=f"(d[63])
    : "r"(a0), "r"(a1), "r"(a2), "r"(a3), "l"(db));
}

__device__ __forceinline__ void wgmma_rs_n64_tb_z(float (&d)[32], uint32_t a0, uint32_t a1, uint32_t a2, uint32_t a3, uint64_t db) {
  asm volatile("{\n.reg .pred p;\nsetp.ne.b32 p, 0, 0;\n"
    "wgmma.mma_async.sync.aligned.m64n64k16.f32.bf16.bf16 {%0, %1, %2, %3, %4, %5, %6, %7, %8, %9, %10, %11, %12, %13, %14, %15, %16, %17, %18, %19, %20, %21, %22, %23, %24, %25, %26, %27, %28, %29, %30, %31}, {%32, %33, %34, %35}, %36, p, 1, 1, 1;\n}\n"
    : "=f"(d[0]), "=f"(d[1]), "=f"(d[2]), "=f"(d[3]), "=f"(d[4]), "=f"(d[5]), "=f"(d[6]), "=f"(d[7]), "=f"(d[8]), "=f"(d[9]), "=f"(d[10]), "=f"(d[11]), "=f"(d[12]), "=f"(d[13]), "=f"(d[14]), "=f"(d[15]), "=f"(d[16]), "=f"(d[17]), "=f"(d[18]), "=f"(d[19]), "=f"(d[20]), "=f"(d[21]), "=f"(d[22]), "=f"(d[23]), "=f"(d[24]), "=f"(d[25]), "=f"(d[26]), "=f"(d[27]), "=f"(d[28]), "=f"(d[29]), "=f"(d[30]), "=f"(d[31])
    : "r"(a0), "r"(a1), "r"(a2), "r"(a3), "l"(db));
}

__device__ __forceinline__ void wgmma_rs_n256_tb_z(float (&d)[64], float (&e)[64], uint32_t a0, uint32_t a1, uint32_t a2, uint32_t a3, uint64_t db) {
  asm volatile("{\n.reg .pred p;\nsetp.ne.b32 p, 0, 0;\n"
    "wgmma.mma_async.sync.aligned.m64n256k16.f32.bf16.bf16 {%0, %1, %2, %3, %4, %5, %6, %7, %8, %9, %10, %11, %12, %13, %14, %15, %16, %17, %18, %19, %20, %21, %22, %23, %24, %25, %26, %27, %28, %29, %30, %31, %32, %33, %34, %35, %36, %37, %38, %39, %40, %41, %42, %43, %44, %45, %46, %47, %48, %49, %50, %51, %52, %53, %54, %55, %56, %57, %58, %59, %60, %61, %62, %63, %64, %65, %66, %67, %68, %69, %70, %71, %72, %73, %74, %75, %76, %77, %78, %79, %80, %81, %82, %83, %84, %85, %86, %87, %88, %89, %90, %91, %92, %93, %94, %95, %96, %97, %98, %99, %100, %101, %102, %103, %104, %105, %106, %107, %108, %109, %110, %111, %112, %113, %114, %115, %116, %117, %118, %119, %120, %121, %122, %123, %124, %125, %126, %127}, {%128, %129, %130, %131}, %132, p, 1, 1, 1;\n}\n"
    : "=f"(d[0]), "=f"(d[1]), "=f"(d[2]), "=f"(d[3]), "=f"(d[4]), "=f"(d[5]), "=f"(d[6]), "=f"(d[7]), "=f"(d[8]), "=f"(d[9]), "=f"(d[10]), "=f"(d[11]), "=f"(d[12]), "=f"(d[13]), "=f"(d[14]), "=f"(d[15]), "=f"(d[16]), "=f"(d[17]), "=f"(d[18]), "=f"(d[19]), "=f"(d[20]), "=f"(d[21]), "=f"(d[22]), "=f"(d[23]), "=f"(d[24]), "=f"(d[25]), "=f"(d[26]), "=f"(d[27]), "=f"(d[28]), "=f"(d[29]), "=f"(d[30]), "=f"(d[31]), "=f"(d[32]), "=f"(d[33]), "=f"(d[34]), "=f"(d[35]), "=f"(d[36]), "=f"(d[37]), "=f"(d[38]), "=f"(d[39]), "=f"(d[40]), "=f"(d[41]), "=f"(d[42]), "=f"(d[43]), "=f"(d[44]), "=f"(d[45]), "=f"(d[46]), "=f"(d[47]), "=f"(d[48]), "=f"(d[49]), "=f"(d[50]), "=f"(d[51]), "=f"(d[52]), "=f"(d[53]), "=f"(d[54]), "=f"(d[55]), "=f"(d[56]), "=f"(d[57]), "=f"(d[58]), "=f"(d[59]), "=f"(d[60]), "=f"(d[61]), "=f"(d[62]), "=f"(d[63]), "=f"(e[0]), "=f"(e[1]), "=f"(e[2]), "=f"(e[3]), "=f"(e[4]), "=f"(e[5]), "=f"(e[6]), "=f"(e[7]), "=f"(e[8]), "=f"(e[9]), "=f"(e[10]), "=f"(e[11]), "=f"(e[12]), "=f"(e[13]), "=f"(e[14]), "=f"(e[15]), "=f"(e[16]), "=f"(e[17]), "=f"(e[18]), "=f"(e[19]), "=f"(e[20]), "=f"(e[21]), "=f"(e[22]), "=f"(e[23]), "=f"(e[24]), "=f"(e[25]), "=f"(e[26]), "=f"(e[27]), "=f"(e[28]), "=f"(e[29]), "=f"(e[30]), "=f"(e[31]), "=f"(e[32]), "=f"(e[33]), "=f"(e[34]), "=f"(e[35]), "=f"(e[36]), "=f"(e[37]), "=f"(e[38]), "=f"(e[39]), "=f"(e[40]), "=f"(e[41]), "=f"(e[42]), "=f"(e[43]), "=f"(e[44]), "=f"(e[45]), "=f"(e[46]), "=f"(e[47]), "=f"(e[48]), "=f"(e[49]), "=f"(e[50]), "=f"(e[51]), "=f"(e[52]), "=f"(e[53]), "=f"(e[54]), "=f"(e[55]), "=f"(e[56]), "=f"(e[57]), "=f"(e[58]), "=f"(e[59]), "=f"(e[60]), "=f"(e[61]), "=f"(e[62]), "=f"(e[63])
    : "r"(a0), "r"(a1), "r"(a2), "r"(a3), "l"(db));
}

__device__ __forceinline__ void wgmma_rs_n192_tb(float (&d)[64], float (&e)[64], uint32_t a0, uint32_t a1, uint32_t a2, uint32_t a3, uint64_t db) {
  asm volatile("{\n.reg .pred p;\nsetp.eq.b32 p, 0, 0;\n"
    "wgmma.mma_async.sync.aligned.m64n192k16.f32.bf16.bf16 {%0, %1, %2, %3, %4, %5, %6, %7, %8, %9, %10, %11, %12, %13, %14, %15, %16, %17, %18, %19, %20, %21, %22, %23, %24, %25, %26, %27, %28, %29, %30, %31, %32, %33, %34, %35, %36, %37, %38, %39, %40, %41, %42, %43, %44, %45, %46, %47, %48, %49, %50, %51, %52, %53, %54, %55, %56, %57, %58, %59, %60, %61, %62, %63, %64, %65, %66, %67, %68, %69, %70, %71, %72, %73, %74, %75, %76, %77, %78, %79, %80, %81, %82, %83, %84, %85, %86, %87, %88, %89, %90, %91, %92, %93, %94, %95}, {%96, %97, %98, %99}, %100, p, 1, 1, 1;\n}\n"
    : "+f"(d[0]), "+f"(d[1]), "+f"(d[2]), "+f"(d[3]), "+f"(d[4]), "+f"(d[5]), "+f"(d[6]), "+f"(d[7]), "+f"(d[8]), "+f"(d[9]), "+f"(d[10]), "+f"(d[11]), "+f"(d[12]), "+f"(d[13]), "+f"(d[14]), "+f"(d[15]), "+f"(d[16]), "+f"(d[17]), "+f"(d[18]), "+f"(d[19]), "+f"(d[20]), "+f"(d[21]), "+f"(d[22]), "+f"(d[23]), "+f"(d[24]), "+f"(d[25]), "+f"(d[26]), "+f"(d[27]), "+f"(d[28]), "+f"(d[29]), "+f"(d[30]), "+f"(d[31]), "+f"(d[32]), "+f"(d[33]), "+f"(d[34]), "+f"(d[35]), "+f"(d[36]), "+f"(d[37]), "+f"(d[38]), "+f"(d[39]), "+f"(d[40]), "+f"(d[41]), "+f"(d[42]), "+f"(d[43]), "+f"(d[44]), "+f"(d[45]), "+f"(d[46]), "+f"(d[47]), "+f"(d[48]), "+f"(d[49]), "+f"(d[50]), "+f"(d[51]), "+f"(d[52]), "+f"(d[53]), "+f"(d[54]), "+f"(d[55]), "+f"(d[56]), "+f"(d[57]), "+f"(d[58]), "+f"(d[59]), "+f"(d[60]), "+f"(d[61]), "+f"(d[62]), "+f"(d[63]), "+f"(e[0]), "+f"(e[1]), "+f"(e[2]), "+f"(e[3]), "+f"(e[4]), "+f"(e[5]), "+f"(e[6]), "+f"(e[7]), "+f"(e[8]), "+f"(e[9]), "+f"(e[10]), "+f"(e[11]), "+f"(e[12]), "+f"(e[13]), "+f"(e[14]), "+f"(e[15]), "+f"(e[16]), "+f"(e[17]), "+f"(e[18]), "+f"(e[19]), "+f"(e[20]), "+f"(e[21]), "+f"(e[22]), "+f"(e[23]), "+f"(e[24]), "+f"(e[25]), "+f"(e[26]), "+f"(e[27]), "+f"(e[28]), "+f"(e[29]), "+f"(e[30]), "+f"(e[31])
    : "r"(a0), "r"(a1), "r"(a2), "r"(a3), "l"(db));
}

__device__ __forceinline__ void wgmma_rs_n192_tb_z(float (&d)[64], float (&e)[64], uint32_t a0, uint32_t a1, uint32_t a2, uint32_t a3, uint64_t db) {
  asm volatile("{\n.reg .pred p;\nsetp.ne.b32 p, 0, 0;\n"
    "wgmma.mma_async.sync.aligned.m64n192k16.f32.bf16.bf16 {%0, %1, %2, %3, %4, %5, %6, %7, %8, %9, %10, %11, %12, %13, %14, %15, %16, %17, %18, %19, %20, %21, %22, %23, %24, %25, %26, %27, %28, %29, %30, %31, %32, %33, %34, %35, %36, %37, %38, %39, %40, %41, %42, %43, %44, %45, %46, %47, %48, %49, %50, %51, %52, %53, %54, %55, %56, %57, %58, %59, %60, %61, %62, %63, %64, %65, %66, %67, %68, %69, %70, %71, %72, %73, %74, %75, %76, %77, %78, %79, %80, %81, %82, %83, %84, %85, %86, %87, %88, %89, %90, %91, %92, %93, %94, %95}, {%96, %97, %98, %99}, %100, p, 1, 1, 1;\n}\n"
    : "=f"(d[0]), "=f"(d[1]), "=f"(d[2]), "=f"(d[3]), "=f"(d[4]), "=f"(d[5]), "=f"(d[6]), "=f"(d[7]), "=f"(d[8]), "=f"(d[9]), "=f"(d[10]), "=f"(d[11]), "=f"(d[12]), "=f"(d[13]), "=f"(d[14]), "=f"(d[15]), "=f"(d[16]), "=f"(d[17]), "=f"(d[18]), "=f"(d[19]), "=f"(d[20]), "=f"(d[21]), "=f"(d[22]), "=f"(d[23]), "=f"(d[24]), "=f"(d[25]), "=f"(d[26]), "=f"(d[27]), "=f"(d[28]), "=f"(d[29]), "=f"(d[30]), "=f"(d[31]), "=f"(d[32]), "=f"(d[33]), "=f"(d[34]), "=f"(d[35]), "=f"(d[36]), "=f"(d[37]), "=f"(d[38]), "=f"(d[39]), "=f"(d[40]), "=f"(d[41]), "=f"(d[42]), "=f"(d[43]), "=f"(d[44]), "=f"(d[45]), "=f"(d[46]), "=f"(d[47]), "=f"(d[48]), "=f"(d[49]), "=f"(d[50]), "=f"(d[51]), "=f"(d[52]), "=f"(d[53]), "=f"(d[54]), "=f"(d[55]), "=f"(d[56]), "=f"(d[57]), "=f"(d[58]), "=f"(d[59]), "=f"(d[60]), "=f"(d[61]), "=f"(d[62]), "=f"(d[63]), "=f"(e[0]), "=f"(e[1]), "=f"(e[2]), "=f"(e[3]), "=f"(e[4]), "=f"(e[5]), "=f"(e[6]), "=f"(e[7]), "=f"(e[8]), "=f"(e[9]), "=f"(e[10]), "=f"(e[11]), "=f"(e[12]), "=f"(e[13]), "=f"(e[14]), "=f"(e[15]), "=f"(e[16]), "=f"(e[17]), "=f"(e[18]), "=f"(e[19]), "=f"(e[20]), "=f"(e[21]), "=f"(e[22]), "=f"(e[23]), "=f"(e[24]), "=f"(e[25]), "=f"(e[26]), "=f"(e[27]), "=f"(e[28]), "=f"(e[29]), "=f"(e[30]), "=f"(e[31])
    : "r"(a0), "r"(a1), "r"(a2), "r"(a3), "l"(db));
}

struct Maps {
  CUtensorMap x[2], k[2], v[2], wq[2], wo[2], wo2[2];
  const char* px[2];
};

__global__ void __cluster_dims__(2, 1, 1) __launch_bounds__(384, 1)
fused_gqa_kernel(const __grid_constant__ Maps maps, __nv_bfloat16* __restrict__ out) {
  extern __shared__ __align__(1024) unsigned char smem[];
  const uint32_t sbase = smem_u32(smem);
  const uint32_t full0 = sbase + BAR_OFF;
  const uint32_t empty0 = full0 + N_ITEMS * 8;
  const uint32_t ready0 = empty0 + N_ITEMS * 8;
  const uint32_t pub0 = ready0 + 2 * 8;

  const int tid = threadIdx.x;
  const int wg = tid >> 7;
  const int bid = blockIdx.x;
  const int bp = bid & 3;
  const int h = (bid >> 2) & 15;
  const int p = bid >> 6;

  if (tid == 0) {
#pragma unroll
    for (int i = 0; i < 5; i++) mbar_init(full0 + (WQ0 + i) * 8, 1);
#pragma unroll
    for (int i = 0; i < 4; i++) mbar_init(full0 + (X0 + i) * 8, 1);
    asm volatile("fence.mbarrier_init.release.cluster;" ::: "memory");
#pragma unroll
    for (int kc = 0; kc < 5; kc++) {
      if (kc < 4) {
        mbar_expect_tx(full0 + (X0 + kc) * 8, 16384);
        tma_load3(sbase + x_off(kc), &maps.x[p], 0, bp * 128, kc, full0 + (X0 + kc) * 8);
      }
      mbar_expect_tx(full0 + (WQ0 + kc) * 8, T32);
      tma_load3(sbase + wq_off(kc), &maps.wq[p], 0, kc * 64, h * 4, full0 + (WQ0 + kc) * 8);
    }
    TR(0, 56);
  } else if (tid >= 64 && tid < 96) {
    const char* base = maps.px[p] + (size_t)(bp * 128 + h * 8) * 1152;
#pragma unroll
    for (int i = 0; i < 3; i++)
      if ((tid & 31) + i * 32 < 72) l2_prefetch(base + ((tid & 31) + i * 32) * 128);
  } else if (tid == 32) {
    prefetch_tmap(&maps.k[p]);
    prefetch_tmap(&maps.v[p]);
    prefetch_tmap(&maps.wo[p]);
    prefetch_tmap(&maps.wo2[p]);
  } else if (tid >= 128) {
    const int i = tid - 128;
    if (i < N_ITEMS) {
      if (!(i < 5 || (i >= X0 && i < X0 + 4))) mbar_init(full0 + i * 8, 1);
    } else if (i >= 64 && i < 64 + N_ITEMS) {
      const int e = i - 64;
      const int q = e >= R0 + 17 ? e - R0 - 17 : e - R0;
      mbar_init(empty0 + e * 8, q >= 9 ? 4 : 8);
    } else if (i >= 128 && i < 128 + 2) {
      mbar_init(ready0 + (i - 128) * 8, 1);
    } else if (i >= 160 && i < 160 + 4) {
      mbar_init(pub0 + (i - 160) * 8, 4);
    }
    asm volatile("fence.mbarrier_init.release.cluster;" ::: "memory");
  }
  __syncthreads();
  if (tid == 0) TR(0, 57);

  if (wg == 0) {
    asm volatile("setmaxnreg.dec.sync.aligned.u32 24;");
    if (tid == 0) {
      const int kvrow = (2 * bp * 16 + h) * kSK;
      auto load_ring = [&](int pos) {
        const int bb = pos >= 17 ? 1 : 0, q = pos - bb * 17;
        const uint32_t fb = full0 + (R0 + pos) * 8;
        const uint32_t dst = sbase + ring_off(pos);
        if (q < 8 && q >= KV_INFLIGHT) mbar_wait(fb - KV_INFLIGHT * 8);
        TR(0, R0 + pos);
        mbar_expect_tx(fb, T32);
        if (q < 8) tma_load3(dst, (q & 1) ? &maps.v[p] : &maps.k[p], 0, kvrow + bb * 16 * kSK + (q >> 1) * 128, 0, fb);
        else if (q == 8) tma_load3(dst, &maps.wo2[p], 0, h * 256, 8, fb);
        else {
          const int c = (q - 9) >> 1, w = (q - 9) & 1;
          tma_load3(dst, &maps.wo[p], 0, h * 256 + ((c + 2 * w) & 3) * 64, w * 4, fb);
        }
      };
#pragma unroll 1
      for (int c = 0; c < 9; c++) {
        mbar_wait(empty0 + (X0 + c) * 8);
        if (c < 5) {
          mbar_expect_tx(full0 + (X0 + c + 4) * 8, 16384);
          tma_load3(sbase + x_off(c + 4), &maps.x[p], 0, bp * 128, c + 4, full0 + (X0 + c + 4) * 8);
        }
        if (c < 4) {
          TR(0, WQ0 + c + 5);
          mbar_expect_tx(full0 + (WQ0 + c + 5) * 8, T32);
          tma_load3(sbase + wq_off(c + 5), &maps.wq[p], 0, (c + 5) * 64, h * 4, full0 + (WQ0 + c + 5) * 8);
        } else if (c < 8) {
          load_ring(c - 4);
          if (c == 7) load_ring(4);
        } else {
          load_ring(5);
        }
      }
#pragma unroll 1
      for (int pos = 6; pos < N_RING; pos++) {
        mbar_wait(empty0 + (R0 + pos - 6) * 8);
        load_ring(pos);
      }
    } else if (tid == 96) {
      unsigned target[2];
#pragma unroll
      for (int bb = 0; bb < 2; bb++) {
        unsigned v;
        asm volatile("ld.relaxed.gpu.global.u32 %0, [%1];" : "=r"(v) : "l"(&g_cnt[(p * 8 + 2 * bp + bb) * 32]) : "memory");
        target[bb] = (v / 32u + 1u) * 32u;
      }
      mbar_wait(pub0 + 8);
#pragma unroll
      for (int bb = 0; bb < 2; bb++) {
        const unsigned* c = &g_cnt[(p * 8 + 2 * bp + bb) * 32];
        for (uint32_t it = 0; it < WAIT_LIMIT; ++it) {
          unsigned v;
          asm volatile("ld.acquire.gpu.global.u32 %0, [%1];" : "=r"(v) : "l"(c) : "memory");
          if ((int)(v - target[bb]) >= 0) break;
        }
        mbar_arrive(ready0 + bb * 8);
      }
    } else if (tid == 32 || tid == 64) {
      const int w = (tid >> 5) - 1;
#pragma unroll 1
      for (int bb = 0; bb < 2; bb++) {
        mbar_wait(pub0 + (w * 2 + bb) * 8);
        __threadfence();
        asm volatile("red.relaxed.gpu.global.add.u32 [%0], 1;" ::"l"(&g_cnt[(p * 8 + 2 * bp + bb) * 32]) : "memory");
      }
    }
  } else {
    asm volatile("setmaxnreg.inc.sync.aligned.u32 240;");
    const int w = wg - 1;
    const int t128 = tid & 127;
    const int lane = tid & 31;

    auto release = [&](int item) {
      __syncwarp();
      if (lane == 0) mbar_arrive(empty0 + item * 8);
    };

    TRC(0);
    const float cs = 0.08838834764831845f * 1.4426950408889634f;
    float s[64], o[64];
#pragma unroll
    for (int i = 0; i < 64; i++) s[i] = 0.f, o[i] = 0.f;
    uint32_t qf[32];
    uint4* park = reinterpret_cast<uint4*>(smem + PARK_OFF) + w * 1024 + t128;
    {
#pragma unroll 1
      for (int kc = 0; kc < 9; kc++) {
        mbar_wait(full0 + (X0 + kc) * 8);
        mbar_wait(full0 + (WQ0 + kc) * 8);
        if (kc == 0) TRC(1);
        const uint64_t da = make_desc(sbase + x_off(kc), 16, 1024);
        const uint64_t db = make_desc(sbase + wq_off(kc) + w * 16384, 8192, 1024);
        wg_fence();
#pragma unroll
        for (int ks = 0; ks < 4; ks++) {
          wgmma_ss_n128_tb(s, da + ks * 2, db + ks * 128, (kc | ks) != 0);
          wgmma_ss_n128_tb(o, da + 512 + ks * 2, db + ks * 128, (kc | ks) != 0);
        }
        wg_commit();
        wg_wait<0>();
        release(X0 + kc);
      }
      fence_regs(s);
      fence_regs(o);
#pragma unroll
      for (int i = 0; i < 32; i++) qf[i] = pack_bf16(s[2 * i], s[2 * i + 1]);
      named_bar(1, 256);
#pragma unroll
      for (int i = 0; i < 8; i++) park[i * 128] = pack8(o, i);
      TRC(2);
    }
#pragma unroll 1
    for (int bb = 0; bb < 2; bb++) {
      const int pos0 = bb * 17;
#pragma unroll
      for (int i = 0; i < 64; i++) o[i] = 0.f;
      float m0 = -INFINITY, m1 = -INFINITY, l0 = 0.f, l1 = 0.f;
#pragma unroll 1
      for (int t = 0; t < 4; t++) {
        const int pos = pos0 + t * 2;
        {
          const uint32_t base = sbase + ring_off(pos);
          mbar_wait(full0 + (R0 + pos) * 8);
          if (t == 0 && w == 1) named_bar(4, 256);
          const uint64_t db = make_desc(base, 16, 1024);
          wg_fence();
          wgmma_rs_n128_z(s, qf[0], qf[1], qf[2], qf[3], db);
#pragma unroll
          for (int ks = 1; ks < 8; ks++)
            wgmma_rs_n128(s, qf[4 * ks], qf[4 * ks + 1], qf[4 * ks + 2], qf[4 * ks + 3], db + (ks >> 2) * 1024 + (ks & 3) * 2, 1);
          wg_commit();
          wg_wait<0>();
          fence_regs(s);
          if (t == 0 && w == 0) named_arrive(4, 256);
          release(R0 + pos);
        }
        float mx0 = s[0], mx1 = s[2];
#pragma unroll
        for (int g = 0; g < 16; g++) {
          mx0 = fmaxf(mx0, fmaxf(s[4 * g], s[4 * g + 1]));
          mx1 = fmaxf(mx1, fmaxf(s[4 * g + 2], s[4 * g + 3]));
        }
        mx0 = fmaxf(mx0, __shfl_xor_sync(0xffffffffu, mx0, 1));
        mx0 = fmaxf(mx0, __shfl_xor_sync(0xffffffffu, mx0, 2));
        mx1 = fmaxf(mx1, __shfl_xor_sync(0xffffffffu, mx1, 1));
        mx1 = fmaxf(mx1, __shfl_xor_sync(0xffffffffu, mx1, 2));
        const float mn0 = fmaxf(m0, mx0), mn1 = fmaxf(m1, mx1);
        const float a0 = ex2((m0 - mn0) * cs), a1 = ex2((m1 - mn1) * cs);
        m0 = mn0;
        m1 = mn1;
        const float ms0 = mn0 * cs, ms1 = mn1 * cs;
        float rs0 = 0.f, rs1 = 0.f;
        uint32_t pf[32];
#pragma unroll
        for (int g = 0; g < 16; g++) {
          const float p0 = ex2(fmaf(s[4 * g], cs, -ms0));
          const float p1 = ex2(fmaf(s[4 * g + 1], cs, -ms0));
          const float p2 = ex2(fmaf(s[4 * g + 2], cs, -ms1));
          const float p3 = ex2(fmaf(s[4 * g + 3], cs, -ms1));
          rs0 += p0 + p1;
          rs1 += p2 + p3;
          pf[2 * g] = pack_bf16(p0, p1);
          pf[2 * g + 1] = pack_bf16(p2, p3);
        }
        l0 = l0 * a0 + rs0;
        l1 = l1 * a1 + rs1;
#pragma unroll
        for (int g = 0; g < 16; g++) {
          o[4 * g] *= a0;
          o[4 * g + 1] *= a0;
          o[4 * g + 2] *= a1;
          o[4 * g + 3] *= a1;
        }
        {
          const uint32_t base = sbase + ring_off(pos + 1);
          mbar_wait(full0 + (R0 + pos + 1) * 8);
          const uint64_t db = make_desc(base, 16384, 1024);
          wg_fence();
#pragma unroll
          for (int ks = 0; ks < 8; ks++)
            wgmma_rs_n128_tb(o, pf[4 * ks], pf[4 * ks + 1], pf[4 * ks + 2], pf[4 * ks + 3], db + ks * 128, 1);
          wg_commit();
          wg_wait<0>();
          fence_regs(o);
          if (t < 3) release(R0 + pos + 1);
          TRC(3 + bb * 10 + t);
        }
      }
      l0 += __shfl_xor_sync(0xffffffffu, l0, 1);
      l0 += __shfl_xor_sync(0xffffffffu, l0, 2);
      l1 += __shfl_xor_sync(0xffffffffu, l1, 1);
      l1 += __shfl_xor_sync(0xffffffffu, l1, 2);
      const float i0 = 1.f / l0, i1 = 1.f / l1;
      uint32_t own[32], oth[32];
#pragma unroll
      for (int i = 0; i < 16; i++) {
        own[2 * i] = pack_bf16(o[4 * i] * i0, o[4 * i + 1] * i0);
        own[2 * i + 1] = pack_bf16(o[4 * i + 2] * i1, o[4 * i + 3] * i1);
      }
      uint4* part = g_part + (size_t)(((p * 8 + 2 * bp + bb) * 16 + h) * 2 + w) * 20 * 128 + t128;
      {
        float acc[32];
        mbar_wait(full0 + (R0 + pos0 + 8) * 8);
        const uint64_t db = make_desc(sbase + ring_off(pos0 + 8) + w * 16384, 8192, 1024);
        wg_fence();
        wgmma_rs_n64_tb_z(acc, own[0], own[1], own[2], own[3], db);
#pragma unroll
        for (int ks = 1; ks < 8; ks++)
          wgmma_rs_n64_tb(acc, own[4 * ks], own[4 * ks + 1], own[4 * ks + 2], own[4 * ks + 3], db + ks * 128, 1);
        wg_commit();
        named_bar(1, 256);
        uint4* xb = reinterpret_cast<uint4*>(smem + ring_off(pos0 + 7)) + t128;
#pragma unroll
        for (int i = 0; i < 8; i++) xb[(w * 8 + i) * 128] = make_uint4(own[4 * i], own[4 * i + 1], own[4 * i + 2], own[4 * i + 3]);
        named_bar(1, 256);
#pragma unroll
        for (int i = 0; i < 8; i++) {
          const uint4 v = xb[((w ^ 1) * 8 + i) * 128];
          oth[4 * i] = v.x;
          oth[4 * i + 1] = v.y;
          oth[4 * i + 2] = v.z;
          oth[4 * i + 3] = v.w;
        }
        asm volatile("fence.proxy.async.shared::cta;" ::: "memory");
        release(R0 + pos0 + 7);
        wg_wait<0>();
        fence_regs(acc);
        release(R0 + pos0 + 8);
#pragma unroll
        for (int i = 0; i < 4; i++) __stcg(part + (16 + i) * 128, pack8(acc, i));
      }
      TRC(7 + bb * 10);
#pragma unroll
      for (int c = 0; c < 4; c++) {
        const int pos = pos0 + 9 + c * 2 + w;
        mbar_wait(full0 + (R0 + pos) * 8);
        const uint64_t db = make_desc(sbase + ring_off(pos), 8192, 1024);
        wg_fence();
#pragma unroll
        for (int ks = 0; ks < 4; ks++) {
          const int a = ((c & 1) * 4 + ks) * 4;
          if (c < 2) {
            if ((c | ks) == 0) wgmma_rs_n256_tb_z(s, o, own[a], own[a + 1], own[a + 2], own[a + 3], db);
            else wgmma_rs_n256_tb(s, o, own[a], own[a + 1], own[a + 2], own[a + 3], db + ks * 128, 1);
          } else {
            wgmma_rs_n256_tb(s, o, oth[a], oth[a + 1], oth[a + 2], oth[a + 3], db + ks * 128, 1);
          }
        }
        wg_commit();
        if (c > 0) {
          wg_wait<1>();
          release(R0 + pos - 2);
        }
      }
      wg_wait<0>();
      fence_regs(s);
      fence_regs(o);
      release(R0 + pos0 + 15 + w);
      TRC(8 + bb * 10);
#pragma unroll
      for (int i = 0; i < 8; i++) __stcg(part + i * 128, pack8(s, i));
#pragma unroll
      for (int i = 0; i < 8; i++) __stcg(part + (8 + i) * 128, pack8(o, i));
      __syncwarp();
      if (lane == 0) mbar_arrive(pub0 + (w * 2 + bb) * 8);
      TRC(9 + bb * 10);
#pragma unroll
      for (int i = 0; i < 8; i++) {
        const uint4 v = park[i * 128];
        qf[4 * i] = v.x;
        qf[4 * i + 1] = v.y;
        qf[4 * i + 2] = v.z;
        qf[4 * i + 3] = v.w;
      }
    }
    {
      const int row0 = (t128 >> 5) * 16 + (lane >> 2);
      auto sum_store = [&](const uint4* v, int n, __nv_bfloat16* op) {
        float a[8];
#pragma unroll
        for (int e = 0; e < 8; e++) a[e] = 0.f;
#pragma unroll
        for (int c = 0; c < n; c++) {
          a[0] += bf_lo(v[c].x);
          a[1] += bf_hi(v[c].x);
          a[2] += bf_lo(v[c].y);
          a[3] += bf_hi(v[c].y);
          a[4] += bf_lo(v[c].z);
          a[5] += bf_hi(v[c].z);
          a[6] += bf_lo(v[c].w);
          a[7] += bf_hi(v[c].w);
        }
        *reinterpret_cast<uint32_t*>(op) = pack_bf16(a[0], a[1]);
        *reinterpret_cast<uint32_t*>(op + 8 * 1152) = pack_bf16(a[2], a[3]);
        *reinterpret_cast<uint32_t*>(op + 8) = pack_bf16(a[4], a[5]);
        *reinterpret_cast<uint32_t*>(op + 8 * 1152 + 8) = pack_bf16(a[6], a[7]);
      };
      const bool extra = (t128 >> 5) == (h >> 2);
#pragma unroll
      for (int bb = 0; bb < 2; bb++) {
        mbar_wait(ready0 + bb * 8);
        TRC(20 + bb);
        const uint4* pr = g_part + (size_t)((p * 8 + 2 * bp + bb) * 16) * 2 * 20 * 128 + t128;
        __nv_bfloat16* orow = out + (size_t)((2 * bp + bb) * 64 + row0) * 1152 + p * 576 + (lane & 3) * 2;
        uint4 v[16];
#pragma unroll
        for (int c = 0; c < 16; c++) v[c] = __ldcg(pr + (size_t)((c * 2 + w) * 20 + h) * 128);
        if (extra && bb == w) {
          uint4 u[32];
#pragma unroll
          for (int c = 0; c < 32; c++) u[c] = __ldcg(pr + (size_t)(c * 20 + 16 + (h & 3)) * 128);
          sum_store(u, 32, orow + 512 + (h & 3) * 16);
        }
        sum_store(v, 16, orow + w * 256 + h * 16);
      }
    }
    TRC(22);
  }
}

typedef CUresult (*EncodeFn)(CUtensorMap*, CUtensorMapDataType, cuuint32_t, void*, const cuuint64_t*, const cuuint64_t*,
                             const cuuint32_t*, const cuuint32_t*, CUtensorMapInterleave, CUtensorMapSwizzle,
                             CUtensorMapL2promotion, CUtensorMapFloatOOBfill);

void encode3d(EncodeFn fn, CUtensorMap* m, void* ptr, uint64_t cols, uint64_t rows, uint32_t box_rows, uint32_t box_chunks) {
  cuuint64_t dims[3] = {64, rows, cols / 64};
  cuuint64_t strides[2] = {cols * 2, 128};
  cuuint32_t box[3] = {64, box_rows, box_chunks};
  cuuint32_t es[3] = {1, 1, 1};
  fn(m, CU_TENSOR_MAP_DATA_TYPE_BFLOAT16, 3, ptr, dims, strides, box, es, CU_TENSOR_MAP_INTERLEAVE_NONE,
     CU_TENSOR_MAP_SWIZZLE_128B, CU_TENSOR_MAP_L2_PROMOTION_L2_256B, CU_TENSOR_MAP_FLOAT_OOB_FILL_NONE);
}

}

extern "C" void kernel_launch(void* const* d_in, const int* in_sizes, int n_in, void* d_out, int out_size) {
  static EncodeFn fn = nullptr;
  if (!fn) {
    void* f = nullptr;
    cudaDriverEntryPointQueryResult st;
    cudaGetDriverEntryPoint("cuTensorMapEncodeTiled", &f, cudaEnableDefault, &st);
    fn = (EncodeFn)f;
    cudaFuncSetAttribute(fused_gqa_kernel, cudaFuncAttributeMaxDynamicSharedMemorySize, SMEM_BYTES);
  }
  Maps maps;
  for (int p = 0; p < 2; p++) {
    encode3d(fn, &maps.x[p], d_in[p * 5 + 0], kD, 512, 128, 1);
    encode3d(fn, &maps.k[p], d_in[p * 5 + 1], kDH, 8 * 16 * kSK, 128, 2);
    encode3d(fn, &maps.v[p], d_in[p * 5 + 2], kDH, 8 * 16 * kSK, 128, 2);
    encode3d(fn, &maps.wq[p], d_in[p * 5 + 3], kHQD, kD, 64, 4);
    encode3d(fn, &maps.wo[p], d_in[p * 5 + 4], kD, kHQD, 64, 4);
    encode3d(fn, &maps.wo2[p], d_in[p * 5 + 4], kD, kHQD, 256, 1);
    maps.px[p] = (const char*)d_in[p * 5 + 0];
  }
  fused_gqa_kernel<<<128, 384, SMEM_BYTES>>>(maps, (__nv_bfloat16*)d_out);
}
```

```cpp
#include <cuda_runtime.h>
#include <cuda_bf16.h>
#include <cuda.h>
#include <stdint.h>

namespace {

constexpr int kD = 576, kHQD = 4096, kSK = 512, kDH = 128;

constexpr int N_WQ = 9, N_X = 9, N_KV = 16, N_WO = 12;
constexpr int N_ITEMS = N_WQ + N_X + N_KV + N_WO;
constexpr int T32 = 32 * 1024;
constexpr int WO_BYTES = 24 * 1024;
constexpr int PARK_OFF = 192 * 1024;
constexpr int BAR_OFF = 224 * 1024;
constexpr int SMEM_BYTES = BAR_OFF + 2 * N_ITEMS * 8 + 256;
constexpr int WQ0 = 0, X0 = N_WQ, KV0 = X0 + N_X, WO0 = KV0 + N_KV;
#define KV_INFLIGHT 2

__device__ __forceinline__ int wq_off(int kc) { return (kc < 5 ? kc : kc - 5) * T32; }
__device__ __forceinline__ int x_off(int kc) { return ((kc & 2) ? 5 * T32 : PARK_OFF) + (kc & 1) * 16384; }
__device__ __forceinline__ int ring_off(int pos) { return (int)((0x352104u >> ((pos % 6) * 4)) & 15u) * T32; }
__device__ __forceinline__ int kv_off(int n) { return ring_off(n); }
__device__ __forceinline__ int wo_off(int m) { return (int)((0x547832106547ull >> (m * 4)) & 15ull) * WO_BYTES; }

__device__ uint4 g_part[16 * 16 * 36 * 128];
__device__ unsigned int g_cnt[16 * 4 * 32];

#define TR(role, ev)
#define TRC(ev)
constexpr uint32_t WAIT_CYCLES = 1u << 20;
constexpr uint32_t WAIT_LIMIT = 1u << 12;
__device__ __forceinline__ uint32_t smem_u32(const void* p) { return (uint32_t)__cvta_generic_to_shared(p); }
__device__ __forceinline__ void mbar_init(uint32_t bar, uint32_t cnt) {
  asm volatile("mbarrier.init.shared::cta.b64 [%0], %1;" ::"r"(bar), "r"(cnt) : "memory");
}
__device__ __forceinline__ void mbar_expect_tx(uint32_t bar, uint32_t bytes) {
  asm volatile("mbarrier.arrive.expect_tx.shared::cta.b64 _, [%0], %1;" ::"r"(bar), "r"(bytes) : "memory");
}
__device__ __forceinline__ void mbar_arrive(uint32_t bar) {
  asm volatile("mbarrier.arrive.shared::cta.b64 _, [%0];" ::"r"(bar) : "memory");
}
__device__ __forceinline__ bool mbar_try(uint32_t bar, uint32_t parity) {
  uint32_t ok;
  asm volatile(
      "{\n.reg .pred p;\nmbarrier.try_wait.parity.shared::cta.b64 p, [%1], %2;\nselp.u32 %0, 1, 0, p;\n}\n"
      : "=r"(ok)
      : "r"(bar), "r"(parity)
      : "memory");
  return ok != 0;
}
__device__ __forceinline__ void mbar_wait(uint32_t bar) {
  if (mbar_try(bar, 0)) return;
  const uint32_t t0 = (uint32_t)clock();
  while (!mbar_try(bar, 0))
    if ((uint32_t)clock() - t0 > WAIT_CYCLES) break;
}
__device__ __forceinline__ void tma_load3(uint32_t dst, const CUtensorMap* tm, int c0, int c1, int c2, uint32_t bar) {
  asm volatile(
      "cp.async.bulk.tensor.3d.shared::cluster.global.mbarrier::complete_tx::bytes [%0], [%1, {%3, %4, %5}], [%2];" ::"r"(dst),
      "l"(tm), "r"(bar), "r"(c0), "r"(c1), "r"(c2)
      : "memory");
}
__device__ __forceinline__ void l2_prefetch(const void* p) { asm volatile("prefetch.global.L2 [%0];" ::"l"(p) : "memory"); }
__device__ __forceinline__ void prefetch_tmap(const CUtensorMap* tm) {
  asm volatile("prefetch.tensormap [%0];" ::"l"(tm) : "memory");
}
__device__ __forceinline__ void named_bar(int id, int n) { asm volatile("bar.sync %0, %1;" ::"r"(id), "r"(n) : "memory"); }
__device__ __forceinline__ void named_arrive(int id, int n) { asm volatile("bar.arrive %0, %1;" ::"r"(id), "r"(n) : "memory"); }
__device__ __forceinline__ void wg_fence() { asm volatile("wgmma.fence.sync.aligned;" ::: "memory"); }
__device__ __forceinline__ void wg_commit() { asm volatile("wgmma.commit_group.sync.aligned;" ::: "memory"); }
template <int N>
__device__ __forceinline__ void wg_wait() { asm volatile("wgmma.wait_group.sync.aligned %0;" ::"n"(N) : "memory"); }
template <int N>
__device__ __forceinline__ void fence_regs(float (&d)[N]) {
#pragma unroll
  for (int i = 0; i < N; i++) asm volatile("" : "+f"(d[i])::"memory");
}
__device__ __forceinline__ void fence_regs32(float (&d)[64]) {
#pragma unroll
  for (int i = 0; i < 32; i++) asm volatile("" : "+f"(d[i])::"memory");
}
__device__ __forceinline__ uint64_t make_desc(uint32_t addr, uint32_t lbo, uint32_t sbo) {
  return (uint64_t)((addr & 0x3FFFF) >> 4) | ((uint64_t)(lbo >> 4) << 16) | ((uint64_t)(sbo >> 4) << 32) | (1ull << 62);
}
__device__ __forceinline__ uint32_t pack_bf16(float lo, float hi) {
  uint32_t r;
  asm("cvt.rn.bf16x2.f32 %0, %1, %2;" : "=r"(r) : "f"(hi), "f"(lo));
  return r;
}
__device__ __forceinline__ float ex2(float x) {
  float y;
  asm("ex2.approx.ftz.f32 %0, %1;" : "=f"(y) : "f"(x));
  return y;
}
__device__ __forceinline__ float bf_lo(uint32_t v) { return __uint_as_float(v << 16); }
__device__ __forceinline__ float bf_hi(uint32_t v) { return __uint_as_float(v & 0xffff0000u); }
template <int N>
__device__ __forceinline__ uint4 pack8(const float (&a)[N], int i) {
  return make_uint4(pack_bf16(a[8 * i], a[8 * i + 1]), pack_bf16(a[8 * i + 2], a[8 * i + 3]), pack_bf16(a[8 * i + 4], a[8 * i + 5]),
                    pack_bf16(a[8 * i + 6], a[8 * i + 7]));
}

__device__ __forceinline__ void wgmma_ss_n128_tb(float (&d)[64], uint64_t da, uint64_t db, int scale_d) {
  asm volatile("{\n.reg .pred p;\nsetp.ne.b32 p, %66, 0;\n"
    "wgmma.mma_async.sync.aligned.m64n128k16.f32.bf16.bf16 {%0, %1, %2, %3, %4, %5, %6, %7, %8, %9, %10, %11, %12, %13, %14, %15, %16, %17, %18, %19, %20, %21, %22, %23, %24, %25, %26, %27, %28, %29, %30, %31, %32, %33, %34, %35, %36, %37, %38, %39, %40, %41, %42, %43, %44, %45, %46, %47, %48, %49, %50, %51, %52, %53, %54, %55, %56, %57, %58, %59, %60, %61, %62, %63}, %64, %65, p, 1, 1, 0, 1;\n}\n"
    : "+f"(d[0]), "+f"(d[1]), "+f"(d[2]), "+f"(d[3]), "+f"(d[4]), "+f"(d[5]), "+f"(d[6]), "+f"(d[7]), "+f"(d[8]), "+f"(d[9]), "+f"(d[10]), "+f"(d[11]), "+f"(d[12]), "+f"(d[13]), "+f"(d[14]), "+f"(d[15]), "+f"(d[16]), "+f"(d[17]), "+f"(d[18]), "+f"(d[19]), "+f"(d[20]), "+f"(d[21]), "+f"(d[22]), "+f"(d[23]), "+f"(d[24]), "+f"(d[25]), "+f"(d[26]), "+f"(d[27]), "+f"(d[28]), "+f"(d[29]), "+f"(d[30]), "+f"(d[31]), "+f"(d[32]), "+f"(d[33]), "+f"(d[34]), "+f"(d[35]), "+f"(d[36]), "+f"(d[37]), "+f"(d[38]), "+f"(d[39]), "+f"(d[40]), "+f"(d[41]), "+f"(d[42]), "+f"(d[43]), "+f"(d[44]), "+f"(d[45]), "+f"(d[46]), "+f"(d[47]), "+f"(d[48]), "+f"(d[49]), "+f"(d[50]), "+f"(d[51]), "+f"(d[52]), "+f"(d[53]), "+f"(d[54]), "+f"(d[55]), "+f"(d[56]), "+f"(d[57]), "+f"(d[58]), "+f"(d[59]), "+f"(d[60]), "+f"(d[61]), "+f"(d[62]), "+f"(d[63])
    : "l"(da), "l"(db), "r"(scale_d));
}

__device__ __forceinline__ void wgmma_rs_n128(float (&d)[64], uint32_t a0, uint32_t a1, uint32_t a2, uint32_t a3, uint64_t db, int scale_d) {
  asm volatile("{\n.reg .pred p;\nsetp.ne.b32 p, %69, 0;\n"
    "wgmma.mma_async.sync.aligned.m64n128k16.f32.bf16.bf16 {%0, %1, %2, %3, %4, %5, %6, %7, %8, %9, %10, %11, %12, %13, %14, %15, %16, %17, %18, %19, %20, %21, %22, %23, %24, %25, %26, %27, %28, %29, %30, %31, %32, %33, %34, %35, %36, %37, %38, %39, %40, %41, %42, %43, %44, %45, %46, %47, %48, %49, %50, %51, %52, %53, %54, %55, %56, %57, %58, %59, %60, %61, %62, %63}, {%64, %65, %66, %67}, %68, p, 1, 1, 0;\n}\n"
    : "+f"(d[0]), "+f"(d[1]), "+f"(d[2]), "+f"(d[3]), "+f"(d[4]), "+f"(d[5]), "+f"(d[6]), "+f"(d[7]), "+f"(d[8]), "+f"(d[9]), "+f"(d[10]), "+f"(d[11]), "+f"(d[12]), "+f"(d[13]), "+f"(d[14]), "+f"(d[15]), "+f"(d[16]), "+f"(d[17]), "+f"(d[18]), "+f"(d[19]), "+f"(d[20]), "+f"(d[21]), "+f"(d[22]), "+f"(d[23]), "+f"(d[24]), "+f"(d[25]), "+f"(d[26]), "+f"(d[27]), "+f"(d[28]), "+f"(d[29]), "+f"(d[30]), "+f"(d[31]), "+f"(d[32]), "+f"(d[33]), "+f"(d[34]), "+f"(d[35]), "+f"(d[36]), "+f"(d[37]), "+f"(d[38]), "+f"(d[39]), "+f"(d[40]), "+f"(d[41]), "+f"(d[42]), "+f"(d[43]), "+f"(d[44]), "+f"(d[45]), "+f"(d[46]), "+f"(d[47]), "+f"(d[48]), "+f"(d[49]), "+f"(d[50]), "+f"(d[51]), "+f"(d[52]), "+f"(d[53]), "+f"(d[54]), "+f"(d[55]), "+f"(d[56]), "+f"(d[57]), "+f"(d[58]), "+f"(d[59]), "+f"(d[60]), "+f"(d[61]), "+f"(d[62]), "+f"(d[63])
    : "r"(a0), "r"(a1), "r"(a2), "r"(a3), "l"(db), "r"(scale_d));
}

__device__ __forceinline__ void wgmma_rs_n128_tb(float (&d)[64], uint32_t a0, uint32_t a1, uint32_t a2, uint32_t a3, uint64_t db, int scale_d) {
  asm volatile("{\n.reg .pred p;\nsetp.ne.b32 p, %69, 0;\n"
    "wgmma.mma_async.sync.aligned.m64n128k16.f32.bf16.bf16 {%0, %1, %2, %3, %4, %5, %6, %7, %8, %9, %10, %11, %12, %13, %14, %15, %16, %17, %18, %19, %20, %21, %22, %23, %24, %25, %26, %27, %28, %29, %30, %31, %32, %33, %34, %35, %36, %37, %38, %39, %40, %41, %42, %43, %44, %45, %46, %47, %48, %49, %50, %51, %52, %53, %54, %55, %56, %57, %58, %59, %60, %61, %62, %63}, {%64, %65, %66, %67}, %68, p, 1, 1, 1;\n}\n"
    : "+f"(d[0]), "+f"(d[1]), "+f"(d[2]), "+f"(d[3]), "+f"(d[4]), "+f"(d[5]), "+f"(d[6]), "+f"(d[7]), "+f"(d[8]), "+f"(d[9]), "+f"(d[10]), "+f"(d[11]), "+f"(d[12]), "+f"(d[13]), "+f"(d[14]), "+f"(d[15]), "+f"(d[16]), "+f"(d[17]), "+f"(d[18]), "+f"(d[19]), "+f"(d[20]), "+f"(d[21]), "+f"(d[22]), "+f"(d[23]), "+f"(d[24]), "+f"(d[25]), "+f"(d[26]), "+f"(d[27]), "+f"(d[28]), "+f"(d[29]), "+f"(d[30]), "+f"(d[31]), "+f"(d[32]), "+f"(d[33]), "+f"(d[34]), "+f"(d[35]), "+f"(d[36]), "+f"(d[37]), "+f"(d[38]), "+f"(d[39]), "+f"(d[40]), "+f"(d[41]), "+f"(d[42]), "+f"(d[43]), "+f"(d[44]), "+f"(d[45]), "+f"(d[46]), "+f"(d[47]), "+f"(d[48]), "+f"(d[49]), "+f"(d[50]), "+f"(d[51]), "+f"(d[52]), "+f"(d[53]), "+f"(d[54]), "+f"(d[55]), "+f"(d[56]), "+f"(d[57]), "+f"(d[58]), "+f"(d[59]), "+f"(d[60]), "+f"(d[61]), "+f"(d[62]), "+f"(d[63])
    : "r"(a0), "r"(a1), "r"(a2), "r"(a3), "l"(db), "r"(scale_d));
}

__device__ __forceinline__ void wgmma_rs_n32_tb(float (&d)[16], uint32_t a0, uint32_t a1, uint32_t a2, uint32_t a3, uint64_t db, int scale_d) {
  asm volatile("{\n.reg .pred p;\nsetp.ne.b32 p, %21, 0;\n"
    "wgmma.mma_async.sync.aligned.m64n32k16.f32.bf16.bf16 {%0, %1, %2, %3, %4, %5, %6, %7, %8, %9, %10, %11, %12, %13, %14, %15}, {%16, %17, %18, %19}, %20, p, 1, 1, 1;\n}\n"
    : "+f"(d[0]), "+f"(d[1]), "+f"(d[2]), "+f"(d[3]), "+f"(d[4]), "+f"(d[5]), "+f"(d[6]), "+f"(d[7]), "+f"(d[8]), "+f"(d[9]), "+f"(d[10]), "+f"(d[11]), "+f"(d[12]), "+f"(d[13]), "+f"(d[14]), "+f"(d[15])
    : "r"(a0), "r"(a1), "r"(a2), "r"(a3), "l"(db), "r"(scale_d));
}

__device__ __forceinline__ void wgmma_rs_n64_tb(float (&d)[32], uint32_t a0, uint32_t a1, uint32_t a2, uint32_t a3, uint64_t db, int scale_d) {
  asm volatile("{\n.reg .pred p;\nsetp.ne.b32 p, %37, 0;\n"
    "wgmma.mma_async.sync.aligned.m64n64k16.f32.bf16.bf16 {%0, %1, %2, %3, %4, %5, %6, %7, %8, %9, %10, %11, %12, %13, %14, %15, %16, %17, %18, %19, %20, %21, %22, %23, %24, %25, %26, %27, %28, %29, %30, %31}, {%32, %33, %34, %35}, %36, p, 1, 1, 1;\n}\n"
    : "+f"(d[0]), "+f"(d[1]), "+f"(d[2]), "+f"(d[3]), "+f"(d[4]), "+f"(d[5]), "+f"(d[6]), "+f"(d[7]), "+f"(d[8]), "+f"(d[9]), "+f"(d[10]), "+f"(d[11]), "+f"(d[12]), "+f"(d[13]), "+f"(d[14]), "+f"(d[15]), "+f"(d[16]), "+f"(d[17]), "+f"(d[18]), "+f"(d[19]), "+f"(d[20]), "+f"(d[21]), "+f"(d[22]), "+f"(d[23]), "+f"(d[24]), "+f"(d[25]), "+f"(d[26]), "+f"(d[27]), "+f"(d[28]), "+f"(d[29]), "+f"(d[30]), "+f"(d[31])
    : "r"(a0), "r"(a1), "r"(a2), "r"(a3), "l"(db), "r"(scale_d));
}

__device__ __forceinline__ void wgmma_rs_n256_tb(float (&d)[64], float (&e)[64], uint32_t a0, uint32_t a1, uint32_t a2, uint32_t a3, uint64_t db, int scale_d) {
  asm volatile("{\n.reg .pred p;\nsetp.ne.b32 p, %133, 0;\n"
    "wgmma.mma_async.sync.aligned.m64n256k16.f32.bf16.bf16 {%0, %1, %2, %3, %4, %5, %6, %7, %8, %9, %10, %11, %12, %13, %14, %15, %16, %17, %18, %19, %20, %21, %22, %23, %24, %25, %26, %27, %28, %29, %30, %31, %32, %33, %34, %35, %36, %37, %38, %39, %40, %41, %42, %43, %44, %45, %46, %47, %48, %49, %50, %51, %52, %53, %54, %55, %56, %57, %58, %59, %60, %61, %62, %63, %64, %65, %66, %67, %68, %69, %70, %71, %72, %73, %74, %75, %76, %77, %78, %79, %80, %81, %82, %83, %84, %85, %86, %87, %88, %89, %90, %91, %92, %93, %94, %95, %96, %97, %98, %99, %100, %101, %102, %103, %104, %105, %106, %107, %108, %109, %110, %111, %112, %113, %114, %115, %116, %117, %118, %119, %120, %121, %122, %123, %124, %125, %126, %127}, {%128, %129, %130, %131}, %132, p, 1, 1, 1;\n}\n"
    : "+f"(d[0]), "+f"(d[1]), "+f"(d[2]), "+f"(d[3]), "+f"(d[4]), "+f"(d[5]), "+f"(d[6]), "+f"(d[7]), "+f"(d[8]), "+f"(d[9]), "+f"(d[10]), "+f"(d[11]), "+f"(d[12]), "+f"(d[13]), "+f"(d[14]), "+f"(d[15]), "+f"(d[16]), "+f"(d[17]), "+f"(d[18]), "+f"(d[19]), "+f"(d[20]), "+f"(d[21]), "+f"(d[22]), "+f"(d[23]), "+f"(d[24]), "+f"(d[25]), "+f"(d[26]), "+f"(d[27]), "+f"(d[28]), "+f"(d[29]), "+f"(d[30]), "+f"(d[31]), "+f"(d[32]), "+f"(d[33]), "+f"(d[34]), "+f"(d[35]), "+f"(d[36]), "+f"(d[37]), "+f"(d[38]), "+f"(d[39]), "+f"(d[40]), "+f"(d[41]), "+f"(d[42]), "+f"(d[43]), "+f"(d[44]), "+f"(d[45]), "+f"(d[46]), "+f"(d[47]), "+f"(d[48]), "+f"(d[49]), "+f"(d[50]), "+f"(d[51]), "+f"(d[52]), "+f"(d[53]), "+f"(d[54]), "+f"(d[55]), "+f"(d[56]), "+f"(d[57]), "+f"(d[58]), "+f"(d[59]), "+f"(d[60]), "+f"(d[61]), "+f"(d[62]), "+f"(d[63]), "+f"(e[0]), "+f"(e[1]), "+f"(e[2]), "+f"(e[3]), "+f"(e[4]), "+f"(e[5]), "+f"(e[6]), "+f"(e[7]), "+f"(e[8]), "+f"(e[9]), "+f"(e[10]), "+f"(e[11]), "+f"(e[12]), "+f"(e[13]), "+f"(e[14]), "+f"(e[15]), "+f"(e[16]), "+f"(e[17]), "+f"(e[18]), "+f"(e[19]), "+f"(e[20]), "+f"(e[21]), "+f"(e[22]), "+f"(e[23]), "+f"(e[24]), "+f"(e[25]), "+f"(e[26]), "+f"(e[27]), "+f"(e[28]), "+f"(e[29]), "+f"(e[30]), "+f"(e[31]), "+f"(e[32]), "+f"(e[33]), "+f"(e[34]), "+f"(e[35]), "+f"(e[36]), "+f"(e[37]), "+f"(e[38]), "+f"(e[39]), "+f"(e[40]), "+f"(e[41]), "+f"(e[42]), "+f"(e[43]), "+f"(e[44]), "+f"(e[45]), "+f"(e[46]), "+f"(e[47]), "+f"(e[48]), "+f"(e[49]), "+f"(e[50]), "+f"(e[51]), "+f"(e[52]), "+f"(e[53]), "+f"(e[54]), "+f"(e[55]), "+f"(e[56]), "+f"(e[57]), "+f"(e[58]), "+f"(e[59]), "+f"(e[60]), "+f"(e[61]), "+f"(e[62]), "+f"(e[63])
    : "r"(a0), "r"(a1), "r"(a2), "r"(a3), "l"(db), "r"(scale_d));
}

__device__ __forceinline__ void wgmma_rs_n128_z(float (&d)[64], uint32_t a0, uint32_t a1, uint32_t a2, uint32_t a3, uint64_t db) {
  asm volatile("{\n.reg .pred p;\nsetp.ne.b32 p, 0, 0;\n"
    "wgmma.mma_async.sync.aligned.m64n128k16.f32.bf16.bf16 {%0, %1, %2, %3, %4, %5, %6, %7, %8, %9, %10, %11, %12, %13, %14, %15, %16, %17, %18, %19, %20, %21, %22, %23, %24, %25, %26, %27, %28, %29, %30, %31, %32, %33, %34, %35, %36, %37, %38, %39, %40, %41, %42, %43, %44, %45, %46, %47, %48, %49, %50, %51, %52, %53, %54, %55, %56, %57, %58, %59, %60, %61, %62, %63}, {%64, %65, %66, %67}, %68, p, 1, 1, 0;\n}\n"
    : "=f"(d[0]), "=f"(d[1]), "=f"(d[2]), "=f"(d[3]), "=f"(d[4]), "=f"(d[5]), "=f"(d[6]), "=f"(d[7]), "=f"(d[8]), "=f"(d[9]), "=f"(d[10]), "=f"(d[11]), "=f"(d[12]), "=f"(d[13]), "=f"(d[14]), "=f"(d[15]), "=f"(d[16]), "=f"(d[17]), "=f"(d[18]), "=f"(d[19]), "=f"(d[20]), "=f"(d[21]), "=f"(d[22]), "=f"(d[23]), "=f"(d[24]), "=f"(d[25]), "=f"(d[26]), "=f"(d[27]), "=f"(d[28]), "=f"(d[29]), "=f"(d[30]), "=f"(d[31]), "=f"(d[32]), "=f"(d[33]), "=f"(d[34]), "=f"(d[35]), "=f"(d[36]), "=f"(d[37]), "=f"(d[38]), "=f"(d[39]), "=f"(d[40]), "=f"(d[41]), "=f"(d[42]), "=f"(d[43]), "=f"(d[44]), "=f"(d[45]), "=f"(d[46]), "=f"(d[47]), "=f"(d[48]), "=f"(d[49]), "=f"(d[50]), "=f"(d[51]), "=f"(d[52]), "=f"(d[53]), "=f"(d[54]), "=f"(d[55]), "=f"(d[56]), "=f"(d[57]), "=f"(d[58]), "=f"(d[59]), "=f"(d[60]), "=f"(d[61]), "=f"(d[62]), "=f"(d[63])
    : "r"(a0), "r"(a1), "r"(a2), "r"(a3), "l"(db));
}

__device__ __forceinline__ void wgmma_rs_n64_tb_z(float (&d)[32], uint32_t a0, uint32_t a1, uint32_t a2, uint32_t a3, uint64_t db) {
  asm volatile("{\n.reg .pred p;\nsetp.ne.b32 p, 0, 0;\n"
    "wgmma.mma_async.sync.aligned.m64n64k16.f32.bf16.bf16 {%0, %1, %2, %3, %4, %5, %6, %7, %8, %9, %10, %11, %12, %13, %14, %15, %16, %17, %18, %19, %20, %21, %22, %23, %24, %25, %26, %27, %28, %29, %30, %31}, {%32, %33, %34, %35}, %36, p, 1, 1, 1;\n}\n"
    : "=f"(d[0]), "=f"(d[1]), "=f"(d[2]), "=f"(d[3]), "=f"(d[4]), "=f"(d[5]), "=f"(d[6]), "=f"(d[7]), "=f"(d[8]), "=f"(d[9]), "=f"(d[10]), "=f"(d[11]), "=f"(d[12]), "=f"(d[13]), "=f"(d[14]), "=f"(d[15]), "=f"(d[16]), "=f"(d[17]), "=f"(d[18]), "=f"(d[19]), "=f"(d[20]), "=f"(d[21]), "=f"(d[22]), "=f"(d[23]), "=f"(d[24]), "=f"(d[25]), "=f"(d[26]), "=f"(d[27]), "=f"(d[28]), "=f"(d[29]), "=f"(d[30]), "=f"(d[31])
    : "r"(a0), "r"(a1), "r"(a2), "r"(a3), "l"(db));
}

__device__ __forceinline__ void wgmma_rs_n256_tb_z(float (&d)[64], float (&e)[64], uint32_t a0, uint32_t a1, uint32_t a2, uint32_t a3, uint64_t db) {
  asm volatile("{\n.reg .pred p;\nsetp.ne.b32 p, 0, 0;\n"
    "wgmma.mma_async.sync.aligned.m64n256k16.f32.bf16.bf16 {%0, %1, %2, %3, %4, %5, %6, %7, %8, %9, %10, %11, %12, %13, %14, %15, %16, %17, %18, %19, %20, %21, %22, %23, %24, %25, %26, %27, %28, %29, %30, %31, %32, %33, %34, %35, %36, %37, %38, %39, %40, %41, %42, %43, %44, %45, %46, %47, %48, %49, %50, %51, %52, %53, %54, %55, %56, %57, %58, %59, %60, %61, %62, %63, %64, %65, %66, %67, %68, %69, %70, %71, %72, %73, %74, %75, %76, %77, %78, %79, %80, %81, %82, %83, %84, %85, %86, %87, %88, %89, %90, %91, %92, %93, %94, %95, %96, %97, %98, %99, %100, %101, %102, %103, %104, %105, %106, %107, %108, %109, %110, %111, %112, %113, %114, %115, %116, %117, %118, %119, %120, %121, %122, %123, %124, %125, %126, %127}, {%128, %129, %130, %131}, %132, p, 1, 1, 1;\n}\n"
    : "=f"(d[0]), "=f"(d[1]), "=f"(d[2]), "=f"(d[3]), "=f"(d[4]), "=f"(d[5]), "=f"(d[6]), "=f"(d[7]), "=f"(d[8]), "=f"(d[9]), "=f"(d[10]), "=f"(d[11]), "=f"(d[12]), "=f"(d[13]), "=f"(d[14]), "=f"(d[15]), "=f"(d[16]), "=f"(d[17]), "=f"(d[18]), "=f"(d[19]), "=f"(d[20]), "=f"(d[21]), "=f"(d[22]), "=f"(d[23]), "=f"(d[24]), "=f"(d[25]), "=f"(d[26]), "=f"(d[27]), "=f"(d[28]), "=f"(d[29]), "=f"(d[30]), "=f"(d[31]), "=f"(d[32]), "=f"(d[33]), "=f"(d[34]), "=f"(d[35]), "=f"(d[36]), "=f"(d[37]), "=f"(d[38]), "=f"(d[39]), "=f"(d[40]), "=f"(d[41]), "=f"(d[42]), "=f"(d[43]), "=f"(d[44]), "=f"(d[45]), "=f"(d[46]), "=f"(d[47]), "=f"(d[48]), "=f"(d[49]), "=f"(d[50]), "=f"(d[51]), "=f"(d[52]), "=f"(d[53]), "=f"(d[54]), "=f"(d[55]), "=f"(d[56]), "=f"(d[57]), "=f"(d[58]), "=f"(d[59]), "=f"(d[60]), "=f"(d[61]), "=f"(d[62]), "=f"(d[63]), "=f"(e[0]), "=f"(e[1]), "=f"(e[2]), "=f"(e[3]), "=f"(e[4]), "=f"(e[5]), "=f"(e[6]), "=f"(e[7]), "=f"(e[8]), "=f"(e[9]), "=f"(e[10]), "=f"(e[11]), "=f"(e[12]), "=f"(e[13]), "=f"(e[14]), "=f"(e[15]), "=f"(e[16]), "=f"(e[17]), "=f"(e[18]), "=f"(e[19]), "=f"(e[20]), "=f"(e[21]), "=f"(e[22]), "=f"(e[23]), "=f"(e[24]), "=f"(e[25]), "=f"(e[26]), "=f"(e[27]), "=f"(e[28]), "=f"(e[29]), "=f"(e[30]), "=f"(e[31]), "=f"(e[32]), "=f"(e[33]), "=f"(e[34]), "=f"(e[35]), "=f"(e[36]), "=f"(e[37]), "=f"(e[38]), "=f"(e[39]), "=f"(e[40]), "=f"(e[41]), "=f"(e[42]), "=f"(e[43]), "=f"(e[44]), "=f"(e[45]), "=f"(e[46]), "=f"(e[47]), "=f"(e[48]), "=f"(e[49]), "=f"(e[50]), "=f"(e[51]), "=f"(e[52]), "=f"(e[53]), "=f"(e[54]), "=f"(e[55]), "=f"(e[56]), "=f"(e[57]), "=f"(e[58]), "=f"(e[59]), "=f"(e[60]), "=f"(e[61]), "=f"(e[62]), "=f"(e[63])
    : "r"(a0), "r"(a1), "r"(a2), "r"(a3), "l"(db));
}

__device__ __forceinline__ void wgmma_rs_n192_tb(float (&d)[64], float (&e)[64], uint32_t a0, uint32_t a1, uint32_t a2, uint32_t a3, uint64_t db) {
  asm volatile("{\n.reg .pred p;\nsetp.eq.b32 p, 0, 0;\n"
    "wgmma.mma_async.sync.aligned.m64n192k16.f32.bf16.bf16 {%0, %1, %2, %3, %4, %5, %6, %7, %8, %9, %10, %11, %12, %13, %14, %15, %16, %17, %18, %19, %20, %21, %22, %23, %24, %25, %26, %27, %28, %29, %30, %31, %32, %33, %34, %35, %36, %37, %38, %39, %40, %41, %42, %43, %44, %45, %46, %47, %48, %49, %50, %51, %52, %53, %54, %55, %56, %57, %58, %59, %60, %61, %62, %63, %64, %65, %66, %67, %68, %69, %70, %71, %72, %73, %74, %75, %76, %77, %78, %79, %80, %81, %82, %83, %84, %85, %86, %87, %88, %89, %90, %91, %92, %93, %94, %95}, {%96, %97, %98, %99}, %100, p, 1, 1, 1;\n}\n"
    : "+f"(d[0]), "+f"(d[1]), "+f"(d[2]), "+f"(d[3]), "+f"(d[4]), "+f"(d[5]), "+f"(d[6]), "+f"(d[7]), "+f"(d[8]), "+f"(d[9]), "+f"(d[10]), "+f"(d[11]), "+f"(d[12]), "+f"(d[13]), "+f"(d[14]), "+f"(d[15]), "+f"(d[16]), "+f"(d[17]), "+f"(d[18]), "+f"(d[19]), "+f"(d[20]), "+f"(d[21]), "+f"(d[22]), "+f"(d[23]), "+f"(d[24]), "+f"(d[25]), "+f"(d[26]), "+f"(d[27]), "+f"(d[28]), "+f"(d[29]), "+f"(d[30]), "+f"(d[31]), "+f"(d[32]), "+f"(d[33]), "+f"(d[34]), "+f"(d[35]), "+f"(d[36]), "+f"(d[37]), "+f"(d[38]), "+f"(d[39]), "+f"(d[40]), "+f"(d[41]), "+f"(d[42]), "+f"(d[43]), "+f"(d[44]), "+f"(d[45]), "+f"(d[46]), "+f"(d[47]), "+f"(d[48]), "+f"(d[49]), "+f"(d[50]), "+f"(d[51]), "+f"(d[52]), "+f"(d[53]), "+f"(d[54]), "+f"(d[55]), "+f"(d[56]), "+f"(d[57]), "+f"(d[58]), "+f"(d[59]), "+f"(d[60]), "+f"(d[61]), "+f"(d[62]), "+f"(d[63]), "+f"(e[0]), "+f"(e[1]), "+f"(e[2]), "+f"(e[3]), "+f"(e[4]), "+f"(e[5]), "+f"(e[6]), "+f"(e[7]), "+f"(e[8]), "+f"(e[9]), "+f"(e[10]), "+f"(e[11]), "+f"(e[12]), "+f"(e[13]), "+f"(e[14]), "+f"(e[15]), "+f"(e[16]), "+f"(e[17]), "+f"(e[18]), "+f"(e[19]), "+f"(e[20]), "+f"(e[21]), "+f"(e[22]), "+f"(e[23]), "+f"(e[24]), "+f"(e[25]), "+f"(e[26]), "+f"(e[27]), "+f"(e[28]), "+f"(e[29]), "+f"(e[30]), "+f"(e[31])
    : "r"(a0), "r"(a1), "r"(a2), "r"(a3), "l"(db));
}

__device__ __forceinline__ void wgmma_rs_n192_tb_z(float (&d)[64], float (&e)[64], uint32_t a0, uint32_t a1, uint32_t a2, uint32_t a3, uint64_t db) {
  asm volatile("{\n.reg .pred p;\nsetp.ne.b32 p, 0, 0;\n"
    "wgmma.mma_async.sync.aligned.m64n192k16.f32.bf16.bf16 {%0, %1, %2, %3, %4, %5, %6, %7, %8, %9, %10, %11, %12, %13, %14, %15, %16, %17, %18, %19, %20, %21, %22, %23, %24, %25, %26, %27, %28, %29, %30, %31, %32, %33, %34, %35, %36, %37, %38, %39, %40, %41, %42, %43, %44, %45, %46, %47, %48, %49, %50, %51, %52, %53, %54, %55, %56, %57, %58, %59, %60, %61, %62, %63, %64, %65, %66, %67, %68, %69, %70, %71, %72, %73, %74, %75, %76, %77, %78, %79, %80, %81, %82, %83, %84, %85, %86, %87, %88, %89, %90, %91, %92, %93, %94, %95}, {%96, %97, %98, %99}, %100, p, 1, 1, 1;\n}\n"
    : "=f"(d[0]), "=f"(d[1]), "=f"(d[2]), "=f"(d[3]), "=f"(d[4]), "=f"(d[5]), "=f"(d[6]), "=f"(d[7]), "=f"(d[8]), "=f"(d[9]), "=f"(d[10]), "=f"(d[11]), "=f"(d[12]), "=f"(d[13]), "=f"(d[14]), "=f"(d[15]), "=f"(d[16]), "=f"(d[17]), "=f"(d[18]), "=f"(d[19]), "=f"(d[20]), "=f"(d[21]), "=f"(d[22]), "=f"(d[23]), "=f"(d[24]), "=f"(d[25]), "=f"(d[26]), "=f"(d[27]), "=f"(d[28]), "=f"(d[29]), "=f"(d[30]), "=f"(d[31]), "=f"(d[32]), "=f"(d[33]), "=f"(d[34]), "=f"(d[35]), "=f"(d[36]), "=f"(d[37]), "=f"(d[38]), "=f"(d[39]), "=f"(d[40]), "=f"(d[41]), "=f"(d[42]), "=f"(d[43]), "=f"(d[44]), "=f"(d[45]), "=f"(d[46]), "=f"(d[47]), "=f"(d[48]), "=f"(d[49]), "=f"(d[50]), "=f"(d[51]), "=f"(d[52]), "=f"(d[53]), "=f"(d[54]), "=f"(d[55]), "=f"(d[56]), "=f"(d[57]), "=f"(d[58]), "=f"(d[59]), "=f"(d[60]), "=f"(d[61]), "=f"(d[62]), "=f"(d[63]), "=f"(e[0]), "=f"(e[1]), "=f"(e[2]), "=f"(e[3]), "=f"(e[4]), "=f"(e[5]), "=f"(e[6]), "=f"(e[7]), "=f"(e[8]), "=f"(e[9]), "=f"(e[10]), "=f"(e[11]), "=f"(e[12]), "=f"(e[13]), "=f"(e[14]), "=f"(e[15]), "=f"(e[16]), "=f"(e[17]), "=f"(e[18]), "=f"(e[19]), "=f"(e[20]), "=f"(e[21]), "=f"(e[22]), "=f"(e[23]), "=f"(e[24]), "=f"(e[25]), "=f"(e[26]), "=f"(e[27]), "=f"(e[28]), "=f"(e[29]), "=f"(e[30]), "=f"(e[31])
    : "r"(a0), "r"(a1), "r"(a2), "r"(a3), "l"(db));
}

struct Maps {
  CUtensorMap x[2], k[2], v[2], wq[2], wo[2];
  const char *px[2], *pwo[2];
};

__device__ __forceinline__ void poll_tiles(int tile, const unsigned (&target)[3], uint32_t ready) {
#pragma unroll
  for (int pn = 0; pn < 3; pn++) {
    const unsigned* c = &g_cnt[(tile * 4 + pn) * 32];
    for (uint32_t it = 0; it < WAIT_LIMIT; ++it) {
      unsigned v;
      asm volatile("ld.acquire.gpu.global.u32 %0, [%1];" : "=r"(v) : "l"(c) : "memory");
      if ((int)(v - target[pn]) >= 0) break;
    }
    mbar_arrive(ready + pn * 8);
  }
}
__device__ __forceinline__ void read_targets(int tile, unsigned (&target)[3]) {
#pragma unroll
  for (int pn = 0; pn < 3; pn++) {
    unsigned v;
    asm volatile("ld.relaxed.gpu.global.u32 %0, [%1];" : "=r"(v) : "l"(&g_cnt[(tile * 4 + pn) * 32]) : "memory");
    target[pn] = (v / 16u + 1u) * 16u;
  }
}

__global__ void __cluster_dims__(2, 1, 1) __launch_bounds__(384, 1)
fused_gqa_kernel(const __grid_constant__ Maps maps, __nv_bfloat16* __restrict__ out) {
  extern __shared__ __align__(1024) unsigned char smem[];
  const uint32_t sbase = smem_u32(smem);
  const uint32_t full0 = sbase + BAR_OFF;
  const uint32_t empty0 = full0 + N_ITEMS * 8;
  const uint32_t ready0 = empty0 + N_ITEMS * 8;
  const uint32_t pub0 = ready0 + 6 * 8;

  const int tid = threadIdx.x;
  const int wg = tid >> 7;
  const int bid = blockIdx.x;
  const int bp = bid & 3;
  const int h = (bid >> 2) & 15;
  const int p = bid >> 6;

  if (tid == 0) {
#pragma unroll
    for (int i = 0; i < 5; i++) mbar_init(full0 + (WQ0 + i) * 8, 1);
#pragma unroll
    for (int i = 0; i < 4; i++) mbar_init(full0 + (X0 + i) * 8, 1);
    asm volatile("fence.mbarrier_init.release.cluster;" ::: "memory");
#pragma unroll
    for (int kc = 0; kc < 5; kc++) {
      if (kc < 4) {
        mbar_expect_tx(full0 + (X0 + kc) * 8, 16384);
        tma_load3(sbase + x_off(kc), &maps.x[p], 0, bp * 128, kc, full0 + (X0 + kc) * 8);
      }
      mbar_expect_tx(full0 + (WQ0 + kc) * 8, T32);
      tma_load3(sbase + wq_off(kc), &maps.wq[p], 0, kc * 64, h * 4, full0 + (WQ0 + kc) * 8);
    }
    TR(0, 56);
  } else if (tid >= 64 && tid < 96) {
    const char* base = maps.px[p] + (size_t)(bp * 128 + h * 8) * 1152;
#pragma unroll
    for (int i = 0; i < 3; i++)
      if ((tid & 31) + i * 32 < 72) l2_prefetch(base + ((tid & 31) + i * 32) * 128);
  } else if (tid == 32) {
    prefetch_tmap(&maps.k[p]);
    prefetch_tmap(&maps.v[p]);
    prefetch_tmap(&maps.wo[p]);
  } else if (tid >= 128) {
    const int i = tid - 128;
    if (i < N_ITEMS) {
      if (!(i < 5 || (i >= X0 && i < X0 + 4))) mbar_init(full0 + i * 8, 1);
    } else if (i >= 64 && i < 64 + N_ITEMS) {
      mbar_init(empty0 + (i - 64) * 8, i == 64 + WQ0 ? 4 : 8);
    } else if (i >= 128 && i < 128 + 6) {
      mbar_init(ready0 + (i - 128) * 8, 1);
    } else if (i >= 160 && i < 160 + 6) {
      mbar_init(pub0 + (i - 160) * 8, 4);
    }
    asm volatile("fence.mbarrier_init.release.cluster;" ::: "memory");
  }
  __syncthreads();
  if (tid == 0) TR(0, 57);

  if (wg == 0) {
    asm volatile("setmaxnreg.dec.sync.aligned.u32 24;");
    if (tid == 0) {
      const int kvrow = (2 * bp * 16 + h) * kSK;
      auto load_kv = [&](int n) {
        if (n >= KV_INFLIGHT) mbar_wait(full0 + (KV0 + n - KV_INFLIGHT) * 8);
        const uint32_t fb = full0 + (KV0 + n) * 8;
        TR(0, KV0 + n);
        mbar_expect_tx(fb, T32);
        tma_load3(sbase + kv_off(n), (n & 1) ? &maps.v[p] : &maps.k[p], 0, kvrow + (n >> 3) * 16 * kSK + ((n & 7) >> 1) * 128, 0, fb);
      };
#pragma unroll 1
      for (int c = 0; c < 9; c++) {
        mbar_wait(empty0 + (X0 + c) * 8);
        if (c < 5) {
          mbar_expect_tx(full0 + (X0 + c + 4) * 8, 16384);
          tma_load3(sbase + x_off(c + 4), &maps.x[p], 0, bp * 128, c + 4, full0 + (X0 + c + 4) * 8);
        }
        if (c < 4) {
          TR(0, WQ0 + c + 5);
          mbar_expect_tx(full0 + (WQ0 + c + 5) * 8, T32);
          tma_load3(sbase + wq_off(c + 5), &maps.wq[p], 0, (c + 5) * 64, h * 4, full0 + (WQ0 + c + 5) * 8);
        } else if (c < 8) {
          load_kv(c - 4);
          if (c == 7) load_kv(4);
        } else {
          load_kv(5);
        }
      }
#pragma unroll 1
      for (int n = 6; n < N_KV; n++) {
        mbar_wait(empty0 + (KV0 + n - 6) * 8);
        load_kv(n);
      }
#pragma unroll 1
      for (int m = 0; m < N_WO; m++) {
        const int dep = m >= 9 ? WO0 + m - 9 : (m == 8 ? WQ0 : KV0 + 10 + (int)((0x55432210u >> (m * 4)) & 15u));
        mbar_wait(empty0 + dep * 8);
        const uint32_t fb = full0 + (WO0 + m) * 8;
        TR(0, WO0 + m);
        mbar_expect_tx(fb, WO_BYTES);
        tma_load3(sbase + wo_off(m), &maps.wo[p], 0, h * 256 + (m & 3) * 64, (m >> 2) * 3, fb);
      }
    } else if (tid == 96 || tid == 112) {
      const int w = (tid >> 4) & 1;
      unsigned target[3];
      read_targets(p * 8 + 2 * bp + w, target);
      mbar_wait(pub0 + w * 24);
      poll_tiles(p * 8 + 2 * bp + w, target, ready0 + w * 24);
    } else if (tid >= 32 && tid < 96) {
      const int w = (tid >> 5) - 1;
      if (tid & 31) return;
      const int tile = p * 8 + 2 * bp + w;
#pragma unroll 1
      for (int e = 0; e < 3; e++) {
        mbar_wait(pub0 + (w * 3 + e) * 8);
        __threadfence();
        asm volatile("red.relaxed.gpu.global.add.u32 [%0], 1;" ::"l"(&g_cnt[(tile * 4 + e) * 32]) : "memory");
      }
    }
  } else {
    asm volatile("setmaxnreg.inc.sync.aligned.u32 240;");
    const int w = wg - 1;
    const int t128 = tid & 127;
    const int lane = tid & 31;

    auto release = [&](int item) {
      __syncwarp();
      if (lane == 0) mbar_arrive(empty0 + item * 8);
    };

    TRC(0);
    const float cs = 0.08838834764831845f * 1.4426950408889634f;
    float s[64], o[64];
#pragma unroll
    for (int i = 0; i < 64; i++) s[i] = 0.f, o[i] = 0.f;
    uint32_t qf[32];
    uint4* park = reinterpret_cast<uint4*>(smem + PARK_OFF) + w * 1024 + t128;
    {
#pragma unroll 1
      for (int kc = 0; kc < 9; kc++) {
        mbar_wait(full0 + (X0 + kc) * 8);
        mbar_wait(full0 + (WQ0 + kc) * 8);
        if (kc == 0) TRC(1);
        const uint64_t da = make_desc(sbase + x_off(kc), 16, 1024);
        const uint64_t db = make_desc(sbase + wq_off(kc) + w * 16384, 8192, 1024);
        wg_fence();
#pragma unroll
        for (int ks = 0; ks < 4; ks++) {
          wgmma_ss_n128_tb(s, da + ks * 2, db + ks * 128, (kc | ks) != 0);
          wgmma_ss_n128_tb(o, da + 512 + ks * 2, db + ks * 128, (kc | ks) != 0);
        }
        wg_commit();
        wg_wait<0>();
        release(X0 + kc);
      }
      fence_regs(s);
      fence_regs(o);
#pragma unroll
      for (int i = 0; i < 32; i++) qf[i] = pack_bf16(s[2 * i], s[2 * i + 1]);
      named_bar(1, 256);
#pragma unroll
      for (int i = 0; i < 8; i++) park[i * 128] = pack8(o, i);
      TRC(2);
    }
#pragma unroll 1
    for (int bb = 0; bb < 2; bb++) {
#pragma unroll
      for (int i = 0; i < 64; i++) o[i] = 0.f;
      float m0 = -INFINITY, m1 = -INFINITY, l0 = 0.f, l1 = 0.f;
#pragma unroll 1
      for (int t = 0; t < 4; t++) {
        const int n = bb * 8 + t * 2;
        {
          const uint32_t base = sbase + kv_off(n);
          mbar_wait(full0 + (KV0 + n) * 8);
          if (n == 0 && w == 1) named_bar(4, 256);
          const uint64_t db = make_desc(base, 16, 1024);
          wg_fence();
          wgmma_rs_n128_z(s, qf[0], qf[1], qf[2], qf[3], db);
#pragma unroll
          for (int ks = 1; ks < 8; ks++)
            wgmma_rs_n128(s, qf[4 * ks], qf[4 * ks + 1], qf[4 * ks + 2], qf[4 * ks + 3], db + (ks >> 2) * 1024 + (ks & 3) * 2, 1);
          wg_commit();
          wg_wait<0>();
          fence_regs(s);
          if (n == 0 && w == 0) named_arrive(4, 256);
          release(KV0 + n);
        }
        float mx0 = s[0], mx1 = s[2];
#pragma unroll
        for (int g = 0; g < 16; g++) {
          mx0 = fmaxf(mx0, fmaxf(s[4 * g], s[4 * g + 1]));
          mx1 = fmaxf(mx1, fmaxf(s[4 * g + 2], s[4 * g + 3]));
        }
        mx0 = fmaxf(mx0, __shfl_xor_sync(0xffffffffu, mx0, 1));
        mx0 = fmaxf(mx0, __shfl_xor_sync(0xffffffffu, mx0, 2));
        mx1 = fmaxf(mx1, __shfl_xor_sync(0xffffffffu, mx1, 1));
        mx1 = fmaxf(mx1, __shfl_xor_sync(0xffffffffu, mx1, 2));
        const float mn0 = fmaxf(m0, mx0), mn1 = fmaxf(m1, mx1);
        const float a0 = ex2((m0 - mn0) * cs), a1 = ex2((m1 - mn1) * cs);
        m0 = mn0;
        m1 = mn1;
        const float ms0 = mn0 * cs, ms1 = mn1 * cs;
        float rs0 = 0.f, rs1 = 0.f;
        uint32_t pf[32];
#pragma unroll
        for (int g = 0; g < 16; g++) {
          const float p0 = ex2(fmaf(s[4 * g], cs, -ms0));
          const float p1 = ex2(fmaf(s[4 * g + 1], cs, -ms0));
          const float p2 = ex2(fmaf(s[4 * g + 2], cs, -ms1));
          const float p3 = ex2(fmaf(s[4 * g + 3], cs, -ms1));
          rs0 += p0 + p1;
          rs1 += p2 + p3;
          pf[2 * g] = pack_bf16(p0, p1);
          pf[2 * g + 1] = pack_bf16(p2, p3);
        }
        l0 = l0 * a0 + rs0;
        l1 = l1 * a1 + rs1;
#pragma unroll
        for (int g = 0; g < 16; g++) {
          o[4 * g] *= a0;
          o[4 * g + 1] *= a0;
          o[4 * g + 2] *= a1;
          o[4 * g + 3] *= a1;
        }
        {
          const uint32_t base = sbase + kv_off(n + 1);
          mbar_wait(full0 + (KV0 + n + 1) * 8);
          const uint64_t db = make_desc(base, 16384, 1024);
          wg_fence();
#pragma unroll
          for (int ks = 0; ks < 8; ks++)
            wgmma_rs_n128_tb(o, pf[4 * ks], pf[4 * ks + 1], pf[4 * ks + 2], pf[4 * ks + 3], db + ks * 128, 1);
          wg_commit();
          wg_wait<0>();
          fence_regs(o);
          release(KV0 + n + 1);
          TRC(3 + bb * 5 + t);
        }
      }
      l0 += __shfl_xor_sync(0xffffffffu, l0, 1);
      l0 += __shfl_xor_sync(0xffffffffu, l0, 2);
      l1 += __shfl_xor_sync(0xffffffffu, l1, 1);
      l1 += __shfl_xor_sync(0xffffffffu, l1, 2);
      const float i0 = 1.f / l0, i1 = 1.f / l1;
      if (bb == 0) {
#pragma unroll
        for (int i = 0; i < 8; i++) {
          const uint4 v = park[i * 128];
          qf[4 * i] = v.x;
          qf[4 * i + 1] = v.y;
          qf[4 * i + 2] = v.z;
          qf[4 * i + 3] = v.w;
          park[i * 128] = make_uint4(pack_bf16(o[8 * i] * i0, o[8 * i + 1] * i0), pack_bf16(o[8 * i + 2] * i1, o[8 * i + 3] * i1),
                                     pack_bf16(o[8 * i + 4] * i0, o[8 * i + 5] * i0), pack_bf16(o[8 * i + 6] * i1, o[8 * i + 7] * i1));
        }
        if (w == 1) named_arrive(5, 256);
      } else {
#pragma unroll
        for (int i = 0; i < 16; i++) {
          qf[2 * i] = pack_bf16(o[4 * i] * i0, o[4 * i + 1] * i0);
          qf[2 * i + 1] = pack_bf16(o[4 * i + 2] * i1, o[4 * i + 3] * i1);
        }
      }
    }
    uint32_t af[64];
    {
      const uint4* src = reinterpret_cast<const uint4*>(smem + PARK_OFF) + t128;
      if (w == 0) {
        named_bar(5, 256);
#pragma unroll
        for (int i = 0; i < 16; i++) {
          const uint4 v = src[i * 128];
          af[4 * i] = v.x;
          af[4 * i + 1] = v.y;
          af[4 * i + 2] = v.z;
          af[4 * i + 3] = v.w;
        }
#pragma unroll
        for (int i = 0; i < 8; i++) park[i * 128] = make_uint4(qf[4 * i], qf[4 * i + 1], qf[4 * i + 2], qf[4 * i + 3]);
        asm volatile("fence.proxy.async.shared::cta;" ::: "memory");
        named_arrive(1, 256);
      } else {
        named_bar(1, 256);
#pragma unroll
        for (int i = 0; i < 8; i++) {
          const uint4 v = src[i * 128];
          af[4 * i] = v.x;
          af[4 * i + 1] = v.y;
          af[4 * i + 2] = v.z;
          af[4 * i + 3] = v.w;
        }
#pragma unroll
        for (int i = 0; i < 32; i++) af[32 + i] = qf[i];
        asm volatile("fence.proxy.async.shared::cta;" ::: "memory");
        release(WQ0);
      }
    }
    TRC(12);
    const int tile = p * 8 + 2 * bp + w;
    uint4* part = g_part + (size_t)(tile * 16 + h) * 36 * 128 + t128;
#pragma unroll
    for (int pn = 0; pn < 3; pn++) {
#pragma unroll
      for (int kc = 0; kc < 4; kc++) {
        const int m = pn * 4 + kc;
        mbar_wait(full0 + (WO0 + m) * 8);
        const uint64_t db = make_desc(sbase + wo_off(m), 8192, 1024);
        wg_fence();
#pragma unroll
        for (int ks = 0; ks < 4; ks++) {
          const int a = (kc * 4 + ks) * 4;
          if ((kc | ks) == 0) wgmma_rs_n192_tb_z(s, o, af[a], af[a + 1], af[a + 2], af[a + 3], db);
          else wgmma_rs_n192_tb(s, o, af[a], af[a + 1], af[a + 2], af[a + 3], db + ks * 128);
        }
        wg_commit();
        if (kc > 0) {
          wg_wait<1>();
          if (m - 1 < 3) release(WO0 + m - 1);
        }
      }
      wg_wait<0>();
      fence_regs(s);
      fence_regs32(o);
      TRC(13 + pn * 2);
#pragma unroll
      for (int i = 0; i < 8; i++) __stcg(part + (pn * 12 + i) * 128, pack8(s, i));
#pragma unroll
      for (int i = 0; i < 4; i++) __stcg(part + (pn * 12 + 8 + i) * 128, pack8(o, i));
      __syncwarp();
      if (lane == 0) mbar_arrive(pub0 + (w * 3 + pn) * 8);
      TRC(14 + pn * 2);
    }
    if (t128 < 96) {
      const int u = h * 96 + t128;
      const int slot = u >> 7, thr = u & 127;
      const int row0 = (thr >> 5) * 16 + ((thr & 31) >> 2);
      __nv_bfloat16* orow = out + (size_t)((2 * bp + w) * 64 + row0) * 1152 + p * 576 + slot * 16 + (thr & 3) * 2;
      const uint4* pr = g_part + (size_t)(tile * 16) * 36 * 128 + slot * 128 + thr;
      uint4 v[3][16];
#pragma unroll
      for (int pn = 0; pn < 3; pn++) {
        mbar_wait(ready0 + (w * 3 + pn) * 8);
        TRC(19 + pn);
#pragma unroll
        for (int c = 0; c < 16; c++) v[pn][c] = __ldcg(pr + (size_t)(c * 36 + pn * 12) * 128);
      }
#pragma unroll
      for (int pn = 0; pn < 3; pn++) {
        float a[8];
#pragma unroll
        for (int e = 0; e < 8; e++) a[e] = 0.f;
#pragma unroll
        for (int c = 0; c < 16; c++) {
          a[0] += bf_lo(v[pn][c].x);
          a[1] += bf_hi(v[pn][c].x);
          a[2] += bf_lo(v[pn][c].y);
          a[3] += bf_hi(v[pn][c].y);
          a[4] += bf_lo(v[pn][c].z);
          a[5] += bf_hi(v[pn][c].z);
          a[6] += bf_lo(v[pn][c].w);
          a[7] += bf_hi(v[pn][c].w);
        }
        __nv_bfloat16* op = orow + pn * 192;
        *reinterpret_cast<uint32_t*>(op) = pack_bf16(a[0], a[1]);
        *reinterpret_cast<uint32_t*>(op + 8 * 1152) = pack_bf16(a[2], a[3]);
        *reinterpret_cast<uint32_t*>(op + 8) = pack_bf16(a[4], a[5]);
        *reinterpret_cast<uint32_t*>(op + 8 * 1152 + 8) = pack_bf16(a[6], a[7]);
      }
    }
    TRC(22);
  }
}

typedef CUresult (*EncodeFn)(CUtensorMap*, CUtensorMapDataType, cuuint32_t, void*, const cuuint64_t*, const cuuint64_t*,
                             const cuuint32_t*, const cuuint32_t*, CUtensorMapInterleave, CUtensorMapSwizzle,
                             CUtensorMapL2promotion, CUtensorMapFloatOOBfill);

void encode3d(EncodeFn fn, CUtensorMap* m, void* ptr, uint64_t cols, uint64_t rows, uint32_t box_rows, uint32_t box_chunks) {
  cuuint64_t dims[3] = {64, rows, cols / 64};
  cuuint64_t strides[2] = {cols * 2, 128};
  cuuint32_t box[3] = {64, box_rows, box_chunks};
  cuuint32_t es[3] = {1, 1, 1};
  fn(m, CU_TENSOR_MAP_DATA_TYPE_BFLOAT16, 3, ptr, dims, strides, box, es, CU_TENSOR_MAP_INTERLEAVE_NONE,
     CU_TENSOR_MAP_SWIZZLE_128B, CU_TENSOR_MAP_L2_PROMOTION_L2_256B, CU_TENSOR_MAP_FLOAT_OOB_FILL_NONE);
}

}

extern "C" void kernel_launch(void* const* d_in, const int* in_sizes, int n_in, void* d_out, int out_size) {
  static EncodeFn fn = nullptr;
  if (!fn) {
    void* f = nullptr;
    cudaDriverEntryPointQueryResult st;
    cudaGetDriverEntryPoint("cuTensorMapEncodeTiled", &f, cudaEnableDefault, &st);
    fn = (EncodeFn)f;
    cudaFuncSetAttribute(fused_gqa_kernel, cudaFuncAttributeMaxDynamicSharedMemorySize, SMEM_BYTES);
  }
  Maps maps;
  for (int p = 0; p < 2; p++) {
    encode3d(fn, &maps.x[p], d_in[p * 5 + 0], kD, 512, 128, 1);
    encode3d(fn, &maps.k[p], d_in[p * 5 + 1], kDH, 8 * 16 * kSK, 128, 2);
    encode3d(fn, &maps.v[p], d_in[p * 5 + 2], kDH, 8 * 16 * kSK, 128, 2);
    encode3d(fn, &maps.wq[p], d_in[p * 5 + 3], kHQD, kD, 64, 4);
    encode3d(fn, &maps.wo[p], d_in[p * 5 + 4], kD, kHQD, 64, 3);
    maps.px[p] = (const char*)d_in[p * 5 + 0];
    maps.pwo[p] = (const char*)d_in[p * 5 + 4];
  }
  fused_gqa_kernel<<<128, 384, SMEM_BYTES>>>(maps, (__nv_bfloat16*)d_out);
}
```

```cpp
#include <cuda_runtime.h>
#include <cuda_bf16.h>
#include <cuda.h>
#include <stdint.h>

namespace {

constexpr int kD = 576, kHQD = 4096, kSK = 512, kDH = 128;

constexpr int N_WQ = 9, N_X = 9, N_KV = 16, N_WO = 12;
constexpr int N_ITEMS = N_WQ + N_X + N_KV + N_WO;
constexpr int T32 = 32 * 1024;
constexpr int WO_BYTES = 24 * 1024;
constexpr int PARK_OFF = 192 * 1024;
constexpr int BAR_OFF = 224 * 1024;
constexpr int SMEM_BYTES = BAR_OFF + 2 * N_ITEMS * 8 + 256;
constexpr int WQ0 = 0, X0 = N_WQ, KV0 = X0 + N_X, WO0 = KV0 + N_KV;
#define KV0_AT 1
#define KV_INFLIGHT 2

__device__ __forceinline__ int wq_off(int kc) { return (kc & 3) * T32; }
__device__ __forceinline__ int x_off(int kc) { return ((kc & 2) ? 5 * T32 : PARK_OFF) + (kc & 1) * 16384; }
__device__ __forceinline__ int ring_off(int pos) { return (int)((0x053214u >> ((pos % 6) * 4)) & 15u) * T32; }
__device__ __forceinline__ int kv_off(int n) { return ring_off(n); }
__device__ __forceinline__ int wo_off(int m) { return (int)((0x607854321607ull >> (m * 4)) & 15ull) * WO_BYTES; }

__device__ uint4 g_part[16 * 16 * 36 * 128];
__device__ unsigned int g_cnt[16 * 4 * 32];

#define TR(role, ev)
#define TRC(ev)
constexpr uint32_t WAIT_CYCLES = 1u << 20;
constexpr uint32_t WAIT_LIMIT = 1u << 12;
__device__ __forceinline__ uint32_t smem_u32(const void* p) { return (uint32_t)__cvta_generic_to_shared(p); }
__device__ __forceinline__ void mbar_init(uint32_t bar, uint32_t cnt) {
  asm volatile("mbarrier.init.shared::cta.b64 [%0], %1;" ::"r"(bar), "r"(cnt) : "memory");
}
__device__ __forceinline__ void mbar_expect_tx(uint32_t bar, uint32_t bytes) {
  asm volatile("mbarrier.arrive.expect_tx.shared::cta.b64 _, [%0], %1;" ::"r"(bar), "r"(bytes) : "memory");
}
__device__ __forceinline__ void mbar_arrive(uint32_t bar) {
  asm volatile("mbarrier.arrive.shared::cta.b64 _, [%0];" ::"r"(bar) : "memory");
}
__device__ __forceinline__ bool mbar_try(uint32_t bar, uint32_t parity) {
  uint32_t ok;
  asm volatile(
      "{\n.reg .pred p;\nmbarrier.try_wait.parity.shared::cta.b64 p, [%1], %2;\nselp.u32 %0, 1, 0, p;\n}\n"
      : "=r"(ok)
      : "r"(bar), "r"(parity)
      : "memory");
  return ok != 0;
}
__device__ __forceinline__ void mbar_wait(uint32_t bar) {
  if (mbar_try(bar, 0)) return;
  const uint32_t t0 = (uint32_t)clock();
  while (!mbar_try(bar, 0))
    if ((uint32_t)clock() - t0 > WAIT_CYCLES) break;
}
__device__ __forceinline__ void tma_load3(uint32_t dst, const CUtensorMap* tm, int c0, int c1, int c2, uint32_t bar) {
  asm volatile(
      "cp.async.bulk.tensor.3d.shared::cluster.global.mbarrier::complete_tx::bytes [%0], [%1, {%3, %4, %5}], [%2];" ::"r"(dst),
      "l"(tm), "r"(bar), "r"(c0), "r"(c1), "r"(c2)
      : "memory");
}
__device__ __forceinline__ void l2_prefetch(const void* p) { asm volatile("prefetch.global.L2 [%0];" ::"l"(p) : "memory"); }
__device__ __forceinline__ void prefetch_tmap(const CUtensorMap* tm) {
  asm volatile("prefetch.tensormap [%0];" ::"l"(tm) : "memory");
}
__device__ __forceinline__ void named_bar(int id, int n) { asm volatile("bar.sync %0, %1;" ::"r"(id), "r"(n) : "memory"); }
__device__ __forceinline__ void named_arrive(int id, int n) { asm volatile("bar.arrive %0, %1;" ::"r"(id), "r"(n) : "memory"); }
__device__ __forceinline__ void wg_fence() { asm volatile("wgmma.fence.sync.aligned;" ::: "memory"); }
__device__ __forceinline__ void wg_commit() { asm volatile("wgmma.commit_group.sync.aligned;" ::: "memory"); }
template <int N>
__device__ __forceinline__ void wg_wait() { asm volatile("wgmma.wait_group.sync.aligned %0;" ::"n"(N) : "memory"); }
template <int N>
__device__ __forceinline__ void fence_regs(float (&d)[N]) {
#pragma unroll
  for (int i = 0; i < N; i++) asm volatile("" : "+f"(d[i])::"memory");
}
__device__ __forceinline__ void fence_regs32(float (&d)[64]) {
#pragma unroll
  for (int i = 0; i < 32; i++) asm volatile("" : "+f"(d[i])::"memory");
}
__device__ __forceinline__ uint64_t make_desc(uint32_t addr, uint32_t lbo, uint32_t sbo) {
  return (uint64_t)((addr & 0x3FFFF) >> 4) | ((uint64_t)(lbo >> 4) << 16) | ((uint64_t)(sbo >> 4) << 32) | (1ull << 62);
}
__device__ __forceinline__ uint32_t pack_bf16(float lo, float hi) {
  uint32_t r;
  asm("cvt.rn.bf16x2.f32 %0, %1, %2;" : "=r"(r) : "f"(hi), "f"(lo));
  return r;
}
__device__ __forceinline__ float ex2(float x) {
  float y;
  asm("ex2.approx.ftz.f32 %0, %1;" : "=f"(y) : "f"(x));
  return y;
}
__device__ __forceinline__ float bf_lo(uint32_t v) { return __uint_as_float(v << 16); }
__device__ __forceinline__ float bf_hi(uint32_t v) { return __uint_as_float(v & 0xffff0000u); }
template <int N>
__device__ __forceinline__ uint4 pack8(const float (&a)[N], int i) {
  return make_uint4(pack_bf16(a[8 * i], a[8 * i + 1]), pack_bf16(a[8 * i + 2], a[8 * i + 3]), pack_bf16(a[8 * i + 4], a[8 * i + 5]),
                    pack_bf16(a[8 * i + 6], a[8 * i + 7]));
}

__device__ __forceinline__ void wgmma_ss_n128_tb(float (&d)[64], uint64_t da, uint64_t db, int scale_d) {
  asm volatile("{\n.reg .pred p;\nsetp.ne.b32 p, %66, 0;\n"
    "wgmma.mma_async.sync.aligned.m64n128k16.f32.bf16.bf16 {%0, %1, %2, %3, %4, %5, %6, %7, %8, %9, %10, %11, %12, %13, %14, %15, %16, %17, %18, %19, %20, %21, %22, %23, %24, %25, %26, %27, %28, %29, %30, %31, %32, %33, %34, %35, %36, %37, %38, %39, %40, %41, %42, %43, %44, %45, %46, %47, %48, %49, %50, %51, %52, %53, %54, %55, %56, %57, %58, %59, %60, %61, %62, %63}, %64, %65, p, 1, 1, 0, 1;\n}\n"
    : "+f"(d[0]), "+f"(d[1]), "+f"(d[2]), "+f"(d[3]), "+f"(d[4]), "+f"(d[5]), "+f"(d[6]), "+f"(d[7]), "+f"(d[8]), "+f"(d[9]), "+f"(d[10]), "+f"(d[11]), "+f"(d[12]), "+f"(d[13]), "+f"(d[14]), "+f"(d[15]), "+f"(d[16]), "+f"(d[17]), "+f"(d[18]), "+f"(d[19]), "+f"(d[20]), "+f"(d[21]), "+f"(d[22]), "+f"(d[23]), "+f"(d[24]), "+f"(d[25]), "+f"(d[26]), "+f"(d[27]), "+f"(d[28]), "+f"(d[29]), "+f"(d[30]), "+f"(d[31]), "+f"(d[32]), "+f"(d[33]), "+f"(d[34]), "+f"(d[35]), "+f"(d[36]), "+f"(d[37]), "+f"(d[38]), "+f"(d[39]), "+f"(d[40]), "+f"(d[41]), "+f"(d[42]), "+f"(d[43]), "+f"(d[44]), "+f"(d[45]), "+f"(d[46]), "+f"(d[47]), "+f"(d[48]), "+f"(d[49]), "+f"(d[50]), "+f"(d[51]), "+f"(d[52]), "+f"(d[53]), "+f"(d[54]), "+f"(d[55]), "+f"(d[56]), "+f"(d[57]), "+f"(d[58]), "+f"(d[59]), "+f"(d[60]), "+f"(d[61]), "+f"(d[62]), "+f"(d[63])
    : "l"(da), "l"(db), "r"(scale_d));
}

__device__ __forceinline__ void wgmma_rs_n128(float (&d)[64], uint32_t a0, uint32_t a1, uint32_t a2, uint32_t a3, uint64_t db, int scale_d) {
  asm volatile("{\n.reg .pred p;\nsetp.ne.b32 p, %69, 0;\n"
    "wgmma.mma_async.sync.aligned.m64n128k16.f32.bf16.bf16 {%0, %1, %2, %3, %4, %5, %6, %7, %8, %9, %10, %11, %12, %13, %14, %15, %16, %17, %18, %19, %20, %21, %22, %23, %24, %25, %26, %27, %28, %29, %30, %31, %32, %33, %34, %35, %36, %37, %38, %39, %40, %41, %42, %43, %44, %45, %46, %47, %48, %49, %50, %51, %52, %53, %54, %55, %56, %57, %58, %59, %60, %61, %62, %63}, {%64, %65, %66, %67}, %68, p, 1, 1, 0;\n}\n"
    : "+f"(d[0]), "+f"(d[1]), "+f"(d[2]), "+f"(d[3]), "+f"(d[4]), "+f"(d[5]), "+f"(d[6]), "+f"(d[7]), "+f"(d[8]), "+f"(d[9]), "+f"(d[10]), "+f"(d[11]), "+f"(d[12]), "+f"(d[13]), "+f"(d[14]), "+f"(d[15]), "+f"(d[16]), "+f"(d[17]), "+f"(d[18]), "+f"(d[19]), "+f"(d[20]), "+f"(d[21]), "+f"(d[22]), "+f"(d[23]), "+f"(d[24]), "+f"(d[25]), "+f"(d[26]), "+f"(d[27]), "+f"(d[28]), "+f"(d[29]), "+f"(d[30]), "+f"(d[31]), "+f"(d[32]), "+f"(d[33]), "+f"(d[34]), "+f"(d[35]), "+f"(d[36]), "+f"(d[37]), "+f"(d[38]), "+f"(d[39]), "+f"(d[40]), "+f"(d[41]), "+f"(d[42]), "+f"(d[43]), "+f"(d[44]), "+f"(d[45]), "+f"(d[46]), "+f"(d[47]), "+f"(d[48]), "+f"(d[49]), "+f"(d[50]), "+f"(d[51]), "+f"(d[52]), "+f"(d[53]), "+f"(d[54]), "+f"(d[55]), "+f"(d[56]), "+f"(d[57]), "+f"(d[58]), "+f"(d[59]), "+f"(d[60]), "+f"(d[61]), "+f"(d[62]), "+f"(d[63])
    : "r"(a0), "r"(a1), "r"(a2), "r"(a3), "l"(db), "r"(scale_d));
}

__device__ __forceinline__ void wgmma_rs_n128_tb(float (&d)[64], uint32_t a0, uint32_t a1, uint32_t a2, uint32_t a3, uint64_t db, int scale_d) {
  asm volatile("{\n.reg .pred p;\nsetp.ne.b32 p, %69, 0;\n"
    "wgmma.mma_async.sync.aligned.m64n128k16.f32.bf16.bf16 {%0, %1, %2, %3, %4, %5, %6, %7, %8, %9, %10, %11, %12, %13, %14, %15, %16, %17, %18, %19, %20, %21, %22, %23, %24, %25, %26, %27, %28, %29, %30, %31, %32, %33, %34, %35, %36, %37, %38, %39, %40, %41, %42, %43, %44, %45, %46, %47, %48, %49, %50, %51, %52, %53, %54, %55, %56, %57, %58, %59, %60, %61, %62, %63}, {%64, %65, %66, %67}, %68, p, 1, 1, 1;\n}\n"
    : "+f"(d[0]), "+f"(d[1]), "+f"(d[2]), "+f"(d[3]), "+f"(d[4]), "+f"(d[5]), "+f"(d[6]), "+f"(d[7]), "+f"(d[8]), "+f"(d[9]), "+f"(d[10]), "+f"(d[11]), "+f"(d[12]), "+f"(d[13]), "+f"(d[14]), "+f"(d[15]), "+f"(d[16]), "+f"(d[17]), "+f"(d[18]), "+f"(d[19]), "+f"(d[20]), "+f"(d[21]), "+f"(d[22]), "+f"(d[23]), "+f"(d[24]), "+f"(d[25]), "+f"(d[26]), "+f"(d[27]), "+f"(d[28]), "+f"(d[29]), "+f"(d[30]), "+f"(d[31]), "+f"(d[32]), "+f"(d[33]), "+f"(d[34]), "+f"(d[35]), "+f"(d[36]), "+f"(d[37]), "+f"(d[38]), "+f"(d[39]), "+f"(d[40]), "+f"(d[41]), "+f"(d[42]), "+f"(d[43]), "+f"(d[44]), "+f"(d[45]), "+f"(d[46]), "+f"(d[47]), "+f"(d[48]), "+f"(d[49]), "+f"(d[50]), "+f"(d[51]), "+f"(d[52]), "+f"(d[53]), "+f"(d[54]), "+f"(d[55]), "+f"(d[56]), "+f"(d[57]), "+f"(d[58]), "+f"(d[59]), "+f"(d[60]), "+f"(d[61]), "+f"(d[62]), "+f"(d[63])
    : "r"(a0), "r"(a1), "r"(a2), "r"(a3), "l"(db), "r"(scale_d));
}

__device__ __forceinline__ void wgmma_rs_n32_tb(float (&d)[16], uint32_t a0, uint32_t a1, uint32_t a2, uint32_t a3, uint64_t db, int scale_d) {
  asm volatile("{\n.reg .pred p;\nsetp.ne.b32 p, %21, 0;\n"
    "wgmma.mma_async.sync.aligned.m64n32k16.f32.bf16.bf16 {%0, %1, %2, %3, %4, %5, %6, %7, %8, %9, %10, %11, %12, %13, %14, %15}, {%16, %17, %18, %19}, %20, p, 1, 1, 1;\n}\n"
    : "+f"(d[0]), "+f"(d[1]), "+f"(d[2]), "+f"(d[3]), "+f"(d[4]), "+f"(d[5]), "+f"(d[6]), "+f"(d[7]), "+f"(d[8]), "+f"(d[9]), "+f"(d[10]), "+f"(d[11]), "+f"(d[12]), "+f"(d[13]), "+f"(d[14]), "+f"(d[15])
    : "r"(a0), "r"(a1), "r"(a2), "r"(a3), "l"(db), "r"(scale_d));
}

__device__ __forceinline__ void wgmma_rs_n64_tb(float (&d)[32], uint32_t a0, uint32_t a1, uint32_t a2, uint32_t a3, uint64_t db, int scale_d) {
  asm volatile("{\n.reg .pred p;\nsetp.ne.b32 p, %37, 0;\n"
    "wgmma.mma_async.sync.aligned.m64n64k16.f32.bf16.bf16 {%0, %1, %2, %3, %4, %5, %6, %7, %8, %9, %10, %11, %12, %13, %14, %15, %16, %17, %18, %19, %20, %21, %22, %23, %24, %25, %26, %27, %28, %29, %30, %31}, {%32, %33, %34, %35}, %36, p, 1, 1, 1;\n}\n"
    : "+f"(d[0]), "+f"(d[1]), "+f"(d[2]), "+f"(d[3]), "+f"(d[4]), "+f"(d[5]), "+f"(d[6]), "+f"(d[7]), "+f"(d[8]), "+f"(d[9]), "+f"(d[10]), "+f"(d[11]), "+f"(d[12]), "+f"(d[13]), "+f"(d[14]), "+f"(d[15]), "+f"(d[16]), "+f"(d[17]), "+f"(d[18]), "+f"(d[19]), "+f"(d[20]), "+f"(d[21]), "+f"(d[22]), "+f"(d[23]), "+f"(d[24]), "+f"(d[25]), "+f"(d[26]), "+f"(d[27]), "+f"(d[28]), "+f"(d[29]), "+f"(d[30]), "+f"(d[31])
    : "r"(a0), "r"(a1), "r"(a2), "r"(a3), "l"(db), "r"(scale_d));
}

__device__ __forceinline__ void wgmma_rs_n256_tb(float (&d)[64], float (&e)[64], uint32_t a0, uint32_t a1, uint32_t a2, uint32_t a3, uint64_t db, int scale_d) {
  asm volatile("{\n.reg .pred p;\nsetp.ne.b32 p, %133, 0;\n"
    "wgmma.mma_async.sync.aligned.m64n256k16.f32.bf16.bf16 {%0, %1, %2, %3, %4, %5, %6, %7, %8, %9, %10, %11, %12, %13, %14, %15, %16, %17, %18, %19, %20, %21, %22, %23, %24, %25, %26, %27, %28, %29, %30, %31, %32, %33, %34, %35, %36, %37, %38, %39, %40, %41, %42, %43, %44, %45, %46, %47, %48, %49, %50, %51, %52, %53, %54, %55, %56, %57, %58, %59, %60, %61, %62, %63, %64, %65, %66, %67, %68, %69, %70, %71, %72, %73, %74, %75, %76, %77, %78, %79, %80, %81, %82, %83, %84, %85, %86, %87, %88, %89, %90, %91, %92, %93, %94, %95, %96, %97, %98, %99, %100, %101, %102, %103, %104, %105, %106, %107, %108, %109, %110, %111, %112, %113, %114, %115, %116, %117, %118, %119, %120, %121, %122, %123, %124, %125, %126, %127}, {%128, %129, %130, %131}, %132, p, 1, 1, 1;\n}\n"
    : "+f"(d[0]), "+f"(d[1]), "+f"(d[2]), "+f"(d[3]), "+f"(d[4]), "+f"(d[5]), "+f"(d[6]), "+f"(d[7]), "+f"(d[8]), "+f"(d[9]), "+f"(d[10]), "+f"(d[11]), "+f"(d[12]), "+f"(d[13]), "+f"(d[14]), "+f"(d[15]), "+f"(d[16]), "+f"(d[17]), "+f"(d[18]), "+f"(d[19]), "+f"(d[20]), "+f"(d[21]), "+f"(d[22]), "+f"(d[23]), "+f"(d[24]), "+f"(d[25]), "+f"(d[26]), "+f"(d[27]), "+f"(d[28]), "+f"(d[29]), "+f"(d[30]), "+f"(d[31]), "+f"(d[32]), "+f"(d[33]), "+f"(d[34]), "+f"(d[35]), "+f"(d[36]), "+f"(d[37]), "+f"(d[38]), "+f"(d[39]), "+f"(d[40]), "+f"(d[41]), "+f"(d[42]), "+f"(d[43]), "+f"(d[44]), "+f"(d[45]), "+f"(d[46]), "+f"(d[47]), "+f"(d[48]), "+f"(d[49]), "+f"(d[50]), "+f"(d[51]), "+f"(d[52]), "+f"(d[53]), "+f"(d[54]), "+f"(d[55]), "+f"(d[56]), "+f"(d[57]), "+f"(d[58]), "+f"(d[59]), "+f"(d[60]), "+f"(d[61]), "+f"(d[62]), "+f"(d[63]), "+f"(e[0]), "+f"(e[1]), "+f"(e[2]), "+f"(e[3]), "+f"(e[4]), "+f"(e[5]), "+f"(e[6]), "+f"(e[7]), "+f"(e[8]), "+f"(e[9]), "+f"(e[10]), "+f"(e[11]), "+f"(e[12]), "+f"(e[13]), "+f"(e[14]), "+f"(e[15]), "+f"(e[16]), "+f"(e[17]), "+f"(e[18]), "+f"(e[19]), "+f"(e[20]), "+f"(e[21]), "+f"(e[22]), "+f"(e[23]), "+f"(e[24]), "+f"(e[25]), "+f"(e[26]), "+f"(e[27]), "+f"(e[28]), "+f"(e[29]), "+f"(e[30]), "+f"(e[31]), "+f"(e[32]), "+f"(e[33]), "+f"(e[34]), "+f"(e[35]), "+f"(e[36]), "+f"(e[37]), "+f"(e[38]), "+f"(e[39]), "+f"(e[40]), "+f"(e[41]), "+f"(e[42]), "+f"(e[43]), "+f"(e[44]), "+f"(e[45]), "+f"(e[46]), "+f"(e[47]), "+f"(e[48]), "+f"(e[49]), "+f"(e[50]), "+f"(e[51]), "+f"(e[52]), "+f"(e[53]), "+f"(e[54]), "+f"(e[55]), "+f"(e[56]), "+f"(e[57]), "+f"(e[58]), "+f"(e[59]), "+f"(e[60]), "+f"(e[61]), "+f"(e[62]), "+f"(e[63])
    : "r"(a0), "r"(a1), "r"(a2), "r"(a3), "l"(db), "r"(scale_d));
}

__device__ __forceinline__ void wgmma_rs_n128_z(float (&d)[64], uint32_t a0, uint32_t a1, uint32_t a2, uint32_t a3, uint64_t db) {
  asm volatile("{\n.reg .pred p;\nsetp.ne.b32 p, 0, 0;\n"
    "wgmma.mma_async.sync.aligned.m64n128k16.f32.bf16.bf16 {%0, %1, %2, %3, %4, %5, %6, %7, %8, %9, %10, %11, %12, %13, %14, %15, %16, %17, %18, %19, %20, %21, %22, %23, %24, %25, %26, %27, %28, %29, %30, %31, %32, %33, %34, %35, %36, %37, %38, %39, %40, %41, %42, %43, %44, %45, %46, %47, %48, %49, %50, %51, %52, %53, %54, %55, %56, %57, %58, %59, %60, %61, %62, %63}, {%64, %65, %66, %67}, %68, p, 1, 1, 0;\n}\n"
    : "=f"(d[0]), "=f"(d[1]), "=f"(d[2]), "=f"(d[3]), "=f"(d[4]), "=f"(d[5]), "=f"(d[6]), "=f"(d[7]), "=f"(d[8]), "=f"(d[9]), "=f"(d[10]), "=f"(d[11]), "=f"(d[12]), "=f"(d[13]), "=f"(d[14]), "=f"(d[15]), "=f"(d[16]), "=f"(d[17]), "=f"(d[18]), "=f"(d[19]), "=f"(d[20]), "=f"(d[21]), "=f"(d[22]), "=f"(d[23]), "=f"(d[24]), "=f"(d[25]), "=f"(d[26]), "=f"(d[27]), "=f"(d[28]), "=f"(d[29]), "=f"(d[30]), "=f"(d[31]), "=f"(d[32]), "=f"(d[33]), "=f"(d[34]), "=f"(d[35]), "=f"(d[36]), "=f"(d[37]), "=f"(d[38]), "=f"(d[39]), "=f"(d[40]), "=f"(d[41]), "=f"(d[42]), "=f"(d[43]), "=f"(d[44]), "=f"(d[45]), "=f"(d[46]), "=f"(d[47]), "=f"(d[48]), "=f"(d[49]), "=f"(d[50]), "=f"(d[51]), "=f"(d[52]), "=f"(d[53]), "=f"(d[54]), "=f"(d[55]), "=f"(d[56]), "=f"(d[57]), "=f"(d[58]), "=f"(d[59]), "=f"(d[60]), "=f"(d[61]), "=f"(d[62]), "=f"(d[63])
    : "r"(a0), "r"(a1), "r"(a2), "r"(a3), "l"(db));
}

__device__ __forceinline__ void wgmma_rs_n64_tb_z(float (&d)[32], uint32_t a0, uint32_t a1, uint32_t a2, uint32_t a3, uint64_t db) {
  asm volatile("{\n.reg .pred p;\nsetp.ne.b32 p, 0, 0;\n"
    "wgmma.mma_async.sync.aligned.m64n64k16.f32.bf16.bf16 {%0, %1, %2, %3, %4, %5, %6, %7, %8, %9, %10, %11, %12, %13, %14, %15, %16, %17, %18, %19, %20, %21, %22, %23, %24, %25, %26, %27, %28, %29, %30, %31}, {%32, %33, %34, %35}, %36, p, 1, 1, 1;\n}\n"
    : "=f"(d[0]), "=f"(d[1]), "=f"(d[2]), "=f"(d[3]), "=f"(d[4]), "=f"(d[5]), "=f"(d[6]), "=f"(d[7]), "=f"(d[8]), "=f"(d[9]), "=f"(d[10]), "=f"(d[11]), "=f"(d[12]), "=f"(d[13]), "=f"(d[14]), "=f"(d[15]), "=f"(d[16]), "=f"(d[17]), "=f"(d[18]), "=f"(d[19]), "=f"(d[20]), "=f"(d[21]), "=f"(d[22]), "=f"(d[23]), "=f"(d[24]), "=f"(d[25]), "=f"(d[26]), "=f"(d[27]), "=f"(d[28]), "=f"(d[29]), "=f"(d[30]), "=f"(d[31])
    : "r"(a0), "r"(a1), "r"(a2), "r"(a3), "l"(db));
}

__device__ __forceinline__ void wgmma_rs_n256_tb_z(float (&d)[64], float (&e)[64], uint32_t a0, uint32_t a1, uint32_t a2, uint32_t a3, uint64_t db) {
  asm volatile("{\n.reg .pred p;\nsetp.ne.b32 p, 0, 0;\n"
    "wgmma.mma_async.sync.aligned.m64n256k16.f32.bf16.bf16 {%0, %1, %2, %3, %4, %5, %6, %7, %8, %9, %10, %11, %12, %13, %14, %15, %16, %17, %18, %19, %20, %21, %22, %23, %24, %25, %26, %27, %28, %29, %30, %31, %32, %33, %34, %35, %36, %37, %38, %39, %40, %41, %42, %43, %44, %45, %46, %47, %48, %49, %50, %51, %52, %53, %54, %55, %56, %57, %58, %59, %60, %61, %62, %63, %64, %65, %66, %67, %68, %69, %70, %71, %72, %73, %74, %75, %76, %77, %78, %79, %80, %81, %82, %83, %84, %85, %86, %87, %88, %89, %90, %91, %92, %93, %94, %95, %96, %97, %98, %99, %100, %101, %102, %103, %104, %105, %106, %107, %108, %109, %110, %111, %112, %113, %114, %115, %116, %117, %118, %119, %120, %121, %122, %123, %124, %125, %126, %127}, {%128, %129, %130, %131}, %132, p, 1, 1, 1;\n}\n"
    : "=f"(d[0]), "=f"(d[1]), "=f"(d[2]), "=f"(d[3]), "=f"(d[4]), "=f"(d[5]), "=f"(d[6]), "=f"(d[7]), "=f"(d[8]), "=f"(d[9]), "=f"(d[10]), "=f"(d[11]), "=f"(d[12]), "=f"(d[13]), "=f"(d[14]), "=f"(d[15]), "=f"(d[16]), "=f"(d[17]), "=f"(d[18]), "=f"(d[19]), "=f"(d[20]), "=f"(d[21]), "=f"(d[22]), "=f"(d[23]), "=f"(d[24]), "=f"(d[25]), "=f"(d[26]), "=f"(d[27]), "=f"(d[28]), "=f"(d[29]), "=f"(d[30]), "=f"(d[31]), "=f"(d[32]), "=f"(d[33]), "=f"(d[34]), "=f"(d[35]), "=f"(d[36]), "=f"(d[37]), "=f"(d[38]), "=f"(d[39]), "=f"(d[40]), "=f"(d[41]), "=f"(d[42]), "=f"(d[43]), "=f"(d[44]), "=f"(d[45]), "=f"(d[46]), "=f"(d[47]), "=f"(d[48]), "=f"(d[49]), "=f"(d[50]), "=f"(d[51]), "=f"(d[52]), "=f"(d[53]), "=f"(d[54]), "=f"(d[55]), "=f"(d[56]), "=f"(d[57]), "=f"(d[58]), "=f"(d[59]), "=f"(d[60]), "=f"(d[61]), "=f"(d[62]), "=f"(d[63]), "=f"(e[0]), "=f"(e[1]), "=f"(e[2]), "=f"(e[3]), "=f"(e[4]), "=f"(e[5]), "=f"(e[6]), "=f"(e[7]), "=f"(e[8]), "=f"(e[9]), "=f"(e[10]), "=f"(e[11]), "=f"(e[12]), "=f"(e[13]), "=f"(e[14]), "=f"(e[15]), "=f"(e[16]), "=f"(e[17]), "=f"(e[18]), "=f"(e[19]), "=f"(e[20]), "=f"(e[21]), "=f"(e[22]), "=f"(e[23]), "=f"(e[24]), "=f"(e[25]), "=f"(e[26]), "=f"(e[27]), "=f"(e[28]), "=f"(e[29]), "=f"(e[30]), "=f"(e[31]), "=f"(e[32]), "=f"(e[33]), "=f"(e[34]), "=f"(e[35]), "=f"(e[36]), "=f"(e[37]), "=f"(e[38]), "=f"(e[39]), "=f"(e[40]), "=f"(e[41]), "=f"(e[42]), "=f"(e[43]), "=f"(e[44]), "=f"(e[45]), "=f"(e[46]), "=f"(e[47]), "=f"(e[48]), "=f"(e[49]), "=f"(e[50]), "=f"(e[51]), "=f"(e[52]), "=f"(e[53]), "=f"(e[54]), "=f"(e[55]), "=f"(e[56]), "=f"(e[57]), "=f"(e[58]), "=f"(e[59]), "=f"(e[60]), "=f"(e[61]), "=f"(e[62]), "=f"(e[63])
    : "r"(a0), "r"(a1), "r"(a2), "r"(a3), "l"(db));
}

__device__ __forceinline__ void wgmma_rs_n192_tb(float (&d)[64], float (&e)[64], uint32_t a0, uint32_t a1, uint32_t a2, uint32_t a3, uint64_t db) {
  asm volatile("{\n.reg .pred p;\nsetp.eq.b32 p, 0, 0;\n"
    "wgmma.mma_async.sync.aligned.m64n192k16.f32.bf16.bf16 {%0, %1, %2, %3, %4, %5, %6, %7, %8, %9, %10, %11, %12, %13, %14, %15, %16, %17, %18, %19, %20, %21, %22, %23, %24, %25, %26, %27, %28, %29, %30, %31, %32, %33, %34, %35, %36, %37, %38, %39, %40, %41, %42, %43, %44, %45, %46, %47, %48, %49, %50, %51, %52, %53, %54, %55, %56, %57, %58, %59, %60, %61, %62, %63, %64, %65, %66, %67, %68, %69, %70, %71, %72, %73, %74, %75, %76, %77, %78, %79, %80, %81, %82, %83, %84, %85, %86, %87, %88, %89, %90, %91, %92, %93, %94, %95}, {%96, %97, %98, %99}, %100, p, 1, 1, 1;\n}\n"
    : "+f"(d[0]), "+f"(d[1]), "+f"(d[2]), "+f"(d[3]), "+f"(d[4]), "+f"(d[5]), "+f"(d[6]), "+f"(d[7]), "+f"(d[8]), "+f"(d[9]), "+f"(d[10]), "+f"(d[11]), "+f"(d[12]), "+f"(d[13]), "+f"(d[14]), "+f"(d[15]), "+f"(d[16]), "+f"(d[17]), "+f"(d[18]), "+f"(d[19]), "+f"(d[20]), "+f"(d[21]), "+f"(d[22]), "+f"(d[23]), "+f"(d[24]), "+f"(d[25]), "+f"(d[26]), "+f"(d[27]), "+f"(d[28]), "+f"(d[29]), "+f"(d[30]), "+f"(d[31]), "+f"(d[32]), "+f"(d[33]), "+f"(d[34]), "+f"(d[35]), "+f"(d[36]), "+f"(d[37]), "+f"(d[38]), "+f"(d[39]), "+f"(d[40]), "+f"(d[41]), "+f"(d[42]), "+f"(d[43]), "+f"(d[44]), "+f"(d[45]), "+f"(d[46]), "+f"(d[47]), "+f"(d[48]), "+f"(d[49]), "+f"(d[50]), "+f"(d[51]), "+f"(d[52]), "+f"(d[53]), "+f"(d[54]), "+f"(d[55]), "+f"(d[56]), "+f"(d[57]), "+f"(d[58]), "+f"(d[59]), "+f"(d[60]), "+f"(d[61]), "+f"(d[62]), "+f"(d[63]), "+f"(e[0]), "+f"(e[1]), "+f"(e[2]), "+f"(e[3]), "+f"(e[4]), "+f"(e[5]), "+f"(e[6]), "+f"(e[7]), "+f"(e[8]), "+f"(e[9]), "+f"(e[10]), "+f"(e[11]), "+f"(e[12]), "+f"(e[13]), "+f"(e[14]), "+f"(e[15]), "+f"(e[16]), "+f"(e[17]), "+f"(e[18]), "+f"(e[19]), "+f"(e[20]), "+f"(e[21]), "+f"(e[22]), "+f"(e[23]), "+f"(e[24]), "+f"(e[25]), "+f"(e[26]), "+f"(e[27]), "+f"(e[28]), "+f"(e[29]), "+f"(e[30]), "+f"(e[31])
    : "r"(a0), "r"(a1), "r"(a2), "r"(a3), "l"(db));
}

__device__ __forceinline__ void wgmma_rs_n192_tb_z(float (&d)[64], float (&e)[64], uint32_t a0, uint32_t a1, uint32_t a2, uint32_t a3, uint64_t db) {
  asm volatile("{\n.reg .pred p;\nsetp.ne.b32 p, 0, 0;\n"
    "wgmma.mma_async.sync.aligned.m64n192k16.f32.bf16.bf16 {%0, %1, %2, %3, %4, %5, %6, %7, %8, %9, %10, %11, %12, %13, %14, %15, %16, %17, %18, %19, %20, %21, %22, %23, %24, %25, %26, %27, %28, %29, %30, %31, %32, %33, %34, %35, %36, %37, %38, %39, %40, %41, %42, %43, %44, %45, %46, %47, %48, %49, %50, %51, %52, %53, %54, %55, %56, %57, %58, %59, %60, %61, %62, %63, %64, %65, %66, %67, %68, %69, %70, %71, %72, %73, %74, %75, %76, %77, %78, %79, %80, %81, %82, %83, %84, %85, %86, %87, %88, %89, %90, %91, %92, %93, %94, %95}, {%96, %97, %98, %99}, %100, p, 1, 1, 1;\n}\n"
    : "=f"(d[0]), "=f"(d[1]), "=f"(d[2]), "=f"(d[3]), "=f"(d[4]), "=f"(d[5]), "=f"(d[6]), "=f"(d[7]), "=f"(d[8]), "=f"(d[9]), "=f"(d[10]), "=f"(d[11]), "=f"(d[12]), "=f"(d[13]), "=f"(d[14]), "=f"(d[15]), "=f"(d[16]), "=f"(d[17]), "=f"(d[18]), "=f"(d[19]), "=f"(d[20]), "=f"(d[21]), "=f"(d[22]), "=f"(d[23]), "=f"(d[24]), "=f"(d[25]), "=f"(d[26]), "=f"(d[27]), "=f"(d[28]), "=f"(d[29]), "=f"(d[30]), "=f"(d[31]), "=f"(d[32]), "=f"(d[33]), "=f"(d[34]), "=f"(d[35]), "=f"(d[36]), "=f"(d[37]), "=f"(d[38]), "=f"(d[39]), "=f"(d[40]), "=f"(d[41]), "=f"(d[42]), "=f"(d[43]), "=f"(d[44]), "=f"(d[45]), "=f"(d[46]), "=f"(d[47]), "=f"(d[48]), "=f"(d[49]), "=f"(d[50]), "=f"(d[51]), "=f"(d[52]), "=f"(d[53]), "=f"(d[54]), "=f"(d[55]), "=f"(d[56]), "=f"(d[57]), "=f"(d[58]), "=f"(d[59]), "=f"(d[60]), "=f"(d[61]), "=f"(d[62]), "=f"(d[63]), "=f"(e[0]), "=f"(e[1]), "=f"(e[2]), "=f"(e[3]), "=f"(e[4]), "=f"(e[5]), "=f"(e[6]), "=f"(e[7]), "=f"(e[8]), "=f"(e[9]), "=f"(e[10]), "=f"(e[11]), "=f"(e[12]), "=f"(e[13]), "=f"(e[14]), "=f"(e[15]), "=f"(e[16]), "=f"(e[17]), "=f"(e[18]), "=f"(e[19]), "=f"(e[20]), "=f"(e[21]), "=f"(e[22]), "=f"(e[23]), "=f"(e[24]), "=f"(e[25]), "=f"(e[26]), "=f"(e[27]), "=f"(e[28]), "=f"(e[29]), "=f"(e[30]), "=f"(e[31])
    : "r"(a0), "r"(a1), "r"(a2), "r"(a3), "l"(db));
}

struct Maps {
  CUtensorMap x[2], k[2], v[2], wq[2], wo[2];
  const char *px[2], *pwo[2];
};

__device__ __forceinline__ void poll_tiles(int tile, const unsigned (&target)[3], uint32_t ready) {
#pragma unroll
  for (int pn = 0; pn < 3; pn++) {
    const unsigned* c = &g_cnt[(tile * 4 + pn) * 32];
    for (uint32_t it = 0; it < WAIT_LIMIT; ++it) {
      unsigned v;
      asm volatile("ld.acquire.gpu.global.u32 %0, [%1];" : "=r"(v) : "l"(c) : "memory");
      if ((int)(v - target[pn]) >= 0) break;
    }
    mbar_arrive(ready + pn * 8);
  }
}
__device__ __forceinline__ void read_targets(int tile, unsigned (&target)[3]) {
#pragma unroll
  for (int pn = 0; pn < 3; pn++) {
    unsigned v;
    asm volatile("ld.relaxed.gpu.global.u32 %0, [%1];" : "=r"(v) : "l"(&g_cnt[(tile * 4 + pn) * 32]) : "memory");
    target[pn] = (v / 16u + 1u) * 16u;
  }
}

__global__ void __cluster_dims__(2, 1, 1) __launch_bounds__(384, 1)
fused_gqa_kernel(const __grid_constant__ Maps maps, __nv_bfloat16* __restrict__ out) {
  extern __shared__ __align__(1024) unsigned char smem[];
  const uint32_t sbase = smem_u32(smem);
  const uint32_t full0 = sbase + BAR_OFF;
  const uint32_t empty0 = full0 + N_ITEMS * 8;
  const uint32_t ready0 = empty0 + N_ITEMS * 8;
  const uint32_t pub0 = ready0 + 6 * 8;

  const int tid = threadIdx.x;
  const int wg = tid >> 7;
  const int bid = blockIdx.x;
  const int bp = bid & 3;
  const int h = (bid >> 2) & 15;
  const int p = bid >> 6;

  if (tid == 0) {
#pragma unroll
    for (int i = 0; i < 4; i++) mbar_init(full0 + (WQ0 + i) * 8, 1);
#pragma unroll
    for (int i = 0; i < 4; i++) mbar_init(full0 + (X0 + i) * 8, 1);
    asm volatile("fence.mbarrier_init.release.cluster;" ::: "memory");
#pragma unroll
    for (int kc = 0; kc < 4; kc++) {
      mbar_expect_tx(full0 + (X0 + kc) * 8, 16384);
      tma_load3(sbase + x_off(kc), &maps.x[p], 0, bp * 128, kc, full0 + (X0 + kc) * 8);
      mbar_expect_tx(full0 + (WQ0 + kc) * 8, T32);
      tma_load3(sbase + wq_off(kc), &maps.wq[p], 0, kc * 64, h * 4, full0 + (WQ0 + kc) * 8);
    }
    TR(0, 56);
  } else if (tid >= 64 && tid < 96) {
    const char* base = maps.px[p] + (size_t)(bp * 128 + h * 8) * 1152;
#pragma unroll
    for (int i = 0; i < 3; i++)
      if ((tid & 31) + i * 32 < 72) l2_prefetch(base + ((tid & 31) + i * 32) * 128);
  } else if (tid == 32) {
    prefetch_tmap(&maps.k[p]);
    prefetch_tmap(&maps.v[p]);
    prefetch_tmap(&maps.wo[p]);
  } else if (tid >= 128) {
    const int i = tid - 128;
    if (i < N_ITEMS) {
      if (!(i < 4 || (i >= X0 && i < X0 + 4))) mbar_init(full0 + i * 8, 1);
    } else if (i >= 64 && i < 64 + N_ITEMS) {
      mbar_init(empty0 + (i - 64) * 8, i == 64 + WQ0 ? 4 : 8);
    } else if (i >= 128 && i < 128 + 6) {
      mbar_init(ready0 + (i - 128) * 8, 1);
    } else if (i >= 160 && i < 160 + 6) {
      mbar_init(pub0 + (i - 160) * 8, 4);
    }
    asm volatile("fence.mbarrier_init.release.cluster;" ::: "memory");
  }
  __syncthreads();
  if (tid == 0) TR(0, 57);

  if (wg == 0) {
    asm volatile("setmaxnreg.dec.sync.aligned.u32 24;");
    if (tid == 0) {
      const int kvrow = (2 * bp * 16 + h) * kSK;
      auto load_kv = [&](int n) {
        if (n >= KV_INFLIGHT) mbar_wait(full0 + (KV0 + n - KV_INFLIGHT) * 8);
        const uint32_t fb = full0 + (KV0 + n) * 8;
        TR(0, KV0 + n);
        mbar_expect_tx(fb, T32);
        tma_load3(sbase + kv_off(n), (n & 1) ? &maps.v[p] : &maps.k[p], 0, kvrow + (n >> 3) * 16 * kSK + ((n & 7) >> 1) * 128, 0, fb);
      };
      if (KV0_AT < 0) load_kv(0);
#pragma unroll 1
      for (int c = 0; c < 9; c++) {
        mbar_wait(empty0 + (X0 + c) * 8);
        if (c < 5) {
          mbar_expect_tx(full0 + (X0 + c + 4) * 8, 16384);
          tma_load3(sbase + x_off(c + 4), &maps.x[p], 0, bp * 128, c + 4, full0 + (X0 + c + 4) * 8);
        }
        if (c < 5) {
          TR(0, WQ0 + c + 4);
          mbar_expect_tx(full0 + (WQ0 + c + 4) * 8, T32);
          tma_load3(sbase + wq_off(c + 4), &maps.wq[p], 0, (c + 4) * 64, h * 4, full0 + (WQ0 + c + 4) * 8);
          if (c == KV0_AT) load_kv(0);
        } else if (c < 8) {
          load_kv(c - 4);
          if (c == 7) load_kv(4);
        } else {
          load_kv(5);
        }
      }
#pragma unroll 1
      for (int n = 6; n < N_KV; n++) {
        mbar_wait(empty0 + (KV0 + n - 6) * 8);
        load_kv(n);
      }
#pragma unroll 1
      for (int m = 0; m < N_WO; m++) {
        const int dep = m >= 9 ? WO0 + m - 9 : (m == 8 ? WQ0 : KV0 + 10 + (int)((0x55443210u >> (m * 4)) & 15u));
        mbar_wait(empty0 + dep * 8);
        const uint32_t fb = full0 + (WO0 + m) * 8;
        TR(0, WO0 + m);
        mbar_expect_tx(fb, WO_BYTES);
        tma_load3(sbase + wo_off(m), &maps.wo[p], 0, h * 256 + (m & 3) * 64, (m >> 2) * 3, fb);
      }
    } else if (tid == 96 || tid == 112) {
      const int w = (tid >> 4) & 1;
      unsigned target[3];
      read_targets(p * 8 + 2 * bp + w, target);
      mbar_wait(pub0 + w * 24);
      poll_tiles(p * 8 + 2 * bp + w, target, ready0 + w * 24);
    } else if (tid >= 32 && tid < 96) {
      const int w = (tid >> 5) - 1;
      if (tid & 31) return;
      const int tile = p * 8 + 2 * bp + w;
#pragma unroll 1
      for (int e = 0; e < 3; e++) {
        mbar_wait(pub0 + (w * 3 + e) * 8);
        __threadfence();
        asm volatile("red.relaxed.gpu.global.add.u32 [%0], 1;" ::"l"(&g_cnt[(tile * 4 + e) * 32]) : "memory");
      }
    }
  } else {
    asm volatile("setmaxnreg.inc.sync.aligned.u32 240;");
    const int w = wg - 1;
    const int t128 = tid & 127;
    const int lane = tid & 31;

    auto release = [&](int item) {
      __syncwarp();
      if (lane == 0) mbar_arrive(empty0 + item * 8);
    };

    TRC(0);
    const float cs = 0.08838834764831845f * 1.4426950408889634f;
    float s[64], o[64];
#pragma unroll
    for (int i = 0; i < 64; i++) s[i] = 0.f, o[i] = 0.f;
    uint32_t qf[32];
    uint4* park = reinterpret_cast<uint4*>(smem + PARK_OFF) + w * 1024 + t128;
    {
#pragma unroll 1
      for (int kc = 0; kc < 9; kc++) {
        mbar_wait(full0 + (X0 + kc) * 8);
        mbar_wait(full0 + (WQ0 + kc) * 8);
        if (kc == 0) TRC(1);
        const uint64_t da = make_desc(sbase + x_off(kc), 16, 1024);
        const uint64_t db = make_desc(sbase + wq_off(kc) + w * 16384, 8192, 1024);
        wg_fence();
#pragma unroll
        for (int ks = 0; ks < 4; ks++) {
          wgmma_ss_n128_tb(s, da + ks * 2, db + ks * 128, (kc | ks) != 0);
          wgmma_ss_n128_tb(o, da + 512 + ks * 2, db + ks * 128, (kc | ks) != 0);
        }
        wg_commit();
        wg_wait<0>();
        release(X0 + kc);
      }
      fence_regs(s);
      fence_regs(o);
#pragma unroll
      for (int i = 0; i < 32; i++) qf[i] = pack_bf16(s[2 * i], s[2 * i + 1]);
      named_bar(1, 256);
#pragma unroll
      for (int i = 0; i < 8; i++) park[i * 128] = pack8(o, i);
      TRC(2);
    }
#pragma unroll 1
    for (int bb = 0; bb < 2; bb++) {
#pragma unroll
      for (int i = 0; i < 64; i++) o[i] = 0.f;
      float m0 = -INFINITY, m1 = -INFINITY, l0 = 0.f, l1 = 0.f;
#pragma unroll 1
      for (int t = 0; t < 4; t++) {
        const int n = bb * 8 + t * 2;
        {
          const uint32_t base = sbase + kv_off(n);
          mbar_wait(full0 + (KV0 + n) * 8);
          if (n == 0 && w == 1) named_bar(4, 256);
          const uint64_t db = make_desc(base, 16, 1024);
          wg_fence();
          wgmma_rs_n128_z(s, qf[0], qf[1], qf[2], qf[3], db);
#pragma unroll
          for (int ks = 1; ks < 8; ks++)
            wgmma_rs_n128(s, qf[4 * ks], qf[4 * ks + 1], qf[4 * ks + 2], qf[4 * ks + 3], db + (ks >> 2) * 1024 + (ks & 3) * 2, 1);
          wg_commit();
          wg_wait<0>();
          fence_regs(s);
          if (n == 0 && w == 0) named_arrive(4, 256);
          release(KV0 + n);
        }
        float mx0 = s[0], mx1 = s[2];
#pragma unroll
        for (int g = 0; g < 16; g++) {
          mx0 = fmaxf(mx0, fmaxf(s[4 * g], s[4 * g + 1]));
          mx1 = fmaxf(mx1, fmaxf(s[4 * g + 2], s[4 * g + 3]));
        }
        mx0 = fmaxf(mx0, __shfl_xor_sync(0xffffffffu, mx0, 1));
        mx0 = fmaxf(mx0, __shfl_xor_sync(0xffffffffu, mx0, 2));
        mx1 = fmaxf(mx1, __shfl_xor_sync(0xffffffffu, mx1, 1));
        mx1 = fmaxf(mx1, __shfl_xor_sync(0xffffffffu, mx1, 2));
        const float mn0 = fmaxf(m0, mx0), mn1 = fmaxf(m1, mx1);
        const float a0 = ex2((m0 - mn0) * cs), a1 = ex2((m1 - mn1) * cs);
        m0 = mn0;
        m1 = mn1;
        const float ms0 = mn0 * cs, ms1 = mn1 * cs;
        float rs0 = 0.f, rs1 = 0.f;
        uint32_t pf[32];
#pragma unroll
        for (int g = 0; g < 16; g++) {
          const float p0 = ex2(fmaf(s[4 * g], cs, -ms0));
          const float p1 = ex2(fmaf(s[4 * g + 1], cs, -ms0));
          const float p2 = ex2(fmaf(s[4 * g + 2], cs, -ms1));
          const float p3 = ex2(fmaf(s[4 * g + 3], cs, -ms1));
          rs0 += p0 + p1;
          rs1 += p2 + p3;
          pf[2 * g] = pack_bf16(p0, p1);
          pf[2 * g + 1] = pack_bf16(p2, p3);
        }
        l0 = l0 * a0 + rs0;
        l1 = l1 * a1 + rs1;
#pragma unroll
        for (int g = 0; g < 16; g++) {
          o[4 * g] *= a0;
          o[4 * g + 1] *= a0;
          o[4 * g + 2] *= a1;
          o[4 * g + 3] *= a1;
        }
        {
          const uint32_t base = sbase + kv_off(n + 1);
          mbar_wait(full0 + (KV0 + n + 1) * 8);
          const uint64_t db = make_desc(base, 16384, 1024);
          wg_fence();
#pragma unroll
          for (int ks = 0; ks < 8; ks++)
            wgmma_rs_n128_tb(o, pf[4 * ks], pf[4 * ks + 1], pf[4 * ks + 2], pf[4 * ks + 3], db + ks * 128, 1);
          wg_commit();
          wg_wait<0>();
          fence_regs(o);
          release(KV0 + n + 1);
          TRC(3 + bb * 5 + t);
        }
      }
      l0 += __shfl_xor_sync(0xffffffffu, l0, 1);
      l0 += __shfl_xor_sync(0xffffffffu, l0, 2);
      l1 += __shfl_xor_sync(0xffffffffu, l1, 1);
      l1 += __shfl_xor_sync(0xffffffffu, l1, 2);
      const float i0 = 1.f / l0, i1 = 1.f / l1;
      if (bb == 0) {
#pragma unroll
        for (int i = 0; i < 8; i++) {
          const uint4 v = park[i * 128];
          qf[4 * i] = v.x;
          qf[4 * i + 1] = v.y;
          qf[4 * i + 2] = v.z;
          qf[4 * i + 3] = v.w;
          park[i * 128] = make_uint4(pack_bf16(o[8 * i] * i0, o[8 * i + 1] * i0), pack_bf16(o[8 * i + 2] * i1, o[8 * i + 3] * i1),
                                     pack_bf16(o[8 * i + 4] * i0, o[8 * i + 5] * i0), pack_bf16(o[8 * i + 6] * i1, o[8 * i + 7] * i1));
        }
        if (w == 1) named_arrive(5, 256);
      } else {
#pragma unroll
        for (int i = 0; i < 16; i++) {
          qf[2 * i] = pack_bf16(o[4 * i] * i0, o[4 * i + 1] * i0);
          qf[2 * i + 1] = pack_bf16(o[4 * i + 2] * i1, o[4 * i + 3] * i1);
        }
      }
    }
    uint32_t af[64];
    {
      const uint4* src = reinterpret_cast<const uint4*>(smem + PARK_OFF) + t128;
      if (w == 0) {
        named_bar(5, 256);
#pragma unroll
        for (int i = 0; i < 16; i++) {
          const uint4 v = src[i * 128];
          af[4 * i] = v.x;
          af[4 * i + 1] = v.y;
          af[4 * i + 2] = v.z;
          af[4 * i + 3] = v.w;
        }
#pragma unroll
        for (int i = 0; i < 8; i++) park[i * 128] = make_uint4(qf[4 * i], qf[4 * i + 1], qf[4 * i + 2], qf[4 * i + 3]);
        asm volatile("fence.proxy.async.shared::cta;" ::: "memory");
        named_arrive(1, 256);
      } else {
        named_bar(1, 256);
#pragma unroll
        for (int i = 0; i < 8; i++) {
          const uint4 v = src[i * 128];
          af[4 * i] = v.x;
          af[4 * i + 1] = v.y;
          af[4 * i + 2] = v.z;
          af[4 * i + 3] = v.w;
        }
#pragma unroll
        for (int i = 0; i < 32; i++) af[32 + i] = qf[i];
        asm volatile("fence.proxy.async.shared::cta;" ::: "memory");
        release(WQ0);
      }
    }
    TRC(12);
    const int tile = p * 8 + 2 * bp + w;
    uint4* part = g_part + (size_t)(tile * 16 + h) * 36 * 128 + t128;
#pragma unroll
    for (int pn = 0; pn < 3; pn++) {
#pragma unroll
      for (int kc = 0; kc < 4; kc++) {
        const int m = pn * 4 + kc;
        mbar_wait(full0 + (WO0 + m) * 8);
        const uint64_t db = make_desc(sbase + wo_off(m), 8192, 1024);
        wg_fence();
#pragma unroll
        for (int ks = 0; ks < 4; ks++) {
          const int a = (kc * 4 + ks) * 4;
          if ((kc | ks) == 0) wgmma_rs_n192_tb_z(s, o, af[a], af[a + 1], af[a + 2], af[a + 3], db);
          else wgmma_rs_n192_tb(s, o, af[a], af[a + 1], af[a + 2], af[a + 3], db + ks * 128);
        }
        wg_commit();
        if (kc > 0) {
          wg_wait<1>();
          if (m - 1 < 3) release(WO0 + m - 1);
        }
      }
      wg_wait<0>();
      fence_regs(s);
      fence_regs32(o);
      TRC(13 + pn * 2);
#pragma unroll
      for (int i = 0; i < 8; i++) __stcg(part + (pn * 12 + i) * 128, pack8(s, i));
#pragma unroll
      for (int i = 0; i < 4; i++) __stcg(part + (pn * 12 + 8 + i) * 128, pack8(o, i));
      __syncwarp();
      if (lane == 0) mbar_arrive(pub0 + (w * 3 + pn) * 8);
      TRC(14 + pn * 2);
    }
    if (t128 < 96) {
      const int u = h * 96 + t128;
      const int slot = u >> 7, thr = u & 127;
      const int row0 = (thr >> 5) * 16 + ((thr & 31) >> 2);
      __nv_bfloat16* orow = out + (size_t)((2 * bp + w) * 64 + row0) * 1152 + p * 576 + slot * 16 + (thr & 3) * 2;
      const uint4* pr = g_part + (size_t)(tile * 16) * 36 * 128 + slot * 128 + thr;
      uint4 v[3][16];
#pragma unroll
      for (int pn = 0; pn < 3; pn++) {
        mbar_wait(ready0 + (w * 3 + pn) * 8);
        TRC(19 + pn);
#pragma unroll
        for (int c = 0; c < 16; c++) v[pn][c] = __ldcg(pr + (size_t)(c * 36 + pn * 12) * 128);
      }
#pragma unroll
      for (int pn = 0; pn < 3; pn++) {
        float a[8];
#pragma unroll
        for (int e = 0; e < 8; e++) a[e] = 0.f;
#pragma unroll
        for (int c = 0; c < 16; c++) {
          a[0] += bf_lo(v[pn][c].x);
          a[1] += bf_hi(v[pn][c].x);
          a[2] += bf_lo(v[pn][c].y);
          a[3] += bf_hi(v[pn][c].y);
          a[4] += bf_lo(v[pn][c].z);
          a[5] += bf_hi(v[pn][c].z);
          a[6] += bf_lo(v[pn][c].w);
          a[7] += bf_hi(v[pn][c].w);
        }
        __nv_bfloat16* op = orow + pn * 192;
        *reinterpret_cast<uint32_t*>(op) = pack_bf16(a[0], a[1]);
        *reinterpret_cast<uint32_t*>(op + 8 * 1152) = pack_bf16(a[2], a[3]);
        *reinterpret_cast<uint32_t*>(op + 8) = pack_bf16(a[4], a[5]);
        *reinterpret_cast<uint32_t*>(op + 8 * 1152 + 8) = pack_bf16(a[6], a[7]);
      }
    }
    TRC(22);
  }
}

typedef CUresult (*EncodeFn)(CUtensorMap*, CUtensorMapDataType, cuuint32_t, void*, const cuuint64_t*, const cuuint64_t*,
                             const cuuint32_t*, const cuuint32_t*, CUtensorMapInterleave, CUtensorMapSwizzle,
                             CUtensorMapL2promotion, CUtensorMapFloatOOBfill);

void encode3d(EncodeFn fn, CUtensorMap* m, void* ptr, uint64_t cols, uint64_t rows, uint32_t box_rows, uint32_t box_chunks) {
  cuuint64_t dims[3] = {64, rows, cols / 64};
  cuuint64_t strides[2] = {cols * 2, 128};
  cuuint32_t box[3] = {64, box_rows, box_chunks};
  cuuint32_t es[3] = {1, 1, 1};
  fn(m, CU_TENSOR_MAP_DATA_TYPE_BFLOAT16, 3, ptr, dims, strides, box, es, CU_TENSOR_MAP_INTERLEAVE_NONE,
     CU_TENSOR_MAP_SWIZZLE_128B, CU_TENSOR_MAP_L2_PROMOTION_L2_256B, CU_TENSOR_MAP_FLOAT_OOB_FILL_NONE);
}

}

extern "C" void kernel_launch(void* const* d_in, const int* in_sizes, int n_in, void* d_out, int out_size) {
  static EncodeFn fn = nullptr;
  if (!fn) {
    void* f = nullptr;
    cudaDriverEntryPointQueryResult st;
    cudaGetDriverEntryPoint("cuTensorMapEncodeTiled", &f, cudaEnableDefault, &st);
    fn = (EncodeFn)f;
    cudaFuncSetAttribute(fused_gqa_kernel, cudaFuncAttributeMaxDynamicSharedMemorySize, SMEM_BYTES);
  }
  Maps maps;
  for (int p = 0; p < 2; p++) {
    encode3d(fn, &maps.x[p], d_in[p * 5 + 0], kD, 512, 128, 1);
    encode3d(fn, &maps.k[p], d_in[p * 5 + 1], kDH, 8 * 16 * kSK, 128, 2);
    encode3d(fn, &maps.v[p], d_in[p * 5 + 2], kDH, 8 * 16 * kSK, 128, 2);
    encode3d(fn, &maps.wq[p], d_in[p * 5 + 3], kHQD, kD, 64, 4);
    encode3d(fn, &maps.wo[p], d_in[p * 5 + 4], kD, kHQD, 64, 3);
    maps.px[p] = (const char*)d_in[p * 5 + 0];
    maps.pwo[p] = (const char*)d_in[p * 5 + 4];
  }
  fused_gqa_kernel<<<128, 384, SMEM_BYTES>>>(maps, (__nv_bfloat16*)d_out);
}
```

```cpp
#include <cuda_runtime.h>
#include <cuda_bf16.h>
#include <cuda.h>
#include <stdint.h>

namespace {

constexpr int kD = 576, kHQD = 4096, kSK = 512, kDH = 128;

constexpr int N_WQ = 9, N_X = 9, N_KV = 16, N_WO = 12;
constexpr int N_ITEMS = N_WQ + N_X + N_KV + N_WO;
constexpr int T32 = 32 * 1024;
constexpr int WO_BYTES = 24 * 1024;
constexpr int PARK_OFF = 192 * 1024;
constexpr int BAR_OFF = 224 * 1024;
constexpr int SMEM_BYTES = BAR_OFF + 2 * N_ITEMS * 8 + 256;
constexpr int WQ0 = 0, X0 = N_WQ, KV0 = X0 + N_X, WO0 = KV0 + N_KV;
#define KV_INFLIGHT 2

__device__ __forceinline__ int wq_off(int kc) { return (kc & 3) * T32; }
__device__ __forceinline__ int x_off(int kc) { return ((kc & 2) ? 5 * T32 : PARK_OFF) + (kc & 1) * 16384; }
__device__ __forceinline__ int ring_off(int pos) { return (int)((0x053214u >> ((pos % 6) * 4)) & 15u) * T32; }
__device__ __forceinline__ int kv_off(int n) { return ring_off(n); }
__device__ __forceinline__ int wo_off(int m) { return (int)((0x607854321607ull >> (m * 4)) & 15ull) * WO_BYTES; }

__device__ uint4 g_part[16 * 16 * 36 * 128];
__device__ unsigned int g_cnt[16 * 4 * 32];

#define TR(role, ev)
#define TRC(ev)
constexpr uint32_t WAIT_CYCLES = 1u << 24;
constexpr uint32_t WAIT_LIMIT = 1u << 15;
__device__ __forceinline__ uint32_t smem_u32(const void* p) { return (uint32_t)__cvta_generic_to_shared(p); }
__device__ __forceinline__ void mbar_init(uint32_t bar, uint32_t cnt) {
  asm volatile("mbarrier.init.shared::cta.b64 [%0], %1;" ::"r"(bar), "r"(cnt) : "memory");
}
__device__ __forceinline__ void mbar_expect_tx(uint32_t bar, uint32_t bytes) {
  asm volatile("mbarrier.arrive.expect_tx.shared::cta.b64 _, [%0], %1;" ::"r"(bar), "r"(bytes) : "memory");
}
__device__ __forceinline__ void mbar_arrive(uint32_t bar) {
  asm volatile("mbarrier.arrive.shared::cta.b64 _, [%0];" ::"r"(bar) : "memory");
}
__device__ __forceinline__ bool mbar_try(uint32_t bar, uint32_t parity) {
  uint32_t ok;
  asm volatile(
      "{\n.reg .pred p;\nmbarrier.try_wait.parity.shared::cta.b64 p, [%1], %2;\nselp.u32 %0, 1, 0, p;\n}\n"
      : "=r"(ok)
      : "r"(bar), "r"(parity)
      : "memory");
  return ok != 0;
}
__device__ __forceinline__ void mbar_wait(uint32_t bar) {
  if (mbar_try(bar, 0)) return;
  const uint32_t t0 = (uint32_t)clock();
  while (!mbar_try(bar, 0))
    if ((uint32_t)clock() - t0 > WAIT_CYCLES) break;
}
__device__ __forceinline__ void tma_load3(uint32_t dst, const CUtensorMap* tm, int c0, int c1, int c2, uint32_t bar) {
  asm volatile(
      "cp.async.bulk.tensor.3d.shared::cluster.global.mbarrier::complete_tx::bytes [%0], [%1, {%3, %4, %5}], [%2];" ::"r"(dst),
      "l"(tm), "r"(bar), "r"(c0), "r"(c1), "r"(c2)
      : "memory");
}
__device__ __forceinline__ void l2_prefetch(const void* p) { asm volatile("prefetch.global.L2 [%0];" ::"l"(p) : "memory"); }
__device__ __forceinline__ void prefetch_tmap(const CUtensorMap* tm) {
  asm volatile("prefetch.tensormap [%0];" ::"l"(tm) : "memory");
}
__device__ __forceinline__ void named_bar(int id, int n) { asm volatile("bar.sync %0, %1;" ::"r"(id), "r"(n) : "memory"); }
__device__ __forceinline__ void named_arrive(int id, int n) { asm volatile("bar.arrive %0, %1;" ::"r"(id), "r"(n) : "memory"); }
__device__ __forceinline__ void wg_fence() { asm volatile("wgmma.fence.sync.aligned;" ::: "memory"); }
__device__ __forceinline__ void wg_commit() { asm volatile("wgmma.commit_group.sync.aligned;" ::: "memory"); }
template <int N>
__device__ __forceinline__ void wg_wait() { asm volatile("wgmma.wait_group.sync.aligned %0;" ::"n"(N) : "memory"); }
template <int N>
__device__ __forceinline__ void fence_regs(float (&d)[N]) {
#pragma unroll
  for (int i = 0; i < N; i++) asm volatile("" : "+f"(d[i])::"memory");
}
__device__ __forceinline__ void fence_regs32(float (&d)[64]) {
#pragma unroll
  for (int i = 0; i < 32; i++) asm volatile("" : "+f"(d[i])::"memory");
}
__device__ __forceinline__ uint64_t make_desc(uint32_t addr, uint32_t lbo, uint32_t sbo) {
  return (uint64_t)((addr & 0x3FFFF) >> 4) | ((uint64_t)(lbo >> 4) << 16) | ((uint64_t)(sbo >> 4) << 32) | (1ull << 62);
}
__device__ __forceinline__ uint32_t pack_bf16(float lo, float hi) {
  uint32_t r;
  asm("cvt.rn.bf16x2.f32 %0, %1, %2;" : "=r"(r) : "f"(hi), "f"(lo));
  return r;
}
__device__ __forceinline__ float ex2(float x) {
  float y;
  asm("ex2.approx.ftz.f32 %0, %1;" : "=f"(y) : "f"(x));
  return y;
}
__device__ __forceinline__ float bf_lo(uint32_t v) { return __uint_as_float(v << 16); }
__device__ __forceinline__ float bf_hi(uint32_t v) { return __uint_as_float(v & 0xffff0000u); }
template <int N>
__device__ __forceinline__ uint4 pack8(const float (&a)[N], int i) {
  return make_uint4(pack_bf16(a[8 * i], a[8 * i + 1]), pack_bf16(a[8 * i + 2], a[8 * i + 3]), pack_bf16(a[8 * i + 4], a[8 * i + 5]),
                    pack_bf16(a[8 * i + 6], a[8 * i + 7]));
}

__device__ __forceinline__ void wgmma_ss_n128_tb(float (&d)[64], uint64_t da, uint64_t db, int scale_d) {
  asm volatile("{\n.reg .pred p;\nsetp.ne.b32 p, %66, 0;\n"
    "wgmma.mma_async.sync.aligned.m64n128k16.f32.bf16.bf16 {%0, %1, %2, %3, %4, %5, %6, %7, %8, %9, %10, %11, %12, %13, %14, %15, %16, %17, %18, %19, %20, %21, %22, %23, %24, %25, %26, %27, %28, %29, %30, %31, %32, %33, %34, %35, %36, %37, %38, %39, %40, %41, %42, %43, %44, %45, %46, %47, %48, %49, %50, %51, %52, %53, %54, %55, %56, %57, %58, %59, %60, %61, %62, %63}, %64, %65, p, 1, 1, 0, 1;\n}\n"
    : "+f"(d[0]), "+f"(d[1]), "+f"(d[2]), "+f"(d[3]), "+f"(d[4]), "+f"(d[5]), "+f"(d[6]), "+f"(d[7]), "+f"(d[8]), "+f"(d[9]), "+f"(d[10]), "+f"(d[11]), "+f"(d[12]), "+f"(d[13]), "+f"(d[14]), "+f"(d[15]), "+f"(d[16]), "+f"(d[17]), "+f"(d[18]), "+f"(d[19]), "+f"(d[20]), "+f"(d[21]), "+f"(d[22]), "+f"(d[23]), "+f"(d[24]), "+f"(d[25]), "+f"(d[26]), "+f"(d[27]), "+f"(d[28]), "+f"(d[29]), "+f"(d[30]), "+f"(d[31]), "+f"(d[32]), "+f"(d[33]), "+f"(d[34]), "+f"(d[35]), "+f"(d[36]), "+f"(d[37]), "+f"(d[38]), "+f"(d[39]), "+f"(d[40]), "+f"(d[41]), "+f"(d[42]), "+f"(d[43]), "+f"(d[44]), "+f"(d[45]), "+f"(d[46]), "+f"(d[47]), "+f"(d[48]), "+f"(d[49]), "+f"(d[50]), "+f"(d[51]), "+f"(d[52]), "+f"(d[53]), "+f"(d[54]), "+f"(d[55]), "+f"(d[56]), "+f"(d[57]), "+f"(d[58]), "+f"(d[59]), "+f"(d[60]), "+f"(d[61]), "+f"(d[62]), "+f"(d[63])
    : "l"(da), "l"(db), "r"(scale_d));
}

__device__ __forceinline__ void wgmma_rs_n128(float (&d)[64], uint32_t a0, uint32_t a1, uint32_t a2, uint32_t a3, uint64_t db, int scale_d) {
  asm volatile("{\n.reg .pred p;\nsetp.ne.b32 p, %69, 0;\n"
    "wgmma.mma_async.sync.aligned.m64n128k16.f32.bf16.bf16 {%0, %1, %2, %3, %4, %5, %6, %7, %8, %9, %10, %11, %12, %13, %14, %15, %16, %17, %18, %19, %20, %21, %22, %23, %24, %25, %26, %27, %28, %29, %30, %31, %32, %33, %34, %35, %36, %37, %38, %39, %40, %41, %42, %43, %44, %45, %46, %47, %48, %49, %50, %51, %52, %53, %54, %55, %56, %57, %58, %59, %60, %61, %62, %63}, {%64, %65, %66, %67}, %68, p, 1, 1, 0;\n}\n"
    : "+f"(d[0]), "+f"(d[1]), "+f"(d[2]), "+f"(d[3]), "+f"(d[4]), "+f"(d[5]), "+f"(d[6]), "+f"(d[7]), "+f"(d[8]), "+f"(d[9]), "+f"(d[10]), "+f"(d[11]), "+f"(d[12]), "+f"(d[13]), "+f"(d[14]), "+f"(d[15]), "+f"(d[16]), "+f"(d[17]), "+f"(d[18]), "+f"(d[19]), "+f"(d[20]), "+f"(d[21]), "+f"(d[22]), "+f"(d[23]), "+f"(d[24]), "+f"(d[25]), "+f"(d[26]), "+f"(d[27]), "+f"(d[28]), "+f"(d[29]), "+f"(d[30]), "+f"(d[31]), "+f"(d[32]), "+f"(d[33]), "+f"(d[34]), "+f"(d[35]), "+f"(d[36]), "+f"(d[37]), "+f"(d[38]), "+f"(d[39]), "+f"(d[40]), "+f"(d[41]), "+f"(d[42]), "+f"(d[43]), "+f"(d[44]), "+f"(d[45]), "+f"(d[46]), "+f"(d[47]), "+f"(d[48]), "+f"(d[49]), "+f"(d[50]), "+f"(d[51]), "+f"(d[52]), "+f"(d[53]), "+f"(d[54]), "+f"(d[55]), "+f"(d[56]), "+f"(d[57]), "+f"(d[58]), "+f"(d[59]), "+f"(d[60]), "+f"(d[61]), "+f"(d[62]), "+f"(d[63])
    : "r"(a0), "r"(a1), "r"(a2), "r"(a3), "l"(db), "r"(scale_d));
}

__device__ __forceinline__ void wgmma_rs_n128_tb(float (&d)[64], uint32_t a0, uint32_t a1, uint32_t a2, uint32_t a3, uint64_t db, int scale_d) {
  asm volatile("{\n.reg .pred p;\nsetp.ne.b32 p, %69, 0;\n"
    "wgmma.mma_async.sync.aligned.m64n128k16.f32.bf16.bf16 {%0, %1, %2, %3, %4, %5, %6, %7, %8, %9, %10, %11, %12, %13, %14, %15, %16, %17, %18, %19, %20, %21, %22, %23, %24, %25, %26, %27, %28, %29, %30, %31, %32, %33, %34, %35, %36, %37, %38, %39, %40, %41, %42, %43, %44, %45, %46, %47, %48, %49, %50, %51, %52, %53, %54, %55, %56, %57, %58, %59, %60, %61, %62, %63}, {%64, %65, %66, %67}, %68, p, 1, 1, 1;\n}\n"
    : "+f"(d[0]), "+f"(d[1]), "+f"(d[2]), "+f"(d[3]), "+f"(d[4]), "+f"(d[5]), "+f"(d[6]), "+f"(d[7]), "+f"(d[8]), "+f"(d[9]), "+f"(d[10]), "+f"(d[11]), "+f"(d[12]), "+f"(d[13]), "+f"(d[14]), "+f"(d[15]), "+f"(d[16]), "+f"(d[17]), "+f"(d[18]), "+f"(d[19]), "+f"(d[20]), "+f"(d[21]), "+f"(d[22]), "+f"(d[23]), "+f"(d[24]), "+f"(d[25]), "+f"(d[26]), "+f"(d[27]), "+f"(d[28]), "+f"(d[29]), "+f"(d[30]), "+f"(d[31]), "+f"(d[32]), "+f"(d[33]), "+f"(d[34]), "+f"(d[35]), "+f"(d[36]), "+f"(d[37]), "+f"(d[38]), "+f"(d[39]), "+f"(d[40]), "+f"(d[41]), "+f"(d[42]), "+f"(d[43]), "+f"(d[44]), "+f"(d[45]), "+f"(d[46]), "+f"(d[47]), "+f"(d[48]), "+f"(d[49]), "+f"(d[50]), "+f"(d[51]), "+f"(d[52]), "+f"(d[53]), "+f"(d[54]), "+f"(d[55]), "+f"(d[56]), "+f"(d[57]), "+f"(d[58]), "+f"(d[59]), "+f"(d[60]), "+f"(d[61]), "+f"(d[62]), "+f"(d[63])
    : "r"(a0), "r"(a1), "r"(a2), "r"(a3), "l"(db), "r"(scale_d));
}

__device__ __forceinline__ void wgmma_rs_n128_z(float (&d)[64], uint32_t a0, uint32_t a1, uint32_t a2, uint32_t a3, uint64_t db) {
  asm volatile("{\n.reg .pred p;\nsetp.ne.b32 p, 0, 0;\n"
    "wgmma.mma_async.sync.aligned.m64n128k16.f32.bf16.bf16 {%0, %1, %2, %3, %4, %5, %6, %7, %8, %9, %10, %11, %12, %13, %14, %15, %16, %17, %18, %19, %20, %21, %22, %23, %24, %25, %26, %27, %28, %29, %30, %31, %32, %33, %34, %35, %36, %37, %38, %39, %40, %41, %42, %43, %44, %45, %46, %47, %48, %49, %50, %51, %52, %53, %54, %55, %56, %57, %58, %59, %60, %61, %62, %63}, {%64, %65, %66, %67}, %68, p, 1, 1, 0;\n}\n"
    : "=f"(d[0]), "=f"(d[1]), "=f"(d[2]), "=f"(d[3]), "=f"(d[4]), "=f"(d[5]), "=f"(d[6]), "=f"(d[7]), "=f"(d[8]), "=f"(d[9]), "=f"(d[10]), "=f"(d[11]), "=f"(d[12]), "=f"(d[13]), "=f"(d[14]), "=f"(d[15]), "=f"(d[16]), "=f"(d[17]), "=f"(d[18]), "=f"(d[19]), "=f"(d[20]), "=f"(d[21]), "=f"(d[22]), "=f"(d[23]), "=f"(d[24]), "=f"(d[25]), "=f"(d[26]), "=f"(d[27]), "=f"(d[28]), "=f"(d[29]), "=f"(d[30]), "=f"(d[31]), "=f"(d[32]), "=f"(d[33]), "=f"(d[34]), "=f"(d[35]), "=f"(d[36]), "=f"(d[37]), "=f"(d[38]), "=f"(d[39]), "=f"(d[40]), "=f"(d[41]), "=f"(d[42]), "=f"(d[43]), "=f"(d[44]), "=f"(d[45]), "=f"(d[46]), "=f"(d[47]), "=f"(d[48]), "=f"(d[49]), "=f"(d[50]), "=f"(d[51]), "=f"(d[52]), "=f"(d[53]), "=f"(d[54]), "=f"(d[55]), "=f"(d[56]), "=f"(d[57]), "=f"(d[58]), "=f"(d[59]), "=f"(d[60]), "=f"(d[61]), "=f"(d[62]), "=f"(d[63])
    : "r"(a0), "r"(a1), "r"(a2), "r"(a3), "l"(db));
}

__device__ __forceinline__ void wgmma_rs_n192_tb(float (&d)[64], float (&e)[64], uint32_t a0, uint32_t a1, uint32_t a2, uint32_t a3, uint64_t db) {
  asm volatile("{\n.reg .pred p;\nsetp.eq.b32 p, 0, 0;\n"
    "wgmma.mma_async.sync.aligned.m64n192k16.f32.bf16.bf16 {%0, %1, %2, %3, %4, %5, %6, %7, %8, %9, %10, %11, %12, %13, %14, %15, %16, %17, %18, %19, %20, %21, %22, %23, %24, %25, %26, %27, %28, %29, %30, %31, %32, %33, %34, %35, %36, %37, %38, %39, %40, %41, %42, %43, %44, %45, %46, %47, %48, %49, %50, %51, %52, %53, %54, %55, %56, %57, %58, %59, %60, %61, %62, %63, %64, %65, %66, %67, %68, %69, %70, %71, %72, %73, %74, %75, %76, %77, %78, %79, %80, %81, %82, %83, %84, %85, %86, %87, %88, %89, %90, %91, %92, %93, %94, %95}, {%96, %97, %98, %99}, %100, p, 1, 1, 1;\n}\n"
    : "+f"(d[0]), "+f"(d[1]), "+f"(d[2]), "+f"(d[3]), "+f"(d[4]), "+f"(d[5]), "+f"(d[6]), "+f"(d[7]), "+f"(d[8]), "+f"(d[9]), "+f"(d[10]), "+f"(d[11]), "+f"(d[12]), "+f"(d[13]), "+f"(d[14]), "+f"(d[15]), "+f"(d[16]), "+f"(d[17]), "+f"(d[18]), "+f"(d[19]), "+f"(d[20]), "+f"(d[21]), "+f"(d[22]), "+f"(d[23]), "+f"(d[24]), "+f"(d[25]), "+f"(d[26]), "+f"(d[27]), "+f"(d[28]), "+f"(d[29]), "+f"(d[30]), "+f"(d[31]), "+f"(d[32]), "+f"(d[33]), "+f"(d[34]), "+f"(d[35]), "+f"(d[36]), "+f"(d[37]), "+f"(d[38]), "+f"(d[39]), "+f"(d[40]), "+f"(d[41]), "+f"(d[42]), "+f"(d[43]), "+f"(d[44]), "+f"(d[45]), "+f"(d[46]), "+f"(d[47]), "+f"(d[48]), "+f"(d[49]), "+f"(d[50]), "+f"(d[51]), "+f"(d[52]), "+f"(d[53]), "+f"(d[54]), "+f"(d[55]), "+f"(d[56]), "+f"(d[57]), "+f"(d[58]), "+f"(d[59]), "+f"(d[60]), "+f"(d[61]), "+f"(d[62]), "+f"(d[63]), "+f"(e[0]), "+f"(e[1]), "+f"(e[2]), "+f"(e[3]), "+f"(e[4]), "+f"(e[5]), "+f"(e[6]), "+f"(e[7]), "+f"(e[8]), "+f"(e[9]), "+f"(e[10]), "+f"(e[11]), "+f"(e[12]), "+f"(e[13]), "+f"(e[14]), "+f"(e[15]), "+f"(e[16]), "+f"(e[17]), "+f"(e[18]), "+f"(e[19]), "+f"(e[20]), "+f"(e[21]), "+f"(e[22]), "+f"(e[23]), "+f"(e[24]), "+f"(e[25]), "+f"(e[26]), "+f"(e[27]), "+f"(e[28]), "+f"(e[29]), "+f"(e[30]), "+f"(e[31])
    : "r"(a0), "r"(a1), "r"(a2), "r"(a3), "l"(db));
}

__device__ __forceinline__ void wgmma_rs_n192_tb_z(float (&d)[64], float (&e)[64], uint32_t a0, uint32_t a1, uint32_t a2, uint32_t a3, uint64_t db) {
  asm volatile("{\n.reg .pred p;\nsetp.ne.b32 p, 0, 0;\n"
    "wgmma.mma_async.sync.aligned.m64n192k16.f32.bf16.bf16 {%0, %1, %2, %3, %4, %5, %6, %7, %8, %9, %10, %11, %12, %13, %14, %15, %16, %17, %18, %19, %20, %21, %22, %23, %24, %25, %26, %27, %28, %29, %30, %31, %32, %33, %34, %35, %36, %37, %38, %39, %40, %41, %42, %43, %44, %45, %46, %47, %48, %49, %50, %51, %52, %53, %54, %55, %56, %57, %58, %59, %60, %61, %62, %63, %64, %65, %66, %67, %68, %69, %70, %71, %72, %73, %74, %75, %76, %77, %78, %79, %80, %81, %82, %83, %84, %85, %86, %87, %88, %89, %90, %91, %92, %93, %94, %95}, {%96, %97, %98, %99}, %100, p, 1, 1, 1;\n}\n"
    : "=f"(d[0]), "=f"(d[1]), "=f"(d[2]), "=f"(d[3]), "=f"(d[4]), "=f"(d[5]), "=f"(d[6]), "=f"(d[7]), "=f"(d[8]), "=f"(d[9]), "=f"(d[10]), "=f"(d[11]), "=f"(d[12]), "=f"(d[13]), "=f"(d[14]), "=f"(d[15]), "=f"(d[16]), "=f"(d[17]), "=f"(d[18]), "=f"(d[19]), "=f"(d[20]), "=f"(d[21]), "=f"(d[22]), "=f"(d[23]), "=f"(d[24]), "=f"(d[25]), "=f"(d[26]), "=f"(d[27]), "=f"(d[28]), "=f"(d[29]), "=f"(d[30]), "=f"(d[31]), "=f"(d[32]), "=f"(d[33]), "=f"(d[34]), "=f"(d[35]), "=f"(d[36]), "=f"(d[37]), "=f"(d[38]), "=f"(d[39]), "=f"(d[40]), "=f"(d[41]), "=f"(d[42]), "=f"(d[43]), "=f"(d[44]), "=f"(d[45]), "=f"(d[46]), "=f"(d[47]), "=f"(d[48]), "=f"(d[49]), "=f"(d[50]), "=f"(d[51]), "=f"(d[52]), "=f"(d[53]), "=f"(d[54]), "=f"(d[55]), "=f"(d[56]), "=f"(d[57]), "=f"(d[58]), "=f"(d[59]), "=f"(d[60]), "=f"(d[61]), "=f"(d[62]), "=f"(d[63]), "=f"(e[0]), "=f"(e[1]), "=f"(e[2]), "=f"(e[3]), "=f"(e[4]), "=f"(e[5]), "=f"(e[6]), "=f"(e[7]), "=f"(e[8]), "=f"(e[9]), "=f"(e[10]), "=f"(e[11]), "=f"(e[12]), "=f"(e[13]), "=f"(e[14]), "=f"(e[15]), "=f"(e[16]), "=f"(e[17]), "=f"(e[18]), "=f"(e[19]), "=f"(e[20]), "=f"(e[21]), "=f"(e[22]), "=f"(e[23]), "=f"(e[24]), "=f"(e[25]), "=f"(e[26]), "=f"(e[27]), "=f"(e[28]), "=f"(e[29]), "=f"(e[30]), "=f"(e[31])
    : "r"(a0), "r"(a1), "r"(a2), "r"(a3), "l"(db));
}

struct Maps {
  CUtensorMap x[2], k[2], v[2], wq[2], wo[2];
  const char* px[2];
};

__device__ __forceinline__ void poll_tiles(int tile, const unsigned (&target)[3], uint32_t ready) {
#pragma unroll
  for (int pn = 0; pn < 3; pn++) {
    const unsigned* c = &g_cnt[(tile * 4 + pn) * 32];
    for (uint32_t it = 0; it < WAIT_LIMIT; ++it) {
      unsigned v;
      asm volatile("ld.acquire.gpu.global.u32 %0, [%1];" : "=r"(v) : "l"(c) : "memory");
      if ((int)(v - target[pn]) >= 0) break;
    }
    mbar_arrive(ready + pn * 8);
  }
}
__device__ __forceinline__ void read_targets(int tile, unsigned (&target)[3]) {
#pragma unroll
  for (int pn = 0; pn < 3; pn++) {
    unsigned v;
    asm volatile("ld.relaxed.gpu.global.u32 %0, [%1];" : "=r"(v) : "l"(&g_cnt[(tile * 4 + pn) * 32]) : "memory");
    target[pn] = (v / 16u + 1u) * 16u;
  }
}

__global__ void __launch_bounds__(384, 1)
fused_gqa_kernel(const __grid_constant__ Maps maps, __nv_bfloat16* __restrict__ out) {
  extern __shared__ __align__(1024) unsigned char smem[];
  const uint32_t sbase = smem_u32(smem);
  const uint32_t full0 = sbase + BAR_OFF;
  const uint32_t empty0 = full0 + N_ITEMS * 8;
  const uint32_t ready0 = empty0 + N_ITEMS * 8;
  const uint32_t pub0 = ready0 + 6 * 8;

  const int tid = threadIdx.x;
  const int wg = tid >> 7;
  const int bid = blockIdx.x;
  const int bp = bid & 3;
  const int h = (bid >> 2) & 15;
  const int p = bid >> 6;

  if (tid == 0) {
#pragma unroll
    for (int i = 0; i < 4; i++) mbar_init(full0 + (WQ0 + i) * 8, 1);
#pragma unroll
    for (int i = 0; i < 4; i++) mbar_init(full0 + (X0 + i) * 8, 1);
    mbar_init(full0 + KV0 * 8, 1);
    asm volatile("fence.mbarrier_init.release.cluster;" ::: "memory");
#pragma unroll
    for (int kc = 0; kc < 4; kc++) {
      mbar_expect_tx(full0 + (X0 + kc) * 8, 16384);
      tma_load3(sbase + x_off(kc), &maps.x[p], 0, bp * 128, kc, full0 + (X0 + kc) * 8);
      mbar_expect_tx(full0 + (WQ0 + kc) * 8, T32);
      tma_load3(sbase + wq_off(kc), &maps.wq[p], 0, kc * 64, h * 4, full0 + (WQ0 + kc) * 8);
    }
    mbar_expect_tx(full0 + KV0 * 8, T32);
    tma_load3(sbase + kv_off(0), &maps.k[p], 0, (2 * bp * 16 + h) * kSK, 0, full0 + KV0 * 8);
    TR(0, 56);
  } else if (tid >= 64 && tid < 96) {
    const char* base = maps.px[p] + (size_t)(bp * 128 + h * 8) * 1152;
#pragma unroll
    for (int i = 0; i < 3; i++)
      if ((tid & 31) + i * 32 < 72) l2_prefetch(base + ((tid & 31) + i * 32) * 128);
  } else if (tid == 32) {
    prefetch_tmap(&maps.v[p]);
    prefetch_tmap(&maps.wo[p]);
  } else if (tid >= 128) {
    const int i = tid - 128;
    if (i < N_ITEMS) {
      if (!(i < 4 || (i >= X0 && i < X0 + 4) || i == KV0)) mbar_init(full0 + i * 8, 1);
    } else if (i >= 64 && i < 64 + N_ITEMS) {
      mbar_init(empty0 + (i - 64) * 8, i == 64 + WQ0 ? 4 : 8);
    } else if (i >= 128 && i < 128 + 6) {
      mbar_init(ready0 + (i - 128) * 8, 1);
    } else if (i >= 160 && i < 160 + 6) {
      mbar_init(pub0 + (i - 160) * 8, 4);
    }
    asm volatile("fence.mbarrier_init.release.cluster;" ::: "memory");
  }
  __syncthreads();
  if (tid == 0) TR(0, 57);

  if (wg == 0) {
    asm volatile("setmaxnreg.dec.sync.aligned.u32 24;");
    if (tid == 0) {
      const int kvrow = (2 * bp * 16 + h) * kSK;
      auto load_kv = [&](int n) {
        if (n >= KV_INFLIGHT) mbar_wait(full0 + (KV0 + n - KV_INFLIGHT) * 8);
        const uint32_t fb = full0 + (KV0 + n) * 8;
        TR(0, KV0 + n);
        mbar_expect_tx(fb, T32);
        tma_load3(sbase + kv_off(n), (n & 1) ? &maps.v[p] : &maps.k[p], 0, kvrow + (n >> 3) * 16 * kSK + ((n & 7) >> 1) * 128, 0, fb);
      };
#pragma unroll 1
      for (int c = 0; c < 9; c++) {
        mbar_wait(empty0 + (X0 + c) * 8);
        if (c < 5) {
          mbar_expect_tx(full0 + (X0 + c + 4) * 8, 16384);
          tma_load3(sbase + x_off(c + 4), &maps.x[p], 0, bp * 128, c + 4, full0 + (X0 + c + 4) * 8);
        }
        if (c < 5) {
          TR(0, WQ0 + c + 4);
          mbar_expect_tx(full0 + (WQ0 + c + 4) * 8, T32);
          tma_load3(sbase + wq_off(c + 4), &maps.wq[p], 0, (c + 4) * 64, h * 4, full0 + (WQ0 + c + 4) * 8);
        } else if (c < 8) {
          load_kv(c - 4);
          if (c == 7) load_kv(4);
        } else {
          load_kv(5);
        }
      }
#pragma unroll 1
      for (int n = 6; n < N_KV; n++) {
        mbar_wait(empty0 + (KV0 + n - 6) * 8);
        load_kv(n);
      }
#pragma unroll 1
      for (int m = 0; m < N_WO; m++) {
        const int dep = m >= 9 ? WO0 + m - 9 : (m == 8 ? WQ0 : KV0 + 10 + (int)((0x55443210u >> (m * 4)) & 15u));
        mbar_wait(empty0 + dep * 8);
        const uint32_t fb = full0 + (WO0 + m) * 8;
        TR(0, WO0 + m);
        mbar_expect_tx(fb, WO_BYTES);
        tma_load3(sbase + wo_off(m), &maps.wo[p], 0, h * 256 + (m & 3) * 64, (m >> 2) * 3, fb);
      }
    } else if (tid == 96 || tid == 112) {
      const int w = (tid >> 4) & 1;
      unsigned target[3];
      read_targets(p * 8 + 2 * bp + w, target);
      mbar_wait(pub0 + w * 24);
      poll_tiles(p * 8 + 2 * bp + w, target, ready0 + w * 24);
    } else if (tid >= 32 && tid < 96) {
      const int w = (tid >> 5) - 1;
      if (tid & 31) return;
      const int tile = p * 8 + 2 * bp + w;
#pragma unroll 1
      for (int e = 0; e < 3; e++) {
        mbar_wait(pub0 + (w * 3 + e) * 8);
        __threadfence();
        asm volatile("red.relaxed.gpu.global.add.u32 [%0], 1;" ::"l"(&g_cnt[(tile * 4 + e) * 32]) : "memory");
      }
    }
  } else {
    asm volatile("setmaxnreg.inc.sync.aligned.u32 240;");
    const int w = wg - 1;
    const int t128 = tid & 127;
    const int lane = tid & 31;

    auto release = [&](int item) {
      __syncwarp();
      if (lane == 0) mbar_arrive(empty0 + item * 8);
    };

    TRC(0);
    const float cs = 0.08838834764831845f * 1.4426950408889634f;
    float s[64], o[64];
#pragma unroll
    for (int i = 0; i < 64; i++) s[i] = 0.f, o[i] = 0.f;
    uint32_t qf[32];
    uint4* park = reinterpret_cast<uint4*>(smem + PARK_OFF) + w * 1024 + t128;
    {
#pragma unroll 1
      for (int kc = 0; kc < 9; kc++) {
        mbar_wait(full0 + (X0 + kc) * 8);
        mbar_wait(full0 + (WQ0 + kc) * 8);
        if (kc == 0) TRC(1);
        const uint64_t da = make_desc(sbase + x_off(kc), 16, 1024);
        const uint64_t db = make_desc(sbase + wq_off(kc) + w * 16384, 8192, 1024);
        wg_fence();
#pragma unroll
        for (int ks = 0; ks < 4; ks++) {
          wgmma_ss_n128_tb(s, da + ks * 2, db + ks * 128, (kc | ks) != 0);
          wgmma_ss_n128_tb(o, da + 512 + ks * 2, db + ks * 128, (kc | ks) != 0);
        }
        wg_commit();
        wg_wait<0>();
        release(X0 + kc);
      }
      fence_regs(s);
      fence_regs(o);
#pragma unroll
      for (int i = 0; i < 32; i++) qf[i] = pack_bf16(s[2 * i], s[2 * i + 1]);
      named_bar(1, 256);
#pragma unroll
      for (int i = 0; i < 8; i++) park[i * 128] = pack8(o, i);
      TRC(2);
    }
#pragma unroll 1
    for (int bb = 0; bb < 2; bb++) {
#pragma unroll
      for (int i = 0; i < 64; i++) o[i] = 0.f;
      float m0 = -INFINITY, m1 = -INFINITY, l0 = 0.f, l1 = 0.f;
#pragma unroll 1
      for (int t = 0; t < 4; t++) {
        const int n = bb * 8 + t * 2;
        {
          const uint32_t base = sbase + kv_off(n);
          mbar_wait(full0 + (KV0 + n) * 8);
          if (n == 0 && w == 1) named_bar(4, 256);
          const uint64_t db = make_desc(base, 16, 1024);
          wg_fence();
          wgmma_rs_n128_z(s, qf[0], qf[1], qf[2], qf[3], db);
#pragma unroll
          for (int ks = 1; ks < 8; ks++)
            wgmma_rs_n128(s, qf[4 * ks], qf[4 * ks + 1], qf[4 * ks + 2], qf[4 * ks + 3], db + (ks >> 2) * 1024 + (ks & 3) * 2, 1);
          wg_commit();
          wg_wait<0>();
          fence_regs(s);
          if (n == 0 && w == 0) named_arrive(4, 256);
          release(KV0 + n);
        }
        float mx0 = s[0], mx1 = s[2];
#pragma unroll
        for (int g = 0; g < 16; g++) {
          mx0 = fmaxf(mx0, fmaxf(s[4 * g], s[4 * g + 1]));
          mx1 = fmaxf(mx1, fmaxf(s[4 * g + 2], s[4 * g + 3]));
        }
        mx0 = fmaxf(mx0, __shfl_xor_sync(0xffffffffu, mx0, 1));
        mx0 = fmaxf(mx0, __shfl_xor_sync(0xffffffffu, mx0, 2));
        mx1 = fmaxf(mx1, __shfl_xor_sync(0xffffffffu, mx1, 1));
        mx1 = fmaxf(mx1, __shfl_xor_sync(0xffffffffu, mx1, 2));
        const float mn0 = fmaxf(m0, mx0), mn1 = fmaxf(m1, mx1);
        const float a0 = ex2((m0 - mn0) * cs), a1 = ex2((m1 - mn1) * cs);
        m0 = mn0;
        m1 = mn1;
        const float ms0 = mn0 * cs, ms1 = mn1 * cs;
        float rs0 = 0.f, rs1 = 0.f;
        uint32_t pf[32];
#pragma unroll
        for (int g = 0; g < 16; g++) {
          const float p0 = ex2(fmaf(s[4 * g], cs, -ms0));
          const float p1 = ex2(fmaf(s[4 * g + 1], cs, -ms0));
          const float p2 = ex2(fmaf(s[4 * g + 2], cs, -ms1));
          const float p3 = ex2(fmaf(s[4 * g + 3], cs, -ms1));
          rs0 += p0 + p1;
          rs1 += p2 + p3;
          pf[2 * g] = pack_bf16(p0, p1);
          pf[2 * g + 1] = pack_bf16(p2, p3);
        }
        l0 = l0 * a0 + rs0;
        l1 = l1 * a1 + rs1;
#pragma unroll
        for (int g = 0; g < 16; g++) {
          o[4 * g] *= a0;
          o[4 * g + 1] *= a0;
          o[4 * g + 2] *= a1;
          o[4 * g + 3] *= a1;
        }
        {
          const uint32_t base = sbase + kv_off(n + 1);
          mbar_wait(full0 + (KV0 + n + 1) * 8);
          const uint64_t db = make_desc(base, 16384, 1024);
          wg_fence();
#pragma unroll
          for (int ks = 0; ks < 8; ks++)
            wgmma_rs_n128_tb(o, pf[4 * ks], pf[4 * ks + 1], pf[4 * ks + 2], pf[4 * ks + 3], db + ks * 128, 1);
          wg_commit();
          wg_wait<0>();
          fence_regs(o);
          release(KV0 + n + 1);
          TRC(3 + bb * 5 + t);
        }
      }
      l0 += __shfl_xor_sync(0xffffffffu, l0, 1);
      l0 += __shfl_xor_sync(0xffffffffu, l0, 2);
      l1 += __shfl_xor_sync(0xffffffffu, l1, 1);
      l1 += __shfl_xor_sync(0xffffffffu, l1, 2);
      const float i0 = 1.f / l0, i1 = 1.f / l1;
      if (bb == 0) {
#pragma unroll
        for (int i = 0; i < 8; i++) {
          const uint4 v = park[i * 128];
          qf[4 * i] = v.x;
          qf[4 * i + 1] = v.y;
          qf[4 * i + 2] = v.z;
          qf[4 * i + 3] = v.w;
          park[i * 128] = make_uint4(pack_bf16(o[8 * i] * i0, o[8 * i + 1] * i0), pack_bf16(o[8 * i + 2] * i1, o[8 * i + 3] * i1),
                                     pack_bf16(o[8 * i + 4] * i0, o[8 * i + 5] * i0), pack_bf16(o[8 * i + 6] * i1, o[8 * i + 7] * i1));
        }
        if (w == 1) named_arrive(5, 256);
      } else {
#pragma unroll
        for (int i = 0; i < 16; i++) {
          qf[2 * i] = pack_bf16(o[4 * i] * i0, o[4 * i + 1] * i0);
          qf[2 * i + 1] = pack_bf16(o[4 * i + 2] * i1, o[4 * i + 3] * i1);
        }
      }
    }
    uint32_t af[64];
    {
      const uint4* src = reinterpret_cast<const uint4*>(smem + PARK_OFF) + t128;
      if (w == 0) {
        named_bar(5, 256);
#pragma unroll
        for (int i = 0; i < 16; i++) {
          const uint4 v = src[i * 128];
          af[4 * i] = v.x;
          af[4 * i + 1] = v.y;
          af[4 * i + 2] = v.z;
          af[4 * i + 3] = v.w;
        }
#pragma unroll
        for (int i = 0; i < 8; i++) park[i * 128] = make_uint4(qf[4 * i], qf[4 * i + 1], qf[4 * i + 2], qf[4 * i + 3]);
        asm volatile("fence.proxy.async.shared::cta;" ::: "memory");
        named_arrive(1, 256);
      } else {
        named_bar(1, 256);
#pragma unroll
        for (int i = 0; i < 8; i++) {
          const uint4 v = src[i * 128];
          af[4 * i] = v.x;
          af[4 * i + 1] = v.y;
          af[4 * i + 2] = v.z;
          af[4 * i + 3] = v.w;
        }
#pragma unroll
        for (int i = 0; i < 32; i++) af[32 + i] = qf[i];
        asm volatile("fence.proxy.async.shared::cta;" ::: "memory");
        release(WQ0);
      }
    }
    TRC(12);
    const int tile = p * 8 + 2 * bp + w;
    uint4* part = g_part + (size_t)(tile * 16 + h) * 36 * 128 + t128;
#pragma unroll
    for (int pn = 0; pn < 3; pn++) {
#pragma unroll
      for (int kc = 0; kc < 4; kc++) {
        const int m = pn * 4 + kc;
        mbar_wait(full0 + (WO0 + m) * 8);
        const uint64_t db = make_desc(sbase + wo_off(m), 8192, 1024);
        wg_fence();
#pragma unroll
        for (int ks = 0; ks < 4; ks++) {
          const int a = (kc * 4 + ks) * 4;
          if ((kc | ks) == 0) wgmma_rs_n192_tb_z(s, o, af[a], af[a + 1], af[a + 2], af[a + 3], db);
          else wgmma_rs_n192_tb(s, o, af[a], af[a + 1], af[a + 2], af[a + 3], db + ks * 128);
        }
        wg_commit();
        if (kc > 0) {
          wg_wait<1>();
          if (m - 1 < 3) release(WO0 + m - 1);
        }
      }
      wg_wait<0>();
      fence_regs(s);
      fence_regs32(o);
      TRC(13 + pn * 2);
#pragma unroll
      for (int i = 0; i < 8; i++) __stcg(part + (pn * 12 + i) * 128, pack8(s, i));
#pragma unroll
      for (int i = 0; i < 4; i++) __stcg(part + (pn * 12 + 8 + i) * 128, pack8(o, i));
      __syncwarp();
      if (lane == 0) mbar_arrive(pub0 + (w * 3 + pn) * 8);
      TRC(14 + pn * 2);
    }
    if (t128 < 96) {
      const int u = h * 96 + t128;
      const int slot = u >> 7, thr = u & 127;
      const int row0 = (thr >> 5) * 16 + ((thr & 31) >> 2);
      __nv_bfloat16* orow = out + (size_t)((2 * bp + w) * 64 + row0) * 1152 + p * 576 + slot * 16 + (thr & 3) * 2;
      const uint4* pr = g_part + (size_t)(tile * 16) * 36 * 128 + slot * 128 + thr;
      uint4 v[3][16];
#pragma unroll
      for (int pn = 0; pn < 3; pn++) {
        mbar_wait(ready0 + (w * 3 + pn) * 8);
        TRC(19 + pn);
#pragma unroll
        for (int c = 0; c < 16; c++) v[pn][c] = __ldcg(pr + (size_t)(c * 36 + pn * 12) * 128);
      }
#pragma unroll
      for (int pn = 0; pn < 3; pn++) {
        float a[8];
#pragma unroll
        for (int e = 0; e < 8; e++) a[e] = 0.f;
#pragma unroll
        for (int c = 0; c < 16; c++) {
          a[0] += bf_lo(v[pn][c].x);
          a[1] += bf_hi(v[pn][c].x);
          a[2] += bf_lo(v[pn][c].y);
          a[3] += bf_hi(v[pn][c].y);
          a[4] += bf_lo(v[pn][c].z);
          a[5] += bf_hi(v[pn][c].z);
          a[6] += bf_lo(v[pn][c].w);
          a[7] += bf_hi(v[pn][c].w);
        }
        __nv_bfloat16* op = orow + pn * 192;
        *reinterpret_cast<uint32_t*>(op) = pack_bf16(a[0], a[1]);
        *reinterpret_cast<uint32_t*>(op + 8 * 1152) = pack_bf16(a[2], a[3]);
        *reinterpret_cast<uint32_t*>(op + 8) = pack_bf16(a[4], a[5]);
        *reinterpret_cast<uint32_t*>(op + 8 * 1152 + 8) = pack_bf16(a[6], a[7]);
      }
    }
    TRC(22);
  }
}

typedef CUresult (*EncodeFn)(CUtensorMap*, CUtensorMapDataType, cuuint32_t, void*, const cuuint64_t*, const cuuint64_t*,
                             const cuuint32_t*, const cuuint32_t*, CUtensorMapInterleave, CUtensorMapSwizzle,
                             CUtensorMapL2promotion, CUtensorMapFloatOOBfill);

void encode3d(EncodeFn fn, CUtensorMap* m, void* ptr, uint64_t cols, uint64_t rows, uint32_t box_rows, uint32_t box_chunks) {
  cuuint64_t dims[3] = {64, rows, cols / 64};
  cuuint64_t strides[2] = {cols * 2, 128};
  cuuint32_t box[3] = {64, box_rows, box_chunks};
  cuuint32_t es[3] = {1, 1, 1};
  fn(m, CU_TENSOR_MAP_DATA_TYPE_BFLOAT16, 3, ptr, dims, strides, box, es, CU_TENSOR_MAP_INTERLEAVE_NONE,
     CU_TENSOR_MAP_SWIZZLE_128B, CU_TENSOR_MAP_L2_PROMOTION_NONE, CU_TENSOR_MAP_FLOAT_OOB_FILL_NONE);
}

}

extern "C" void kernel_launch(void* const* d_in, const int* in_sizes, int n_in, void* d_out, int out_size) {
  static EncodeFn fn = nullptr;
  if (!fn) {
    void* f = nullptr;
    cudaDriverEntryPointQueryResult st;
    cudaGetDriverEntryPoint("cuTensorMapEncodeTiled", &f, cudaEnableDefault, &st);
    fn = (EncodeFn)f;
    cudaFuncSetAttribute(fused_gqa_kernel, cudaFuncAttributeMaxDynamicSharedMemorySize, SMEM_BYTES);
  }
  Maps maps;
  for (int p = 0; p < 2; p++) {
    encode3d(fn, &maps.x[p], d_in[p * 5 + 0], kD, 512, 128, 1);
    encode3d(fn, &maps.k[p], d_in[p * 5 + 1], kDH, 8 * 16 * kSK, 128, 2);
    encode3d(fn, &maps.v[p], d_in[p * 5 + 2], kDH, 8 * 16 * kSK, 128, 2);
    encode3d(fn, &maps.wq[p], d_in[p * 5 + 3], kHQD, kD, 64, 4);
    encode3d(fn, &maps.wo[p], d_in[p * 5 + 4], kD, kHQD, 64, 3);
    maps.px[p] = (const char*)d_in[p * 5 + 0];
  }
  fused_gqa_kernel<<<128, 384, SMEM_BYTES>>>(maps, (__nv_bfloat16*)d_out);
}
```

```cpp
#include <cuda_runtime.h>
#include <cuda_bf16.h>
#include <cuda.h>
#include <stdint.h>

namespace {

constexpr int kD = 576, kHQD = 4096, kSK = 512, kDH = 128;

constexpr int N_WQ = 9, N_X = 9, N_KV = 16, N_WO = 12;
constexpr int N_ITEMS = N_WQ + N_X + N_KV + N_WO;
constexpr int T32 = 32 * 1024;
constexpr int WO_BYTES = 24 * 1024;
constexpr int PARK_OFF = 192 * 1024;
constexpr int BAR_OFF = 224 * 1024;
constexpr int SMEM_BYTES = BAR_OFF + 2 * N_ITEMS * 8 + 256;
constexpr int WQ0 = 0, X0 = N_WQ, KV0 = X0 + N_X, WO0 = KV0 + N_KV;
#define KV_INFLIGHT 2

__device__ __forceinline__ int wq_off(int kc) { return (kc & 3) * T32; }
__device__ __forceinline__ int x_off(int kc) { return ((kc & 2) ? 5 * T32 : PARK_OFF) + (kc & 1) * 16384; }
__device__ __forceinline__ int ring_off(int pos) { return (int)((0x053214u >> ((pos % 6) * 4)) & 15u) * T32; }
__device__ __forceinline__ int kv_off(int n) { return ring_off(n); }
__device__ __forceinline__ int wo_off(int m) { return (int)((0x607854321607ull >> (m * 4)) & 15ull) * WO_BYTES; }

__device__ uint4 g_part[16 * 16 * 40 * 128];
__device__ unsigned int g_cnt[16 * 4 * 32];

#define TR(role, ev)
#define TRC(ev)
constexpr uint32_t WAIT_CYCLES = 1u << 24;
constexpr uint32_t WAIT_LIMIT = 1u << 15;
__device__ __forceinline__ uint32_t smem_u32(const void* p) { return (uint32_t)__cvta_generic_to_shared(p); }
__device__ __forceinline__ void mbar_init(uint32_t bar, uint32_t cnt) {
  asm volatile("mbarrier.init.shared::cta.b64 [%0], %1;" ::"r"(bar), "r"(cnt) : "memory");
}
__device__ __forceinline__ void mbar_expect_tx(uint32_t bar, uint32_t bytes) {
  asm volatile("mbarrier.arrive.expect_tx.shared::cta.b64 _, [%0], %1;" ::"r"(bar), "r"(bytes) : "memory");
}
__device__ __forceinline__ void mbar_arrive(uint32_t bar) {
  asm volatile("mbarrier.arrive.shared::cta.b64 _, [%0];" ::"r"(bar) : "memory");
}
__device__ __forceinline__ bool mbar_try(uint32_t bar, uint32_t parity) {
  uint32_t ok;
  asm volatile(
      "{\n.reg .pred p;\nmbarrier.try_wait.parity.shared::cta.b64 p, [%1], %2;\nselp.u32 %0, 1, 0, p;\n}\n"
      : "=r"(ok)
      : "r"(bar), "r"(parity)
      : "memory");
  return ok != 0;
}
__device__ __forceinline__ void mbar_wait(uint32_t bar) {
  if (mbar_try(bar, 0)) return;
  const uint32_t t0 = (uint32_t)clock();
  while (!mbar_try(bar, 0))
    if ((uint32_t)clock() - t0 > WAIT_CYCLES) break;
}
__device__ __forceinline__ void tma_load3(uint32_t dst, const CUtensorMap* tm, int c0, int c1, int c2, uint32_t bar) {
  asm volatile(
      "cp.async.bulk.tensor.3d.shared::cluster.global.mbarrier::complete_tx::bytes [%0], [%1, {%3, %4, %5}], [%2];" ::"r"(dst),
      "l"(tm), "r"(bar), "r"(c0), "r"(c1), "r"(c2)
      : "memory");
}
__device__ __forceinline__ void l2_prefetch(const void* p) { asm volatile("prefetch.global.L2 [%0];" ::"l"(p) : "memory"); }
__device__ __forceinline__ void prefetch_tmap(const CUtensorMap* tm) {
  asm volatile("prefetch.tensormap [%0];" ::"l"(tm) : "memory");
}
__device__ __forceinline__ void named_bar(int id, int n) { asm volatile("bar.sync %0, %1;" ::"r"(id), "r"(n) : "memory"); }
__device__ __forceinline__ void named_arrive(int id, int n) { asm volatile("bar.arrive %0, %1;" ::"r"(id), "r"(n) : "memory"); }
__device__ __forceinline__ void wg_fence() { asm volatile("wgmma.fence.sync.aligned;" ::: "memory"); }
__device__ __forceinline__ void wg_commit() { asm volatile("wgmma.commit_group.sync.aligned;" ::: "memory"); }
template <int N>
__device__ __forceinline__ void wg_wait() { asm volatile("wgmma.wait_group.sync.aligned %0;" ::"n"(N) : "memory"); }
template <int N>
__device__ __forceinline__ void fence_regs(float (&d)[N]) {
#pragma unroll
  for (int i = 0; i < N; i++) asm volatile("" : "+f"(d[i])::"memory");
}
__device__ __forceinline__ void fence_regs32(float (&d)[64]) {
#pragma unroll
  for (int i = 0; i < 32; i++) asm volatile("" : "+f"(d[i])::"memory");
}
__device__ __forceinline__ uint64_t make_desc(uint32_t addr, uint32_t lbo, uint32_t sbo) {
  return (uint64_t)((addr & 0x3FFFF) >> 4) | ((uint64_t)(lbo >> 4) << 16) | ((uint64_t)(sbo >> 4) << 32) | (1ull << 62);
}
__device__ __forceinline__ uint32_t pack_bf16(float lo, float hi) {
  uint32_t r;
  asm("cvt.rn.bf16x2.f32 %0, %1, %2;" : "=r"(r) : "f"(hi), "f"(lo));
  return r;
}
__device__ __forceinline__ float ex2(float x) {
  float y;
  asm("ex2.approx.ftz.f32 %0, %1;" : "=f"(y) : "f"(x));
  return y;
}
__device__ __forceinline__ float bf_lo(uint32_t v) { return __uint_as_float(v << 16); }
__device__ __forceinline__ float bf_hi(uint32_t v) { return __uint_as_float(v & 0xffff0000u); }
template <int N>
__device__ __forceinline__ uint4 pack8(const float (&a)[N], int i) {
  return make_uint4(pack_bf16(a[8 * i], a[8 * i + 1]), pack_bf16(a[8 * i + 2], a[8 * i + 3]), pack_bf16(a[8 * i + 4], a[8 * i + 5]),
                    pack_bf16(a[8 * i + 6], a[8 * i + 7]));
}

__device__ __forceinline__ void wgmma_ss_n128_tb(float (&d)[64], uint64_t da, uint64_t db, int scale_d) {
  asm volatile("{\n.reg .pred p;\nsetp.ne.b32 p, %66, 0;\n"
    "wgmma.mma_async.sync.aligned.m64n128k16.f32.bf16.bf16 {%0, %1, %2, %3, %4, %5, %6, %7, %8, %9, %10, %11, %12, %13, %14, %15, %16, %17, %18, %19, %20, %21, %22, %23, %24, %25, %26, %27, %28, %29, %30, %31, %32, %33, %34, %35, %36, %37, %38, %39, %40, %41, %42, %43, %44, %45, %46, %47, %48, %49, %50, %51, %52, %53, %54, %55, %56, %57, %58, %59, %60, %61, %62, %63}, %64, %65, p, 1, 1, 0, 1;\n}\n"
    : "+f"(d[0]), "+f"(d[1]), "+f"(d[2]), "+f"(d[3]), "+f"(d[4]), "+f"(d[5]), "+f"(d[6]), "+f"(d[7]), "+f"(d[8]), "+f"(d[9]), "+f"(d[10]), "+f"(d[11]), "+f"(d[12]), "+f"(d[13]), "+f"(d[14]), "+f"(d[15]), "+f"(d[16]), "+f"(d[17]), "+f"(d[18]), "+f"(d[19]), "+f"(d[20]), "+f"(d[21]), "+f"(d[22]), "+f"(d[23]), "+f"(d[24]), "+f"(d[25]), "+f"(d[26]), "+f"(d[27]), "+f"(d[28]), "+f"(d[29]), "+f"(d[30]), "+f"(d[31]), "+f"(d[32]), "+f"(d[33]), "+f"(d[34]), "+f"(d[35]), "+f"(d[36]), "+f"(d[37]), "+f"(d[38]), "+f"(d[39]), "+f"(d[40]), "+f"(d[41]), "+f"(d[42]), "+f"(d[43]), "+f"(d[44]), "+f"(d[45]), "+f"(d[46]), "+f"(d[47]), "+f"(d[48]), "+f"(d[49]), "+f"(d[50]), "+f"(d[51]), "+f"(d[52]), "+f"(d[53]), "+f"(d[54]), "+f"(d[55]), "+f"(d[56]), "+f"(d[57]), "+f"(d[58]), "+f"(d[59]), "+f"(d[60]), "+f"(d[61]), "+f"(d[62]), "+f"(d[63])
    : "l"(da), "l"(db), "r"(scale_d));
}

__device__ __forceinline__ void wgmma_rs_n128(float (&d)[64], uint32_t a0, uint32_t a1, uint32_t a2, uint32_t a3, uint64_t db, int scale_d) {
  asm volatile("{\n.reg .pred p;\nsetp.ne.b32 p, %69, 0;\n"
    "wgmma.mma_async.sync.aligned.m64n128k16.f32.bf16.bf16 {%0, %1, %2, %3, %4, %5, %6, %7, %8, %9, %10, %11, %12, %13, %14, %15, %16, %17, %18, %19, %20, %21, %22, %23, %24, %25, %26, %27, %28, %29, %30, %31, %32, %33, %34, %35, %36, %37, %38, %39, %40, %41, %42, %43, %44, %45, %46, %47, %48, %49, %50, %51, %52, %53, %54, %55, %56, %57, %58, %59, %60, %61, %62, %63}, {%64, %65, %66, %67}, %68, p, 1, 1, 0;\n}\n"
    : "+f"(d[0]), "+f"(d[1]), "+f"(d[2]), "+f"(d[3]), "+f"(d[4]), "+f"(d[5]), "+f"(d[6]), "+f"(d[7]), "+f"(d[8]), "+f"(d[9]), "+f"(d[10]), "+f"(d[11]), "+f"(d[12]), "+f"(d[13]), "+f"(d[14]), "+f"(d[15]), "+f"(d[16]), "+f"(d[17]), "+f"(d[18]), "+f"(d[19]), "+f"(d[20]), "+f"(d[21]), "+f"(d[22]), "+f"(d[23]), "+f"(d[24]), "+f"(d[25]), "+f"(d[26]), "+f"(d[27]), "+f"(d[28]), "+f"(d[29]), "+f"(d[30]), "+f"(d[31]), "+f"(d[32]), "+f"(d[33]), "+f"(d[34]), "+f"(d[35]), "+f"(d[36]), "+f"(d[37]), "+f"(d[38]), "+f"(d[39]), "+f"(d[40]), "+f"(d[41]), "+f"(d[42]), "+f"(d[43]), "+f"(d[44]), "+f"(d[45]), "+f"(d[46]), "+f"(d[47]), "+f"(d[48]), "+f"(d[49]), "+f"(d[50]), "+f"(d[51]), "+f"(d[52]), "+f"(d[53]), "+f"(d[54]), "+f"(d[55]), "+f"(d[56]), "+f"(d[57]), "+f"(d[58]), "+f"(d[59]), "+f"(d[60]), "+f"(d[61]), "+f"(d[62]), "+f"(d[63])
    : "r"(a0), "r"(a1), "r"(a2), "r"(a3), "l"(db), "r"(scale_d));
}

__device__ __forceinline__ void wgmma_rs_n128_tb(float (&d)[64], uint32_t a0, uint32_t a1, uint32_t a2, uint32_t a3, uint64_t db, int scale_d) {
  asm volatile("{\n.reg .pred p;\nsetp.ne.b32 p, %69, 0;\n"
    "wgmma.mma_async.sync.aligned.m64n128k16.f32.bf16.bf16 {%0, %1, %2, %3, %4, %5, %6, %7, %8, %9, %10, %11, %12, %13, %14, %15, %16, %17, %18, %19, %20, %21, %22, %23, %24, %25, %26, %27, %28, %29, %30, %31, %32, %33, %34, %35, %36, %37, %38, %39, %40, %41, %42, %43, %44, %45, %46, %47, %48, %49, %50, %51, %52, %53, %54, %55, %56, %57, %58, %59, %60, %61, %62, %63}, {%64, %65, %66, %67}, %68, p, 1, 1, 1;\n}\n"
    : "+f"(d[0]), "+f"(d[1]), "+f"(d[2]), "+f"(d[3]), "+f"(d[4]), "+f"(d[5]), "+f"(d[6]), "+f"(d[7]), "+f"(d[8]), "+f"(d[9]), "+f"(d[10]), "+f"(d[11]), "+f"(d[12]), "+f"(d[13]), "+f"(d[14]), "+f"(d[15]), "+f"(d[16]), "+f"(d[17]), "+f"(d[18]), "+f"(d[19]), "+f"(d[20]), "+f"(d[21]), "+f"(d[22]), "+f"(d[23]), "+f"(d[24]), "+f"(d[25]), "+f"(d[26]), "+f"(d[27]), "+f"(d[28]), "+f"(d[29]), "+f"(d[30]), "+f"(d[31]), "+f"(d[32]), "+f"(d[33]), "+f"(d[34]), "+f"(d[35]), "+f"(d[36]), "+f"(d[37]), "+f"(d[38]), "+f"(d[39]), "+f"(d[40]), "+f"(d[41]), "+f"(d[42]), "+f"(d[43]), "+f"(d[44]), "+f"(d[45]), "+f"(d[46]), "+f"(d[47]), "+f"(d[48]), "+f"(d[49]), "+f"(d[50]), "+f"(d[51]), "+f"(d[52]), "+f"(d[53]), "+f"(d[54]), "+f"(d[55]), "+f"(d[56]), "+f"(d[57]), "+f"(d[58]), "+f"(d[59]), "+f"(d[60]), "+f"(d[61]), "+f"(d[62]), "+f"(d[63])
    : "r"(a0), "r"(a1), "r"(a2), "r"(a3), "l"(db), "r"(scale_d));
}

__device__ __forceinline__ void wgmma_rs_n128_z(float (&d)[64], uint32_t a0, uint32_t a1, uint32_t a2, uint32_t a3, uint64_t db) {
  asm volatile("{\n.reg .pred p;\nsetp.ne.b32 p, 0, 0;\n"
    "wgmma.mma_async.sync.aligned.m64n128k16.f32.bf16.bf16 {%0, %1, %2, %3, %4, %5, %6, %7, %8, %9, %10, %11, %12, %13, %14, %15, %16, %17, %18, %19, %20, %21, %22, %23, %24, %25, %26, %27, %28, %29, %30, %31, %32, %33, %34, %35, %36, %37, %38, %39, %40, %41, %42, %43, %44, %45, %46, %47, %48, %49, %50, %51, %52, %53, %54, %55, %56, %57, %58, %59, %60, %61, %62, %63}, {%64, %65, %66, %67}, %68, p, 1, 1, 0;\n}\n"
    : "=f"(d[0]), "=f"(d[1]), "=f"(d[2]), "=f"(d[3]), "=f"(d[4]), "=f"(d[5]), "=f"(d[6]), "=f"(d[7]), "=f"(d[8]), "=f"(d[9]), "=f"(d[10]), "=f"(d[11]), "=f"(d[12]), "=f"(d[13]), "=f"(d[14]), "=f"(d[15]), "=f"(d[16]), "=f"(d[17]), "=f"(d[18]), "=f"(d[19]), "=f"(d[20]), "=f"(d[21]), "=f"(d[22]), "=f"(d[23]), "=f"(d[24]), "=f"(d[25]), "=f"(d[26]), "=f"(d[27]), "=f"(d[28]), "=f"(d[29]), "=f"(d[30]), "=f"(d[31]), "=f"(d[32]), "=f"(d[33]), "=f"(d[34]), "=f"(d[35]), "=f"(d[36]), "=f"(d[37]), "=f"(d[38]), "=f"(d[39]), "=f"(d[40]), "=f"(d[41]), "=f"(d[42]), "=f"(d[43]), "=f"(d[44]), "=f"(d[45]), "=f"(d[46]), "=f"(d[47]), "=f"(d[48]), "=f"(d[49]), "=f"(d[50]), "=f"(d[51]), "=f"(d[52]), "=f"(d[53]), "=f"(d[54]), "=f"(d[55]), "=f"(d[56]), "=f"(d[57]), "=f"(d[58]), "=f"(d[59]), "=f"(d[60]), "=f"(d[61]), "=f"(d[62]), "=f"(d[63])
    : "r"(a0), "r"(a1), "r"(a2), "r"(a3), "l"(db));
}

__device__ __forceinline__ void wgmma_rs_n192_tb(float (&d)[64], float (&e)[64], uint32_t a0, uint32_t a1, uint32_t a2, uint32_t a3, uint64_t db) {
  asm volatile("{\n.reg .pred p;\nsetp.eq.b32 p, 0, 0;\n"
    "wgmma.mma_async.sync.aligned.m64n192k16.f32.bf16.bf16 {%0, %1, %2, %3, %4, %5, %6, %7, %8, %9, %10, %11, %12, %13, %14, %15, %16, %17, %18, %19, %20, %21, %22, %23, %24, %25, %26, %27, %28, %29, %30, %31, %32, %33, %34, %35, %36, %37, %38, %39, %40, %41, %42, %43, %44, %45, %46, %47, %48, %49, %50, %51, %52, %53, %54, %55, %56, %57, %58, %59, %60, %61, %62, %63, %64, %65, %66, %67, %68, %69, %70, %71, %72, %73, %74, %75, %76, %77, %78, %79, %80, %81, %82, %83, %84, %85, %86, %87, %88, %89, %90, %91, %92, %93, %94, %95}, {%96, %97, %98, %99}, %100, p, 1, 1, 1;\n}\n"
    : "+f"(d[0]), "+f"(d[1]), "+f"(d[2]), "+f"(d[3]), "+f"(d[4]), "+f"(d[5]), "+f"(d[6]), "+f"(d[7]), "+f"(d[8]), "+f"(d[9]), "+f"(d[10]), "+f"(d[11]), "+f"(d[12]), "+f"(d[13]), "+f"(d[14]), "+f"(d[15]), "+f"(d[16]), "+f"(d[17]), "+f"(d[18]), "+f"(d[19]), "+f"(d[20]), "+f"(d[21]), "+f"(d[22]), "+f"(d[23]), "+f"(d[24]), "+f"(d[25]), "+f"(d[26]), "+f"(d[27]), "+f"(d[28]), "+f"(d[29]), "+f"(d[30]), "+f"(d[31]), "+f"(d[32]), "+f"(d[33]), "+f"(d[34]), "+f"(d[35]), "+f"(d[36]), "+f"(d[37]), "+f"(d[38]), "+f"(d[39]), "+f"(d[40]), "+f"(d[41]), "+f"(d[42]), "+f"(d[43]), "+f"(d[44]), "+f"(d[45]), "+f"(d[46]), "+f"(d[47]), "+f"(d[48]), "+f"(d[49]), "+f"(d[50]), "+f"(d[51]), "+f"(d[52]), "+f"(d[53]), "+f"(d[54]), "+f"(d[55]), "+f"(d[56]), "+f"(d[57]), "+f"(d[58]), "+f"(d[59]), "+f"(d[60]), "+f"(d[61]), "+f"(d[62]), "+f"(d[63]), "+f"(e[0]), "+f"(e[1]), "+f"(e[2]), "+f"(e[3]), "+f"(e[4]), "+f"(e[5]), "+f"(e[6]), "+f"(e[7]), "+f"(e[8]), "+f"(e[9]), "+f"(e[10]), "+f"(e[11]), "+f"(e[12]), "+f"(e[13]), "+f"(e[14]), "+f"(e[15]), "+f"(e[16]), "+f"(e[17]), "+f"(e[18]), "+f"(e[19]), "+f"(e[20]), "+f"(e[21]), "+f"(e[22]), "+f"(e[23]), "+f"(e[24]), "+f"(e[25]), "+f"(e[26]), "+f"(e[27]), "+f"(e[28]), "+f"(e[29]), "+f"(e[30]), "+f"(e[31])
    : "r"(a0), "r"(a1), "r"(a2), "r"(a3), "l"(db));
}

__device__ __forceinline__ void wgmma_rs_n192_tb_z(float (&d)[64], float (&e)[64], uint32_t a0, uint32_t a1, uint32_t a2, uint32_t a3, uint64_t db) {
  asm volatile("{\n.reg .pred p;\nsetp.ne.b32 p, 0, 0;\n"
    "wgmma.mma_async.sync.aligned.m64n192k16.f32.bf16.bf16 {%0, %1, %2, %3, %4, %5, %6, %7, %8, %9, %10, %11, %12, %13, %14, %15, %16, %17, %18, %19, %20, %21, %22, %23, %24, %25, %26, %27, %28, %29, %30, %31, %32, %33, %34, %35, %36, %37, %38, %39, %40, %41, %42, %43, %44, %45, %46, %47, %48, %49, %50, %51, %52, %53, %54, %55, %56, %57, %58, %59, %60, %61, %62, %63, %64, %65, %66, %67, %68, %69, %70, %71, %72, %73, %74, %75, %76, %77, %78, %79, %80, %81, %82, %83, %84, %85, %86, %87, %88, %89, %90, %91, %92, %93, %94, %95}, {%96, %97, %98, %99}, %100, p, 1, 1, 1;\n}\n"
    : "=f"(d[0]), "=f"(d[1]), "=f"(d[2]), "=f"(d[3]), "=f"(d[4]), "=f"(d[5]), "=f"(d[6]), "=f"(d[7]), "=f"(d[8]), "=f"(d[9]), "=f"(d[10]), "=f"(d[11]), "=f"(d[12]), "=f"(d[13]), "=f"(d[14]), "=f"(d[15]), "=f"(d[16]), "=f"(d[17]), "=f"(d[18]), "=f"(d[19]), "=f"(d[20]), "=f"(d[21]), "=f"(d[22]), "=f"(d[23]), "=f"(d[24]), "=f"(d[25]), "=f"(d[26]), "=f"(d[27]), "=f"(d[28]), "=f"(d[29]), "=f"(d[30]), "=f"(d[31]), "=f"(d[32]), "=f"(d[33]), "=f"(d[34]), "=f"(d[35]), "=f"(d[36]), "=f"(d[37]), "=f"(d[38]), "=f"(d[39]), "=f"(d[40]), "=f"(d[41]), "=f"(d[42]), "=f"(d[43]), "=f"(d[44]), "=f"(d[45]), "=f"(d[46]), "=f"(d[47]), "=f"(d[48]), "=f"(d[49]), "=f"(d[50]), "=f"(d[51]), "=f"(d[52]), "=f"(d[53]), "=f"(d[54]), "=f"(d[55]), "=f"(d[56]), "=f"(d[57]), "=f"(d[58]), "=f"(d[59]), "=f"(d[60]), "=f"(d[61]), "=f"(d[62]), "=f"(d[63]), "=f"(e[0]), "=f"(e[1]), "=f"(e[2]), "=f"(e[3]), "=f"(e[4]), "=f"(e[5]), "=f"(e[6]), "=f"(e[7]), "=f"(e[8]), "=f"(e[9]), "=f"(e[10]), "=f"(e[11]), "=f"(e[12]), "=f"(e[13]), "=f"(e[14]), "=f"(e[15]), "=f"(e[16]), "=f"(e[17]), "=f"(e[18]), "=f"(e[19]), "=f"(e[20]), "=f"(e[21]), "=f"(e[22]), "=f"(e[23]), "=f"(e[24]), "=f"(e[25]), "=f"(e[26]), "=f"(e[27]), "=f"(e[28]), "=f"(e[29]), "=f"(e[30]), "=f"(e[31])
    : "r"(a0), "r"(a1), "r"(a2), "r"(a3), "l"(db));
}

struct Maps {
  CUtensorMap x[2], k[2], v[2], wq[2], wo[2];
  const char* px[2];
};

__device__ __forceinline__ uint4 pack6(float a0, float a1, float a2, float a3, float a4, float a5, uint32_t tag_hi) {
  const uint32_t p2 = pack_bf16(a2, a3);
  const uint32_t p4 = pack_bf16(a4, a5);
  return make_uint4(pack_bf16(a0, a1), (p2 & 0xffffu) | tag_hi, __byte_perm(p2, p4, 0x5432), (p4 >> 16) | tag_hi);
}
__device__ __forceinline__ uint4 ld_relaxed_v4(const uint4* p) {
  unsigned long long lo, hi;
  asm volatile("ld.relaxed.gpu.global.v2.b64 {%0, %1}, [%2];" : "=l"(lo), "=l"(hi) : "l"(p) : "memory");
  return make_uint4((uint32_t)lo, (uint32_t)(lo >> 32), (uint32_t)hi, (uint32_t)(hi >> 32));
}
__device__ __forceinline__ void st_relaxed_v4(uint4* p, uint4 v) {
  const unsigned long long lo = (unsigned long long)v.x | ((unsigned long long)v.y << 32);
  const unsigned long long hi = (unsigned long long)v.z | ((unsigned long long)v.w << 32);
  asm volatile("st.relaxed.gpu.global.v2.b64 [%0], {%1, %2};" ::"l"(p), "l"(lo), "l"(hi) : "memory");
}
__device__ __forceinline__ void poll_tiles(int tile, const unsigned (&target)[3], uint32_t ready) {
#pragma unroll
  for (int pn = 0; pn < 2; pn++) {
    const unsigned* c = &g_cnt[(tile * 4 + pn) * 32];
    for (uint32_t it = 0; it < WAIT_LIMIT; ++it) {
      unsigned v;
      asm volatile("ld.acquire.gpu.global.u32 %0, [%1];" : "=r"(v) : "l"(c) : "memory");
      if ((int)(v - target[pn]) >= 0) break;
    }
    mbar_arrive(ready + pn * 8);
  }
}
__device__ __forceinline__ void read_targets(int tile, unsigned (&target)[3]) {
#pragma unroll
  for (int pn = 0; pn < 3; pn++) {
    unsigned v;
    asm volatile("ld.relaxed.gpu.global.u32 %0, [%1];" : "=r"(v) : "l"(&g_cnt[(tile * 4 + pn) * 32]) : "memory");
    target[pn] = (v / 16u + 1u) * 16u;
  }
}

__global__ void __launch_bounds__(384, 1)
fused_gqa_kernel(const __grid_constant__ Maps maps, __nv_bfloat16* __restrict__ out) {
  extern __shared__ __align__(1024) unsigned char smem[];
  const uint32_t sbase = smem_u32(smem);
  const uint32_t full0 = sbase + BAR_OFF;
  const uint32_t empty0 = full0 + N_ITEMS * 8;
  const uint32_t ready0 = empty0 + N_ITEMS * 8;
  const uint32_t pub0 = ready0 + 6 * 8;
  volatile uint32_t* s_tag = reinterpret_cast<volatile uint32_t*>(smem + BAR_OFF + 2 * N_ITEMS * 8 + 128);

  const int tid = threadIdx.x;
  const int wg = tid >> 7;
  const int bid = blockIdx.x;
  const int bp = bid & 3;
  const int h = (bid >> 2) & 15;
  const int p = bid >> 6;

  if (tid == 0) {
#pragma unroll
    for (int i = 0; i < 4; i++) mbar_init(full0 + (WQ0 + i) * 8, 1);
#pragma unroll
    for (int i = 0; i < 4; i++) mbar_init(full0 + (X0 + i) * 8, 1);
    mbar_init(full0 + KV0 * 8, 1);
    asm volatile("fence.mbarrier_init.release.cluster;" ::: "memory");
#pragma unroll
    for (int kc = 0; kc < 4; kc++) {
      mbar_expect_tx(full0 + (X0 + kc) * 8, 16384);
      tma_load3(sbase + x_off(kc), &maps.x[p], 0, bp * 128, kc, full0 + (X0 + kc) * 8);
      mbar_expect_tx(full0 + (WQ0 + kc) * 8, T32);
      tma_load3(sbase + wq_off(kc), &maps.wq[p], 0, kc * 64, h * 4, full0 + (WQ0 + kc) * 8);
    }
    mbar_expect_tx(full0 + KV0 * 8, T32);
    tma_load3(sbase + kv_off(0), &maps.k[p], 0, (2 * bp * 16 + h) * kSK, 0, full0 + KV0 * 8);
    TR(0, 56);
  } else if (tid >= 64 && tid < 96) {
    const char* base = maps.px[p] + (size_t)(bp * 128 + h * 8) * 1152;
#pragma unroll
    for (int i = 0; i < 3; i++)
      if ((tid & 31) + i * 32 < 72) l2_prefetch(base + ((tid & 31) + i * 32) * 128);
  } else if (tid == 32) {
    prefetch_tmap(&maps.v[p]);
    prefetch_tmap(&maps.wo[p]);
  } else if (tid >= 128) {
    const int i = tid - 128;
    if (i < N_ITEMS) {
      if (!(i < 4 || (i >= X0 && i < X0 + 4) || i == KV0)) mbar_init(full0 + i * 8, 1);
    } else if (i >= 64 && i < 64 + N_ITEMS) {
      mbar_init(empty0 + (i - 64) * 8, i == 64 + WQ0 ? 4 : 8);
    } else if (i >= 128 && i < 128 + 6) {
      mbar_init(ready0 + (i - 128) * 8, 1);
    } else if (i >= 160 && i < 160 + 6) {
      mbar_init(pub0 + (i - 160) * 8, 4);
    }
    asm volatile("fence.mbarrier_init.release.cluster;" ::: "memory");
  }
  __syncthreads();
  if (tid == 0) TR(0, 57);

  if (wg == 0) {
    asm volatile("setmaxnreg.dec.sync.aligned.u32 24;");
    if (tid == 0) {
      const int kvrow = (2 * bp * 16 + h) * kSK;
      auto load_kv = [&](int n) {
        if (n >= KV_INFLIGHT) mbar_wait(full0 + (KV0 + n - KV_INFLIGHT) * 8);
        const uint32_t fb = full0 + (KV0 + n) * 8;
        TR(0, KV0 + n);
        mbar_expect_tx(fb, T32);
        tma_load3(sbase + kv_off(n), (n & 1) ? &maps.v[p] : &maps.k[p], 0, kvrow + (n >> 3) * 16 * kSK + ((n & 7) >> 1) * 128, 0, fb);
      };
#pragma unroll 1
      for (int c = 0; c < 9; c++) {
        mbar_wait(empty0 + (X0 + c) * 8);
        if (c < 5) {
          mbar_expect_tx(full0 + (X0 + c + 4) * 8, 16384);
          tma_load3(sbase + x_off(c + 4), &maps.x[p], 0, bp * 128, c + 4, full0 + (X0 + c + 4) * 8);
        }
        if (c < 5) {
          TR(0, WQ0 + c + 4);
          mbar_expect_tx(full0 + (WQ0 + c + 4) * 8, T32);
          tma_load3(sbase + wq_off(c + 4), &maps.wq[p], 0, (c + 4) * 64, h * 4, full0 + (WQ0 + c + 4) * 8);
        } else if (c < 8) {
          load_kv(c - 4);
          if (c == 7) load_kv(4);
        } else {
          load_kv(5);
        }
      }
#pragma unroll 1
      for (int n = 6; n < N_KV; n++) {
        mbar_wait(empty0 + (KV0 + n - 6) * 8);
        load_kv(n);
      }
#pragma unroll 1
      for (int m = 0; m < N_WO; m++) {
        const int dep = m >= 9 ? WO0 + m - 9 : (m == 8 ? WQ0 : KV0 + 10 + (int)((0x55443210u >> (m * 4)) & 15u));
        mbar_wait(empty0 + dep * 8);
        const uint32_t fb = full0 + (WO0 + m) * 8;
        TR(0, WO0 + m);
        mbar_expect_tx(fb, WO_BYTES);
        tma_load3(sbase + wo_off(m), &maps.wo[p], 0, h * 256 + (m & 3) * 64, (m >> 2) * 3, fb);
      }
    } else if (tid == 96 || tid == 112) {
      const int w = (tid >> 4) & 1;
      unsigned target[3];
      read_targets(p * 8 + 2 * bp + w, target);
      s_tag[w] = target[0] << 12;
      mbar_arrive(ready0 + w * 24 + 16);
      mbar_wait(pub0 + w * 24);
      poll_tiles(p * 8 + 2 * bp + w, target, ready0 + w * 24);
    } else if (tid >= 32 && tid < 96) {
      const int w = (tid >> 5) - 1;
      if (tid & 31) return;
      const int tile = p * 8 + 2 * bp + w;
#pragma unroll 1
      for (int e = 0; e < 2; e++) {
        mbar_wait(pub0 + (w * 3 + e) * 8);
        __threadfence();
        asm volatile("red.relaxed.gpu.global.add.u32 [%0], 1;" ::"l"(&g_cnt[(tile * 4 + e) * 32]) : "memory");
      }
    }
  } else {
    asm volatile("setmaxnreg.inc.sync.aligned.u32 240;");
    const int w = wg - 1;
    const int t128 = tid & 127;
    const int lane = tid & 31;

    auto release = [&](int item) {
      __syncwarp();
      if (lane == 0) mbar_arrive(empty0 + item * 8);
    };

    TRC(0);
    const float cs = 0.08838834764831845f * 1.4426950408889634f;
    float s[64], o[64];
#pragma unroll
    for (int i = 0; i < 64; i++) s[i] = 0.f, o[i] = 0.f;
    uint32_t qf[32];
    uint4* park = reinterpret_cast<uint4*>(smem + PARK_OFF) + w * 1024 + t128;
    {
#pragma unroll 1
      for (int kc = 0; kc < 9; kc++) {
        mbar_wait(full0 + (X0 + kc) * 8);
        mbar_wait(full0 + (WQ0 + kc) * 8);
        if (kc == 0) TRC(1);
        const uint64_t da = make_desc(sbase + x_off(kc), 16, 1024);
        const uint64_t db = make_desc(sbase + wq_off(kc) + w * 16384, 8192, 1024);
        wg_fence();
#pragma unroll
        for (int ks = 0; ks < 4; ks++) {
          wgmma_ss_n128_tb(s, da + ks * 2, db + ks * 128, (kc | ks) != 0);
          wgmma_ss_n128_tb(o, da + 512 + ks * 2, db + ks * 128, (kc | ks) != 0);
        }
        wg_commit();
        wg_wait<0>();
        release(X0 + kc);
      }
      fence_regs(s);
      fence_regs(o);
#pragma unroll
      for (int i = 0; i < 32; i++) qf[i] = pack_bf16(s[2 * i], s[2 * i + 1]);
      named_bar(1, 256);
#pragma unroll
      for (int i = 0; i < 8; i++) park[i * 128] = pack8(o, i);
      TRC(2);
    }
#pragma unroll 1
    for (int bb = 0; bb < 2; bb++) {
#pragma unroll
      for (int i = 0; i < 64; i++) o[i] = 0.f;
      float m0 = -INFINITY, m1 = -INFINITY, l0 = 0.f, l1 = 0.f;
#pragma unroll 1
      for (int t = 0; t < 4; t++) {
        const int n = bb * 8 + t * 2;
        {
          const uint32_t base = sbase + kv_off(n);
          mbar_wait(full0 + (KV0 + n) * 8);
          if (n == 0 && w == 1) named_bar(4, 256);
          const uint64_t db = make_desc(base, 16, 1024);
          wg_fence();
          wgmma_rs_n128_z(s, qf[0], qf[1], qf[2], qf[3], db);
#pragma unroll
          for (int ks = 1; ks < 8; ks++)
            wgmma_rs_n128(s, qf[4 * ks], qf[4 * ks + 1], qf[4 * ks + 2], qf[4 * ks + 3], db + (ks >> 2) * 1024 + (ks & 3) * 2, 1);
          wg_commit();
          wg_wait<0>();
          fence_regs(s);
          if (n == 0 && w == 0) named_arrive(4, 256);
          release(KV0 + n);
        }
        float mx0 = s[0], mx1 = s[2];
#pragma unroll
        for (int g = 0; g < 16; g++) {
          mx0 = fmaxf(mx0, fmaxf(s[4 * g], s[4 * g + 1]));
          mx1 = fmaxf(mx1, fmaxf(s[4 * g + 2], s[4 * g + 3]));
        }
        mx0 = fmaxf(mx0, __shfl_xor_sync(0xffffffffu, mx0, 1));
        mx0 = fmaxf(mx0, __shfl_xor_sync(0xffffffffu, mx0, 2));
        mx1 = fmaxf(mx1, __shfl_xor_sync(0xffffffffu, mx1, 1));
        mx1 = fmaxf(mx1, __shfl_xor_sync(0xffffffffu, mx1, 2));
        const float mn0 = fmaxf(m0, mx0), mn1 = fmaxf(m1, mx1);
        const float a0 = ex2((m0 - mn0) * cs), a1 = ex2((m1 - mn1) * cs);
        m0 = mn0;
        m1 = mn1;
        const float ms0 = mn0 * cs, ms1 = mn1 * cs;
        float rs0 = 0.f, rs1 = 0.f;
        uint32_t pf[32];
#pragma unroll
        for (int g = 0; g < 16; g++) {
          const float p0 = ex2(fmaf(s[4 * g], cs, -ms0));
          const float p1 = ex2(fmaf(s[4 * g + 1], cs, -ms0));
          const float p2 = ex2(fmaf(s[4 * g + 2], cs, -ms1));
          const float p3 = ex2(fmaf(s[4 * g + 3], cs, -ms1));
          rs0 += p0 + p1;
          rs1 += p2 + p3;
          pf[2 * g] = pack_bf16(p0, p1);
          pf[2 * g + 1] = pack_bf16(p2, p3);
        }
        l0 = l0 * a0 + rs0;
        l1 = l1 * a1 + rs1;
#pragma unroll
        for (int g = 0; g < 16; g++) {
          o[4 * g] *= a0;
          o[4 * g + 1] *= a0;
          o[4 * g + 2] *= a1;
          o[4 * g + 3] *= a1;
        }
        {
          const uint32_t base = sbase + kv_off(n + 1);
          mbar_wait(full0 + (KV0 + n + 1) * 8);
          const uint64_t db = make_desc(base, 16384, 1024);
          wg_fence();
#pragma unroll
          for (int ks = 0; ks < 8; ks++)
            wgmma_rs_n128_tb(o, pf[4 * ks], pf[4 * ks + 1], pf[4 * ks + 2], pf[4 * ks + 3], db + ks * 128, 1);
          wg_commit();
          wg_wait<0>();
          fence_regs(o);
          release(KV0 + n + 1);
          TRC(3 + bb * 5 + t);
        }
      }
      l0 += __shfl_xor_sync(0xffffffffu, l0, 1);
      l0 += __shfl_xor_sync(0xffffffffu, l0, 2);
      l1 += __shfl_xor_sync(0xffffffffu, l1, 1);
      l1 += __shfl_xor_sync(0xffffffffu, l1, 2);
      const float i0 = 1.f / l0, i1 = 1.f / l1;
      if (bb == 0) {
#pragma unroll
        for (int i = 0; i < 8; i++) {
          const uint4 v = park[i * 128];
          qf[4 * i] = v.x;
          qf[4 * i + 1] = v.y;
          qf[4 * i + 2] = v.z;
          qf[4 * i + 3] = v.w;
          park[i * 128] = make_uint4(pack_bf16(o[8 * i] * i0, o[8 * i + 1] * i0), pack_bf16(o[8 * i + 2] * i1, o[8 * i + 3] * i1),
                                     pack_bf16(o[8 * i + 4] * i0, o[8 * i + 5] * i0), pack_bf16(o[8 * i + 6] * i1, o[8 * i + 7] * i1));
        }
        if (w == 1) named_arrive(5, 256);
      } else {
#pragma unroll
        for (int i = 0; i < 16; i++) {
          qf[2 * i] = pack_bf16(o[4 * i] * i0, o[4 * i + 1] * i0);
          qf[2 * i + 1] = pack_bf16(o[4 * i + 2] * i1, o[4 * i + 3] * i1);
        }
      }
    }
    uint32_t af[64];
    {
      const uint4* src = reinterpret_cast<const uint4*>(smem + PARK_OFF) + t128;
      if (w == 0) {
        named_bar(5, 256);
#pragma unroll
        for (int i = 0; i < 16; i++) {
          const uint4 v = src[i * 128];
          af[4 * i] = v.x;
          af[4 * i + 1] = v.y;
          af[4 * i + 2] = v.z;
          af[4 * i + 3] = v.w;
        }
#pragma unroll
        for (int i = 0; i < 8; i++) park[i * 128] = make_uint4(qf[4 * i], qf[4 * i + 1], qf[4 * i + 2], qf[4 * i + 3]);
        asm volatile("fence.proxy.async.shared::cta;" ::: "memory");
        named_arrive(1, 256);
      } else {
        named_bar(1, 256);
#pragma unroll
        for (int i = 0; i < 8; i++) {
          const uint4 v = src[i * 128];
          af[4 * i] = v.x;
          af[4 * i + 1] = v.y;
          af[4 * i + 2] = v.z;
          af[4 * i + 3] = v.w;
        }
#pragma unroll
        for (int i = 0; i < 32; i++) af[32 + i] = qf[i];
        asm volatile("fence.proxy.async.shared::cta;" ::: "memory");
        release(WQ0);
      }
    }
    TRC(12);
    const int tile = p * 8 + 2 * bp + w;
    uint4* part = g_part + (size_t)(tile * 16 + h) * 40 * 128 + t128;
    mbar_wait(ready0 + w * 24 + 16);
    const uint32_t tag = s_tag[w] & 0xffff0000u;
#pragma unroll
    for (int pn = 0; pn < 3; pn++) {
#pragma unroll
      for (int kc = 0; kc < 4; kc++) {
        const int m = pn * 4 + kc;
        mbar_wait(full0 + (WO0 + m) * 8);
        const uint64_t db = make_desc(sbase + wo_off(m), 8192, 1024);
        wg_fence();
#pragma unroll
        for (int ks = 0; ks < 4; ks++) {
          const int a = (kc * 4 + ks) * 4;
          if ((kc | ks) == 0) wgmma_rs_n192_tb_z(s, o, af[a], af[a + 1], af[a + 2], af[a + 3], db);
          else wgmma_rs_n192_tb(s, o, af[a], af[a + 1], af[a + 2], af[a + 3], db + ks * 128);
        }
        wg_commit();
        if (kc > 0) {
          wg_wait<1>();
          if (m - 1 < 3) release(WO0 + m - 1);
        }
      }
      wg_wait<0>();
      fence_regs(s);
      fence_regs32(o);
      TRC(13 + pn * 2);
      if (pn < 2) {
#pragma unroll
        for (int i = 0; i < 8; i++) __stcg(part + (pn * 12 + i) * 128, pack8(s, i));
#pragma unroll
        for (int i = 0; i < 4; i++) __stcg(part + (pn * 12 + 8 + i) * 128, pack8(o, i));
        __syncwarp();
        if (lane == 0) mbar_arrive(pub0 + (w * 3 + pn) * 8);
      } else {
#pragma unroll
        for (int i = 0; i < 16; i++) {
          float a[6];
#pragma unroll
          for (int e = 0; e < 6; e++) a[e] = (6 * i + e < 64) ? s[(6 * i + e) & 63] : o[(6 * i + e - 64) & 63];
          st_relaxed_v4(part + (24 + i) * 128, pack6(a[0], a[1], a[2], a[3], a[4], a[5], tag));
        }
      }
      TRC(14 + pn * 2);
    }
    if (t128 < 96) {
      const int u = h * 96 + t128;
      const int slot = u >> 7, thr = u & 127;
      const int row0 = (thr >> 5) * 16 + ((thr & 31) >> 2);
      __nv_bfloat16* orow = out + (size_t)((2 * bp + w) * 64 + row0) * 1152 + p * 576 + slot * 16 + (thr & 3) * 2;
      const uint4* pr = g_part + (size_t)(tile * 16) * 40 * 128 + slot * 128 + thr;
      uint4 v[2][16];
#pragma unroll
      for (int pn = 0; pn < 2; pn++) {
        mbar_wait(ready0 + (w * 3 + pn) * 8);
        TRC(19 + pn);
#pragma unroll
        for (int c = 0; c < 16; c++) v[pn][c] = __ldcg(pr + (size_t)(c * 40 + pn * 12) * 128);
      }
#pragma unroll
      for (int pn = 0; pn < 2; pn++) {
        float a[8];
#pragma unroll
        for (int e = 0; e < 8; e++) a[e] = 0.f;
#pragma unroll
        for (int c = 0; c < 16; c++) {
          a[0] += bf_lo(v[pn][c].x);
          a[1] += bf_hi(v[pn][c].x);
          a[2] += bf_lo(v[pn][c].y);
          a[3] += bf_hi(v[pn][c].y);
          a[4] += bf_lo(v[pn][c].z);
          a[5] += bf_hi(v[pn][c].z);
          a[6] += bf_lo(v[pn][c].w);
          a[7] += bf_hi(v[pn][c].w);
        }
        __nv_bfloat16* op = orow + pn * 192;
        *reinterpret_cast<uint32_t*>(op) = pack_bf16(a[0], a[1]);
        *reinterpret_cast<uint32_t*>(op + 8 * 1152) = pack_bf16(a[2], a[3]);
        *reinterpret_cast<uint32_t*>(op + 8) = pack_bf16(a[4], a[5]);
        *reinterpret_cast<uint32_t*>(op + 8 * 1152 + 8) = pack_bf16(a[6], a[7]);
      }
    }
    {
      const int row0 = (t128 >> 5) * 16 + (lane >> 2);
      __nv_bfloat16* orow = out + (size_t)((2 * bp + w) * 64 + row0) * 1152 + p * 576 + 384 + (lane & 3) * 2;
      const uint4* pr = g_part + (size_t)(tile * 16) * 40 * 128 + (24 + h) * 128 + t128;
      uint4 v[16];
#pragma unroll
      for (int c = 0; c < 16; c++) v[c] = ld_relaxed_v4(pr + (size_t)(c * 40) * 128);
      for (uint32_t it = 0; it < WAIT_LIMIT; ++it) {
        bool all = true;
#pragma unroll
        for (int c = 0; c < 16; c++) {
          if ((((v[c].y ^ tag) | (v[c].w ^ tag)) >> 16) != 0) {
            v[c] = ld_relaxed_v4(pr + (size_t)(c * 40) * 128);
            all = false;
          }
        }
        if (all) break;
      }
      TRC(21);
      float a[6];
#pragma unroll
      for (int e = 0; e < 6; e++) a[e] = 0.f;
#pragma unroll
      for (int c = 0; c < 16; c++) {
        a[0] += bf_lo(v[c].x);
        a[1] += bf_hi(v[c].x);
        a[2] += bf_lo(v[c].y);
        a[3] += bf_lo(v[c].z);
        a[4] += bf_hi(v[c].z);
        a[5] += bf_lo(v[c].w);
      }
#pragma unroll
      for (int e = 0; e < 3; e++) {
        const int q = 3 * h + e;
        *reinterpret_cast<uint32_t*>(orow + (q & 1) * 8 * 1152 + (q >> 1) * 8) = pack_bf16(a[2 * e], a[2 * e + 1]);
      }
    }
    TRC(22);
  }
}

typedef CUresult (*EncodeFn)(CUtensorMap*, CUtensorMapDataType, cuuint32_t, void*, const cuuint64_t*, const cuuint64_t*,
                             const cuuint32_t*, const cuuint32_t*, CUtensorMapInterleave, CUtensorMapSwizzle,
                             CUtensorMapL2promotion, CUtensorMapFloatOOBfill);

void encode3d(EncodeFn fn, CUtensorMap* m, void* ptr, uint64_t cols, uint64_t rows, uint32_t box_rows, uint32_t box_chunks) {
  cuuint64_t dims[3] = {64, rows, cols / 64};
  cuuint64_t strides[2] = {cols * 2, 128};
  cuuint32_t box[3] = {64, box_rows, box_chunks};
  cuuint32_t es[3] = {1, 1, 1};
  fn(m, CU_TENSOR_MAP_DATA_TYPE_BFLOAT16, 3, ptr, dims, strides, box, es, CU_TENSOR_MAP_INTERLEAVE_NONE,
     CU_TENSOR_MAP_SWIZZLE_128B, CU_TENSOR_MAP_L2_PROMOTION_NONE, CU_TENSOR_MAP_FLOAT_OOB_FILL_NONE);
}

}

extern "C" void kernel_launch(void* const* d_in, const int* in_sizes, int n_in, void* d_out, int out_size) {
  static EncodeFn fn = nullptr;
  if (!fn) {
    void* f = nullptr;
    cudaDriverEntryPointQueryResult st;
    cudaGetDriverEntryPoint("cuTensorMapEncodeTiled", &f, cudaEnableDefault, &st);
    fn = (EncodeFn)f;
    cudaFuncSetAttribute(fused_gqa_kernel, cudaFuncAttributeMaxDynamicSharedMemorySize, SMEM_BYTES);
  }
  Maps maps;
  for (int p = 0; p < 2; p++) {
    encode3d(fn, &maps.x[p], d_in[p * 5 + 0], kD, 512, 128, 1);
    encode3d(fn, &maps.k[p], d_in[p * 5 + 1], kDH, 8 * 16 * kSK, 128, 2);
    encode3d(fn, &maps.v[p], d_in[p * 5 + 2], kDH, 8 * 16 * kSK, 128, 2);
    encode3d(fn, &maps.wq[p], d_in[p * 5 + 3], kHQD, kD, 64, 4);
    encode3d(fn, &maps.wo[p], d_in[p * 5 + 4], kD, kHQD, 64, 3);
    maps.px[p] = (const char*)d_in[p * 5 + 0];
  }
  fused_gqa_kernel<<<128, 384, SMEM_BYTES>>>(maps, (__nv_bfloat16*)d_out);
}
```

```cpp
#include <cuda_runtime.h>
#include <cuda_bf16.h>
#include <cuda.h>
#include <stdint.h>

namespace {

constexpr int kD = 576, kHQD = 4096, kSK = 512, kDH = 128;

constexpr int N_WQ = 9, N_X = 9, N_KV = 16, N_WO = 12;
constexpr int N_ITEMS = N_WQ + N_X + N_KV + N_WO;
constexpr int T32 = 32 * 1024;
constexpr int WO_BYTES = 24 * 1024;
constexpr int PARK_OFF = 192 * 1024;
constexpr int BAR_OFF = 224 * 1024;
constexpr int SMEM_BYTES = BAR_OFF + 2 * N_ITEMS * 8 + 256;
constexpr int WQ0 = 0, X0 = N_WQ, KV0 = X0 + N_X, WO0 = KV0 + N_KV;
#define KV_INFLIGHT 2

__device__ __forceinline__ int wq_off(int kc) { return (kc & 3) * T32; }
__device__ __forceinline__ int x_off(int kc) { return ((kc & 2) ? 5 * T32 : PARK_OFF) + (kc & 1) * 16384; }
__device__ __forceinline__ int ring_off(int pos) { return (int)((0x053214u >> ((pos % 6) * 4)) & 15u) * T32; }
__device__ __forceinline__ int kv_off(int n) { return ring_off(n); }
__device__ __forceinline__ int wo_off(int m) { return (int)((0x607854321607ull >> (m * 4)) & 15ull) * WO_BYTES; }

__device__ uint4 g_part[16 * 16 * 36 * 128];
__device__ unsigned int g_cnt[16 * 4 * 32];

#define TR(role, ev)
#define TRC(ev)
constexpr uint32_t WAIT_CYCLES = 1u << 24;
constexpr uint32_t WAIT_LIMIT = 1u << 15;
__device__ __forceinline__ uint32_t smem_u32(const void* p) { return (uint32_t)__cvta_generic_to_shared(p); }
__device__ __forceinline__ void mbar_init(uint32_t bar, uint32_t cnt) {
  asm volatile("mbarrier.init.shared::cta.b64 [%0], %1;" ::"r"(bar), "r"(cnt) : "memory");
}
__device__ __forceinline__ void mbar_expect_tx(uint32_t bar, uint32_t bytes) {
  asm volatile("mbarrier.arrive.expect_tx.shared::cta.b64 _, [%0], %1;" ::"r"(bar), "r"(bytes) : "memory");
}
__device__ __forceinline__ void mbar_arrive(uint32_t bar) {
  asm volatile("mbarrier.arrive.shared::cta.b64 _, [%0];" ::"r"(bar) : "memory");
}
__device__ __forceinline__ bool mbar_try(uint32_t bar, uint32_t parity) {
  uint32_t ok;
  asm volatile(
      "{\n.reg .pred p;\nmbarrier.try_wait.parity.shared::cta.b64 p, [%1], %2;\nselp.u32 %0, 1, 0, p;\n}\n"
      : "=r"(ok)
      : "r"(bar), "r"(parity)
      : "memory");
  return ok != 0;
}
__device__ __forceinline__ void mbar_wait(uint32_t bar) {
  if (mbar_try(bar, 0)) return;
  const uint32_t t0 = (uint32_t)clock();
  while (!mbar_try(bar, 0))
    if ((uint32_t)clock() - t0 > WAIT_CYCLES) break;
}
__device__ __forceinline__ void tma_load3(uint32_t dst, const CUtensorMap* tm, int c0, int c1, int c2, uint32_t bar) {
  asm volatile(
      "cp.async.bulk.tensor.3d.shared::cluster.global.mbarrier::complete_tx::bytes [%0], [%1, {%3, %4, %5}], [%2];" ::"r"(dst),
      "l"(tm), "r"(bar), "r"(c0), "r"(c1), "r"(c2)
      : "memory");
}
__device__ __forceinline__ void l2_prefetch(const void* p) { asm volatile("prefetch.global.L2 [%0];" ::"l"(p) : "memory"); }
__device__ __forceinline__ void prefetch_tmap(const CUtensorMap* tm) {
  asm volatile("prefetch.tensormap [%0];" ::"l"(tm) : "memory");
}
__device__ __forceinline__ void named_bar(int id, int n) { asm volatile("bar.sync %0, %1;" ::"r"(id), "r"(n) : "memory"); }
__device__ __forceinline__ void named_arrive(int id, int n) { asm volatile("bar.arrive %0, %1;" ::"r"(id), "r"(n) : "memory"); }
__device__ __forceinline__ void wg_fence() { asm volatile("wgmma.fence.sync.aligned;" ::: "memory"); }
__device__ __forceinline__ void wg_commit() { asm volatile("wgmma.commit_group.sync.aligned;" ::: "memory"); }
template <int N>
__device__ __forceinline__ void wg_wait() { asm volatile("wgmma.wait_group.sync.aligned %0;" ::"n"(N) : "memory"); }
template <int N>
__device__ __forceinline__ void fence_regs(float (&d)[N]) {
#pragma unroll
  for (int i = 0; i < N; i++) asm volatile("" : "+f"(d[i])::"memory");
}
__device__ __forceinline__ void fence_regs32(float (&d)[64]) {
#pragma unroll
  for (int i = 0; i < 32; i++) asm volatile("" : "+f"(d[i])::"memory");
}
__device__ __forceinline__ uint64_t make_desc(uint32_t addr, uint32_t lbo, uint32_t sbo) {
  return (uint64_t)((addr & 0x3FFFF) >> 4) | ((uint64_t)(lbo >> 4) << 16) | ((uint64_t)(sbo >> 4) << 32) | (1ull << 62);
}
__device__ __forceinline__ uint32_t pack_bf16(float lo, float hi) {
  uint32_t r;
  asm("cvt.rn.bf16x2.f32 %0, %1, %2;" : "=r"(r) : "f"(hi), "f"(lo));
  return r;
}
__device__ __forceinline__ float ex2(float x) {
  float y;
  asm("ex2.approx.ftz.f32 %0, %1;" : "=f"(y) : "f"(x));
  return y;
}
__device__ __forceinline__ float bf_lo(uint32_t v) { return __uint_as_float(v << 16); }
__device__ __forceinline__ float bf_hi(uint32_t v) { return __uint_as_float(v & 0xffff0000u); }
template <int N>
__device__ __forceinline__ uint4 pack8(const float (&a)[N], int i) {
  return make_uint4(pack_bf16(a[8 * i], a[8 * i + 1]), pack_bf16(a[8 * i + 2], a[8 * i + 3]), pack_bf16(a[8 * i + 4], a[8 * i + 5]),
                    pack_bf16(a[8 * i + 6], a[8 * i + 7]));
}

__device__ __forceinline__ void wgmma_ss_n128_tb(float (&d)[64], uint64_t da, uint64_t db, int scale_d) {
  asm volatile("{\n.reg .pred p;\nsetp.ne.b32 p, %66, 0;\n"
    "wgmma.mma_async.sync.aligned.m64n128k16.f32.bf16.bf16 {%0, %1, %2, %3, %4, %5, %6, %7, %8, %9, %10, %11, %12, %13, %14, %15, %16, %17, %18, %19, %20, %21, %22, %23, %24, %25, %26, %27, %28, %29, %30, %31, %32, %33, %34, %35, %36, %37, %38, %39, %40, %41, %42, %43, %44, %45, %46, %47, %48, %49, %50, %51, %52, %53, %54, %55, %56, %57, %58, %59, %60, %61, %62, %63}, %64, %65, p, 1, 1, 0, 1;\n}\n"
    : "+f"(d[0]), "+f"(d[1]), "+f"(d[2]), "+f"(d[3]), "+f"(d[4]), "+f"(d[5]), "+f"(d[6]), "+f"(d[7]), "+f"(d[8]), "+f"(d[9]), "+f"(d[10]), "+f"(d[11]), "+f"(d[12]), "+f"(d[13]), "+f"(d[14]), "+f"(d[15]), "+f"(d[16]), "+f"(d[17]), "+f"(d[18]), "+f"(d[19]), "+f"(d[20]), "+f"(d[21]), "+f"(d[22]), "+f"(d[23]), "+f"(d[24]), "+f"(d[25]), "+f"(d[26]), "+f"(d[27]), "+f"(d[28]), "+f"(d[29]), "+f"(d[30]), "+f"(d[31]), "+f"(d[32]), "+f"(d[33]), "+f"(d[34]), "+f"(d[35]), "+f"(d[36]), "+f"(d[37]), "+f"(d[38]), "+f"(d[39]), "+f"(d[40]), "+f"(d[41]), "+f"(d[42]), "+f"(d[43]), "+f"(d[44]), "+f"(d[45]), "+f"(d[46]), "+f"(d[47]), "+f"(d[48]), "+f"(d[49]), "+f"(d[50]), "+f"(d[51]), "+f"(d[52]), "+f"(d[53]), "+f"(d[54]), "+f"(d[55]), "+f"(d[56]), "+f"(d[57]), "+f"(d[58]), "+f"(d[59]), "+f"(d[60]), "+f"(d[61]), "+f"(d[62]), "+f"(d[63])
    : "l"(da), "l"(db), "r"(scale_d));
}

__device__ __forceinline__ void wgmma_rs_n128(float (&d)[64], uint32_t a0, uint32_t a1, uint32_t a2, uint32_t a3, uint64_t db, int scale_d) {
  asm volatile("{\n.reg .pred p;\nsetp.ne.b32 p, %69, 0;\n"
    "wgmma.mma_async.sync.aligned.m64n128k16.f32.bf16.bf16 {%0, %1, %2, %3, %4, %5, %6, %7, %8, %9, %10, %11, %12, %13, %14, %15, %16, %17, %18, %19, %20, %21, %22, %23, %24, %25, %26, %27, %28, %29, %30, %31, %32, %33, %34, %35, %36, %37, %38, %39, %40, %41, %42, %43, %44, %45, %46, %47, %48, %49, %50, %51, %52, %53, %54, %55, %56, %57, %58, %59, %60, %61, %62, %63}, {%64, %65, %66, %67}, %68, p, 1, 1, 0;\n}\n"
    : "+f"(d[0]), "+f"(d[1]), "+f"(d[2]), "+f"(d[3]), "+f"(d[4]), "+f"(d[5]), "+f"(d[6]), "+f"(d[7]), "+f"(d[8]), "+f"(d[9]), "+f"(d[10]), "+f"(d[11]), "+f"(d[12]), "+f"(d[13]), "+f"(d[14]), "+f"(d[15]), "+f"(d[16]), "+f"(d[17]), "+f"(d[18]), "+f"(d[19]), "+f"(d[20]), "+f"(d[21]), "+f"(d[22]), "+f"(d[23]), "+f"(d[24]), "+f"(d[25]), "+f"(d[26]), "+f"(d[27]), "+f"(d[28]), "+f"(d[29]), "+f"(d[30]), "+f"(d[31]), "+f"(d[32]), "+f"(d[33]), "+f"(d[34]), "+f"(d[35]), "+f"(d[36]), "+f"(d[37]), "+f"(d[38]), "+f"(d[39]), "+f"(d[40]), "+f"(d[41]), "+f"(d[42]), "+f"(d[43]), "+f"(d[44]), "+f"(d[45]), "+f"(d[46]), "+f"(d[47]), "+f"(d[48]), "+f"(d[49]), "+f"(d[50]), "+f"(d[51]), "+f"(d[52]), "+f"(d[53]), "+f"(d[54]), "+f"(d[55]), "+f"(d[56]), "+f"(d[57]), "+f"(d[58]), "+f"(d[59]), "+f"(d[60]), "+f"(d[61]), "+f"(d[62]), "+f"(d[63])
    : "r"(a0), "r"(a1), "r"(a2), "r"(a3), "l"(db), "r"(scale_d));
}

__device__ __forceinline__ void wgmma_rs_n128_tb(float (&d)[64], uint32_t a0, uint32_t a1, uint32_t a2, uint32_t a3, uint64_t db, int scale_d) {
  asm volatile("{\n.reg .pred p;\nsetp.ne.b32 p, %69, 0;\n"
    "wgmma.mma_async.sync.aligned.m64n128k16.f32.bf16.bf16 {%0, %1, %2, %3, %4, %5, %6, %7, %8, %9, %10, %11, %12, %13, %14, %15, %16, %17, %18, %19, %20, %21, %22, %23, %24, %25, %26, %27, %28, %29, %30, %31, %32, %33, %34, %35, %36, %37, %38, %39, %40, %41, %42, %43, %44, %45, %46, %47, %48, %49, %50, %51, %52, %53, %54, %55, %56, %57, %58, %59, %60, %61, %62, %63}, {%64, %65, %66, %67}, %68, p, 1, 1, 1;\n}\n"
    : "+f"(d[0]), "+f"(d[1]), "+f"(d[2]), "+f"(d[3]), "+f"(d[4]), "+f"(d[5]), "+f"(d[6]), "+f"(d[7]), "+f"(d[8]), "+f"(d[9]), "+f"(d[10]), "+f"(d[11]), "+f"(d[12]), "+f"(d[13]), "+f"(d[14]), "+f"(d[15]), "+f"(d[16]), "+f"(d[17]), "+f"(d[18]), "+f"(d[19]), "+f"(d[20]), "+f"(d[21]), "+f"(d[22]), "+f"(d[23]), "+f"(d[24]), "+f"(d[25]), "+f"(d[26]), "+f"(d[27]), "+f"(d[28]), "+f"(d[29]), "+f"(d[30]), "+f"(d[31]), "+f"(d[32]), "+f"(d[33]), "+f"(d[34]), "+f"(d[35]), "+f"(d[36]), "+f"(d[37]), "+f"(d[38]), "+f"(d[39]), "+f"(d[40]), "+f"(d[41]), "+f"(d[42]), "+f"(d[43]), "+f"(d[44]), "+f"(d[45]), "+f"(d[46]), "+f"(d[47]), "+f"(d[48]), "+f"(d[49]), "+f"(d[50]), "+f"(d[51]), "+f"(d[52]), "+f"(d[53]), "+f"(d[54]), "+f"(d[55]), "+f"(d[56]), "+f"(d[57]), "+f"(d[58]), "+f"(d[59]), "+f"(d[60]), "+f"(d[61]), "+f"(d[62]), "+f"(d[63])
    : "r"(a0), "r"(a1), "r"(a2), "r"(a3), "l"(db), "r"(scale_d));
}

__device__ __forceinline__ void wgmma_rs_n128_z(float (&d)[64], uint32_t a0, uint32_t a1, uint32_t a2, uint32_t a3, uint64_t db) {
  asm volatile("{\n.reg .pred p;\nsetp.ne.b32 p, 0, 0;\n"
    "wgmma.mma_async.sync.aligned.m64n128k16.f32.bf16.bf16 {%0, %1, %2, %3, %4, %5, %6, %7, %8, %9, %10, %11, %12, %13, %14, %15, %16, %17, %18, %19, %20, %21, %22, %23, %24, %25, %26, %27, %28, %29, %30, %31, %32, %33, %34, %35, %36, %37, %38, %39, %40, %41, %42, %43, %44, %45, %46, %47, %48, %49, %50, %51, %52, %53, %54, %55, %56, %57, %58, %59, %60, %61, %62, %63}, {%64, %65, %66, %67}, %68, p, 1, 1, 0;\n}\n"
    : "=f"(d[0]), "=f"(d[1]), "=f"(d[2]), "=f"(d[3]), "=f"(d[4]), "=f"(d[5]), "=f"(d[6]), "=f"(d[7]), "=f"(d[8]), "=f"(d[9]), "=f"(d[10]), "=f"(d[11]), "=f"(d[12]), "=f"(d[13]), "=f"(d[14]), "=f"(d[15]), "=f"(d[16]), "=f"(d[17]), "=f"(d[18]), "=f"(d[19]), "=f"(d[20]), "=f"(d[21]), "=f"(d[22]), "=f"(d[23]), "=f"(d[24]), "=f"(d[25]), "=f"(d[26]), "=f"(d[27]), "=f"(d[28]), "=f"(d[29]), "=f"(d[30]), "=f"(d[31]), "=f"(d[32]), "=f"(d[33]), "=f"(d[34]), "=f"(d[35]), "=f"(d[36]), "=f"(d[37]), "=f"(d[38]), "=f"(d[39]), "=f"(d[40]), "=f"(d[41]), "=f"(d[42]), "=f"(d[43]), "=f"(d[44]), "=f"(d[45]), "=f"(d[46]), "=f"(d[47]), "=f"(d[48]), "=f"(d[49]), "=f"(d[50]), "=f"(d[51]), "=f"(d[52]), "=f"(d[53]), "=f"(d[54]), "=f"(d[55]), "=f"(d[56]), "=f"(d[57]), "=f"(d[58]), "=f"(d[59]), "=f"(d[60]), "=f"(d[61]), "=f"(d[62]), "=f"(d[63])
    : "r"(a0), "r"(a1), "r"(a2), "r"(a3), "l"(db));
}

__device__ __forceinline__ void wgmma_rs_n192_tb(float (&d)[64], float (&e)[64], uint32_t a0, uint32_t a1, uint32_t a2, uint32_t a3, uint64_t db) {
  asm volatile("{\n.reg .pred p;\nsetp.eq.b32 p, 0, 0;\n"
    "wgmma.mma_async.sync.aligned.m64n192k16.f32.bf16.bf16 {%0, %1, %2, %3, %4, %5, %6, %7, %8, %9, %10, %11, %12, %13, %14, %15, %16, %17, %18, %19, %20, %21, %22, %23, %24, %25, %26, %27, %28, %29, %30, %31, %32, %33, %34, %35, %36, %37, %38, %39, %40, %41, %42, %43, %44, %45, %46, %47, %48, %49, %50, %51, %52, %53, %54, %55, %56, %57, %58, %59, %60, %61, %62, %63, %64, %65, %66, %67, %68, %69, %70, %71, %72, %73, %74, %75, %76, %77, %78, %79, %80, %81, %82, %83, %84, %85, %86, %87, %88, %89, %90, %91, %92, %93, %94, %95}, {%96, %97, %98, %99}, %100, p, 1, 1, 1;\n}\n"
    : "+f"(d[0]), "+f"(d[1]), "+f"(d[2]), "+f"(d[3]), "+f"(d[4]), "+f"(d[5]), "+f"(d[6]), "+f"(d[7]), "+f"(d[8]), "+f"(d[9]), "+f"(d[10]), "+f"(d[11]), "+f"(d[12]), "+f"(d[13]), "+f"(d[14]), "+f"(d[15]), "+f"(d[16]), "+f"(d[17]), "+f"(d[18]), "+f"(d[19]), "+f"(d[20]), "+f"(d[21]), "+f"(d[22]), "+f"(d[23]), "+f"(d[24]), "+f"(d[25]), "+f"(d[26]), "+f"(d[27]), "+f"(d[28]), "+f"(d[29]), "+f"(d[30]), "+f"(d[31]), "+f"(d[32]), "+f"(d[33]), "+f"(d[34]), "+f"(d[35]), "+f"(d[36]), "+f"(d[37]), "+f"(d[38]), "+f"(d[39]), "+f"(d[40]), "+f"(d[41]), "+f"(d[42]), "+f"(d[43]), "+f"(d[44]), "+f"(d[45]), "+f"(d[46]), "+f"(d[47]), "+f"(d[48]), "+f"(d[49]), "+f"(d[50]), "+f"(d[51]), "+f"(d[52]), "+f"(d[53]), "+f"(d[54]), "+f"(d[55]), "+f"(d[56]), "+f"(d[57]), "+f"(d[58]), "+f"(d[59]), "+f"(d[60]), "+f"(d[61]), "+f"(d[62]), "+f"(d[63]), "+f"(e[0]), "+f"(e[1]), "+f"(e[2]), "+f"(e[3]), "+f"(e[4]), "+f"(e[5]), "+f"(e[6]), "+f"(e[7]), "+f"(e[8]), "+f"(e[9]), "+f"(e[10]), "+f"(e[11]), "+f"(e[12]), "+f"(e[13]), "+f"(e[14]), "+f"(e[15]), "+f"(e[16]), "+f"(e[17]), "+f"(e[18]), "+f"(e[19]), "+f"(e[20]), "+f"(e[21]), "+f"(e[22]), "+f"(e[23]), "+f"(e[24]), "+f"(e[25]), "+f"(e[26]), "+f"(e[27]), "+f"(e[28]), "+f"(e[29]), "+f"(e[30]), "+f"(e[31])
    : "r"(a0), "r"(a1), "r"(a2), "r"(a3), "l"(db));
}

__device__ __forceinline__ void wgmma_rs_n192_tb_z(float (&d)[64], float (&e)[64], uint32_t a0, uint32_t a1, uint32_t a2, uint32_t a3, uint64_t db) {
  asm volatile("{\n.reg .pred p;\nsetp.ne.b32 p, 0, 0;\n"
    "wgmma.mma_async.sync.aligned.m64n192k16.f32.bf16.bf16 {%0, %1, %2, %3, %4, %5, %6, %7, %8, %9, %10, %11, %12, %13, %14, %15, %16, %17, %18, %19, %20, %21, %22, %23, %24, %25, %26, %27, %28, %29, %30, %31, %32, %33, %34, %35, %36, %37, %38, %39, %40, %41, %42, %43, %44, %45, %46, %47, %48, %49, %50, %51, %52, %53, %54, %55, %56, %57, %58, %59, %60, %61, %62, %63, %64, %65, %66, %67, %68, %69, %70, %71, %72, %73, %74, %75, %76, %77, %78, %79, %80, %81, %82, %83, %84, %85, %86, %87, %88, %89, %90, %91, %92, %93, %94, %95}, {%96, %97, %98, %99}, %100, p, 1, 1, 1;\n}\n"
    : "=f"(d[0]), "=f"(d[1]), "=f"(d[2]), "=f"(d[3]), "=f"(d[4]), "=f"(d[5]), "=f"(d[6]), "=f"(d[7]), "=f"(d[8]), "=f"(d[9]), "=f"(d[10]), "=f"(d[11]), "=f"(d[12]), "=f"(d[13]), "=f"(d[14]), "=f"(d[15]), "=f"(d[16]), "=f"(d[17]), "=f"(d[18]), "=f"(d[19]), "=f"(d[20]), "=f"(d[21]), "=f"(d[22]), "=f"(d[23]), "=f"(d[24]), "=f"(d[25]), "=f"(d[26]), "=f"(d[27]), "=f"(d[28]), "=f"(d[29]), "=f"(d[30]), "=f"(d[31]), "=f"(d[32]), "=f"(d[33]), "=f"(d[34]), "=f"(d[35]), "=f"(d[36]), "=f"(d[37]), "=f"(d[38]), "=f"(d[39]), "=f"(d[40]), "=f"(d[41]), "=f"(d[42]), "=f"(d[43]), "=f"(d[44]), "=f"(d[45]), "=f"(d[46]), "=f"(d[47]), "=f"(d[48]), "=f"(d[49]), "=f"(d[50]), "=f"(d[51]), "=f"(d[52]), "=f"(d[53]), "=f"(d[54]), "=f"(d[55]), "=f"(d[56]), "=f"(d[57]), "=f"(d[58]), "=f"(d[59]), "=f"(d[60]), "=f"(d[61]), "=f"(d[62]), "=f"(d[63]), "=f"(e[0]), "=f"(e[1]), "=f"(e[2]), "=f"(e[3]), "=f"(e[4]), "=f"(e[5]), "=f"(e[6]), "=f"(e[7]), "=f"(e[8]), "=f"(e[9]), "=f"(e[10]), "=f"(e[11]), "=f"(e[12]), "=f"(e[13]), "=f"(e[14]), "=f"(e[15]), "=f"(e[16]), "=f"(e[17]), "=f"(e[18]), "=f"(e[19]), "=f"(e[20]), "=f"(e[21]), "=f"(e[22]), "=f"(e[23]), "=f"(e[24]), "=f"(e[25]), "=f"(e[26]), "=f"(e[27]), "=f"(e[28]), "=f"(e[29]), "=f"(e[30]), "=f"(e[31])
    : "r"(a0), "r"(a1), "r"(a2), "r"(a3), "l"(db));
}

struct Maps {
  CUtensorMap x[2], k[2], v[2], wq[2], wo[2];
  const char* px[2];
};

__device__ __forceinline__ void poll_tiles(int tile, const unsigned (&target)[3], uint32_t ready) {
#pragma unroll
  for (int pn = 0; pn < 3; pn++) {
    const unsigned* c = &g_cnt[(tile * 4 + pn) * 32];
    for (uint32_t it = 0; it < WAIT_LIMIT; ++it) {
      unsigned v;
      asm volatile("ld.acquire.gpu.global.u32 %0, [%1];" : "=r"(v) : "l"(c) : "memory");
      if ((int)(v - target[pn]) >= 0) break;
    }
    mbar_arrive(ready + pn * 8);
  }
}
__device__ __forceinline__ void read_targets(int tile, unsigned (&target)[3]) {
#pragma unroll
  for (int pn = 0; pn < 3; pn++) {
    unsigned v;
    asm volatile("ld.relaxed.gpu.global.u32 %0, [%1];" : "=r"(v) : "l"(&g_cnt[(tile * 4 + pn) * 32]) : "memory");
    target[pn] = (v / 16u + 1u) * 16u;
  }
}

__global__ void __launch_bounds__(384, 1)
fused_gqa_kernel(const __grid_constant__ Maps maps, __nv_bfloat16* __restrict__ out) {
  extern __shared__ __align__(1024) unsigned char smem[];
  const uint32_t sbase = smem_u32(smem);
  const uint32_t full0 = sbase + BAR_OFF;
  const uint32_t empty0 = full0 + N_ITEMS * 8;
  const uint32_t ready0 = empty0 + N_ITEMS * 8;
  const uint32_t pub0 = ready0 + 6 * 8;
  const uint32_t tgt0 = pub0 + 6 * 8;
  volatile unsigned* s_tgt = reinterpret_cast<volatile unsigned*>(smem + BAR_OFF + 2 * N_ITEMS * 8 + 128);

  const int tid = threadIdx.x;
  const int wg = tid >> 7;
  const int bid = blockIdx.x;
  const int bp = bid & 3;
  const int h = (bid >> 2) & 15;
  const int p = bid >> 6;

  if (tid == 0) {
#pragma unroll
    for (int i = 0; i < 4; i++) mbar_init(full0 + (WQ0 + i) * 8, 1);
#pragma unroll
    for (int i = 0; i < 4; i++) mbar_init(full0 + (X0 + i) * 8, 1);
    mbar_init(full0 + KV0 * 8, 1);
    asm volatile("fence.mbarrier_init.release.cluster;" ::: "memory");
#pragma unroll
    for (int kc = 0; kc < 4; kc++) {
      mbar_expect_tx(full0 + (X0 + kc) * 8, 16384);
      tma_load3(sbase + x_off(kc), &maps.x[p], 0, bp * 128, kc, full0 + (X0 + kc) * 8);
      mbar_expect_tx(full0 + (WQ0 + kc) * 8, T32);
      tma_load3(sbase + wq_off(kc), &maps.wq[p], 0, kc * 64, h * 4, full0 + (WQ0 + kc) * 8);
    }
    mbar_expect_tx(full0 + KV0 * 8, T32);
    tma_load3(sbase + kv_off(0), &maps.k[p], 0, (2 * bp * 16 + h) * kSK, 0, full0 + KV0 * 8);
    TR(0, 56);
  } else if (tid >= 64 && tid < 96) {
    const char* base = maps.px[p] + (size_t)(bp * 128 + h * 8) * 1152;
#pragma unroll
    for (int i = 0; i < 3; i++)
      if ((tid & 31) + i * 32 < 72) l2_prefetch(base + ((tid & 31) + i * 32) * 128);
  } else if (tid == 32) {
    prefetch_tmap(&maps.v[p]);
    prefetch_tmap(&maps.wo[p]);
  } else if (tid >= 128) {
    const int i = tid - 128;
    if (i < N_ITEMS) {
      if (!(i < 4 || (i >= X0 && i < X0 + 4) || i == KV0)) mbar_init(full0 + i * 8, 1);
    } else if (i >= 64 && i < 64 + N_ITEMS) {
      mbar_init(empty0 + (i - 64) * 8, i == 64 + WQ0 ? 4 : 8);
    } else if (i >= 128 && i < 128 + 6) {
      mbar_init(ready0 + (i - 128) * 8, 1);
    } else if (i >= 160 && i < 160 + 6) {
      mbar_init(pub0 + (i - 160) * 8, 4);
    } else if (i >= 192 && i < 192 + 2) {
      mbar_init(tgt0 + (i - 192) * 8, 1);
    }
    asm volatile("fence.mbarrier_init.release.cluster;" ::: "memory");
  }
  __syncthreads();
  if (tid == 0) TR(0, 57);

  if (wg == 0) {
    asm volatile("setmaxnreg.dec.sync.aligned.u32 24;");
    if (tid == 0) {
      const int kvrow = (2 * bp * 16 + h) * kSK;
      auto load_kv = [&](int n) {
        if (n >= KV_INFLIGHT) mbar_wait(full0 + (KV0 + n - KV_INFLIGHT) * 8);
        const uint32_t fb = full0 + (KV0 + n) * 8;
        TR(0, KV0 + n);
        mbar_expect_tx(fb, T32);
        tma_load3(sbase + kv_off(n), (n & 1) ? &maps.v[p] : &maps.k[p], 0, kvrow + (n >> 3) * 16 * kSK + ((n & 7) >> 1) * 128, 0, fb);
      };
#pragma unroll 1
      for (int c = 0; c < 9; c++) {
        mbar_wait(empty0 + (X0 + c) * 8);
        if (c < 5) {
          mbar_expect_tx(full0 + (X0 + c + 4) * 8, 16384);
          tma_load3(sbase + x_off(c + 4), &maps.x[p], 0, bp * 128, c + 4, full0 + (X0 + c + 4) * 8);
        }
        if (c < 5) {
          TR(0, WQ0 + c + 4);
          mbar_expect_tx(full0 + (WQ0 + c + 4) * 8, T32);
          tma_load3(sbase + wq_off(c + 4), &maps.wq[p], 0, (c + 4) * 64, h * 4, full0 + (WQ0 + c + 4) * 8);
        } else if (c < 8) {
          load_kv(c - 4);
          if (c == 7) load_kv(4);
        } else {
          load_kv(5);
        }
      }
#pragma unroll 1
      for (int n = 6; n < N_KV; n++) {
        mbar_wait(empty0 + (KV0 + n - 6) * 8);
        load_kv(n);
      }
      mbar_wait(full0 + (KV0 + N_KV - 1) * 8);
#pragma unroll 1
      for (int m = 0; m < N_WO; m++) {
        const int dep = m >= 9 ? WO0 + m - 9 : (m == 8 ? WQ0 : KV0 + 10 + (int)((0x55443210u >> (m * 4)) & 15u));
        mbar_wait(empty0 + dep * 8);
        const uint32_t fb = full0 + (WO0 + m) * 8;
        TR(0, WO0 + m);
        mbar_expect_tx(fb, WO_BYTES);
        tma_load3(sbase + wo_off(m), &maps.wo[p], 0, h * 256 + (m & 3) * 64, (m >> 2) * 3, fb);
      }
    } else if (tid == 96 || tid == 112) {
      const int w = (tid >> 4) & 1;
      mbar_wait(tgt0 + w * 8);
      const unsigned target[3] = {s_tgt[w * 4], s_tgt[w * 4 + 1], s_tgt[w * 4 + 2]};
      mbar_wait(pub0 + w * 24);
      poll_tiles(p * 8 + 2 * bp + w, target, ready0 + w * 24);
    } else if (tid == 32 || tid == 64) {
      const int w = (tid >> 5) - 1;
      const int tile = p * 8 + 2 * bp + w;
      unsigned target[3];
      read_targets(tile, target);
      s_tgt[w * 4] = target[0];
      s_tgt[w * 4 + 1] = target[1];
      s_tgt[w * 4 + 2] = target[2];
      mbar_arrive(tgt0 + w * 8);
#pragma unroll 1
      for (int e = 0; e < 3; e++) {
        mbar_wait(pub0 + (w * 3 + e) * 8);
        asm volatile("red.release.gpu.global.add.u32 [%0], 1;" ::"l"(&g_cnt[(tile * 4 + e) * 32]) : "memory");
      }
    }
  } else {
    asm volatile("setmaxnreg.inc.sync.aligned.u32 240;");
    const int w = wg - 1;
    const int t128 = tid & 127;
    const int lane = tid & 31;

    auto release = [&](int item) {
      __syncwarp();
      if (lane == 0) mbar_arrive(empty0 + item * 8);
    };

    TRC(0);
    const float cs = 0.08838834764831845f * 1.4426950408889634f;
    float s[64], o[64];
#pragma unroll
    for (int i = 0; i < 64; i++) s[i] = 0.f, o[i] = 0.f;
    uint32_t qf[32];
    uint4* park = reinterpret_cast<uint4*>(smem + PARK_OFF) + w * 1024 + t128;
    {
#pragma unroll 1
      for (int kc = 0; kc < 9; kc++) {
        mbar_wait(full0 + (X0 + kc) * 8);
        mbar_wait(full0 + (WQ0 + kc) * 8);
        if (kc == 0) TRC(1);
        const uint64_t da = make_desc(sbase + x_off(kc), 16, 1024);
        const uint64_t db = make_desc(sbase + wq_off(kc) + w * 16384, 8192, 1024);
        wg_fence();
#pragma unroll
        for (int ks = 0; ks < 4; ks++) {
          wgmma_ss_n128_tb(s, da + ks * 2, db + ks * 128, (kc | ks) != 0);
          wgmma_ss_n128_tb(o, da + 512 + ks * 2, db + ks * 128, (kc | ks) != 0);
        }
        wg_commit();
        wg_wait<0>();
        release(X0 + kc);
      }
      fence_regs(s);
      fence_regs(o);
#pragma unroll
      for (int i = 0; i < 32; i++) qf[i] = pack_bf16(s[2 * i], s[2 * i + 1]);
      named_bar(1, 256);
#pragma unroll
      for (int i = 0; i < 8; i++) park[i * 128] = pack8(o, i);
      TRC(2);
    }
#pragma unroll 1
    for (int bb = 0; bb < 2; bb++) {
#pragma unroll
      for (int i = 0; i < 64; i++) o[i] = 0.f;
      float m0 = -INFINITY, m1 = -INFINITY, l0 = 0.f, l1 = 0.f;
#pragma unroll 1
      for (int t = 0; t < 4; t++) {
        const int n = bb * 8 + t * 2;
        {
          const uint32_t base = sbase + kv_off(n);
          mbar_wait(full0 + (KV0 + n) * 8);
          if (n == 0 && w == 1) named_bar(4, 256);
          const uint64_t db = make_desc(base, 16, 1024);
          wg_fence();
          wgmma_rs_n128_z(s, qf[0], qf[1], qf[2], qf[3], db);
#pragma unroll
          for (int ks = 1; ks < 8; ks++)
            wgmma_rs_n128(s, qf[4 * ks], qf[4 * ks + 1], qf[4 * ks + 2], qf[4 * ks + 3], db + (ks >> 2) * 1024 + (ks & 3) * 2, 1);
          wg_commit();
          wg_wait<0>();
          fence_regs(s);
          if (n == 0 && w == 0) named_arrive(4, 256);
          release(KV0 + n);
        }
        float mx0 = s[0], mx1 = s[2];
#pragma unroll
        for (int g = 0; g < 16; g++) {
          mx0 = fmaxf(mx0, fmaxf(s[4 * g], s[4 * g + 1]));
          mx1 = fmaxf(mx1, fmaxf(s[4 * g + 2], s[4 * g + 3]));
        }
        mx0 = fmaxf(mx0, __shfl_xor_sync(0xffffffffu, mx0, 1));
        mx0 = fmaxf(mx0, __shfl_xor_sync(0xffffffffu, mx0, 2));
        mx1 = fmaxf(mx1, __shfl_xor_sync(0xffffffffu, mx1, 1));
        mx1 = fmaxf(mx1, __shfl_xor_sync(0xffffffffu, mx1, 2));
        const float mn0 = fmaxf(m0, mx0), mn1 = fmaxf(m1, mx1);
        const float a0 = ex2((m0 - mn0) * cs), a1 = ex2((m1 - mn1) * cs);
        m0 = mn0;
        m1 = mn1;
        const float ms0 = mn0 * cs, ms1 = mn1 * cs;
        float rs0 = 0.f, rs1 = 0.f;
        uint32_t pf[32];
#pragma unroll
        for (int g = 0; g < 16; g++) {
          const float p0 = ex2(fmaf(s[4 * g], cs, -ms0));
          const float p1 = ex2(fmaf(s[4 * g + 1], cs, -ms0));
          const float p2 = ex2(fmaf(s[4 * g + 2], cs, -ms1));
          const float p3 = ex2(fmaf(s[4 * g + 3], cs, -ms1));
          rs0 += p0 + p1;
          rs1 += p2 + p3;
          pf[2 * g] = pack_bf16(p0, p1);
          pf[2 * g + 1] = pack_bf16(p2, p3);
        }
        l0 = l0 * a0 + rs0;
        l1 = l1 * a1 + rs1;
#pragma unroll
        for (int g = 0; g < 16; g++) {
          o[4 * g] *= a0;
          o[4 * g + 1] *= a0;
          o[4 * g + 2] *= a1;
          o[4 * g + 3] *= a1;
        }
        {
          const uint32_t base = sbase + kv_off(n + 1);
          mbar_wait(full0 + (KV0 + n + 1) * 8);
          const uint64_t db = make_desc(base, 16384, 1024);
          wg_fence();
#pragma unroll
          for (int ks = 0; ks < 8; ks++)
            wgmma_rs_n128_tb(o, pf[4 * ks], pf[4 * ks + 1], pf[4 * ks + 2], pf[4 * ks + 3], db + ks * 128, 1);
          wg_commit();
          wg_wait<0>();
          fence_regs(o);
          release(KV0 + n + 1);
          TRC(3 + bb * 5 + t);
        }
      }
      l0 += __shfl_xor_sync(0xffffffffu, l0, 1);
      l0 += __shfl_xor_sync(0xffffffffu, l0, 2);
      l1 += __shfl_xor_sync(0xffffffffu, l1, 1);
      l1 += __shfl_xor_sync(0xffffffffu, l1, 2);
      const float i0 = 1.f / l0, i1 = 1.f / l1;
      if (bb == 0) {
#pragma unroll
        for (int i = 0; i < 8; i++) {
          const uint4 v = park[i * 128];
          qf[4 * i] = v.x;
          qf[4 * i + 1] = v.y;
          qf[4 * i + 2] = v.z;
          qf[4 * i + 3] = v.w;
          park[i * 128] = make_uint4(pack_bf16(o[8 * i] * i0, o[8 * i + 1] * i0), pack_bf16(o[8 * i + 2] * i1, o[8 * i + 3] * i1),
                                     pack_bf16(o[8 * i + 4] * i0, o[8 * i + 5] * i0), pack_bf16(o[8 * i + 6] * i1, o[8 * i + 7] * i1));
        }
        if (w == 1) named_arrive(5, 256);
      } else {
#pragma unroll
        for (int i = 0; i < 16; i++) {
          qf[2 * i] = pack_bf16(o[4 * i] * i0, o[4 * i + 1] * i0);
          qf[2 * i + 1] = pack_bf16(o[4 * i + 2] * i1, o[4 * i + 3] * i1);
        }
      }
    }
    uint32_t af[64];
    {
      const uint4* src = reinterpret_cast<const uint4*>(smem + PARK_OFF) + t128;
      if (w == 0) {
        named_bar(5, 256);
#pragma unroll
        for (int i = 0; i < 16; i++) {
          const uint4 v = src[i * 128];
          af[4 * i] = v.x;
          af[4 * i + 1] = v.y;
          af[4 * i + 2] = v.z;
          af[4 * i + 3] = v.w;
        }
#pragma unroll
        for (int i = 0; i < 8; i++) park[i * 128] = make_uint4(qf[4 * i], qf[4 * i + 1], qf[4 * i + 2], qf[4 * i + 3]);
        asm volatile("fence.proxy.async.shared::cta;" ::: "memory");
        named_arrive(1, 256);
      } else {
        named_bar(1, 256);
#pragma unroll
        for (int i = 0; i < 8; i++) {
          const uint4 v = src[i * 128];
          af[4 * i] = v.x;
          af[4 * i + 1] = v.y;
          af[4 * i + 2] = v.z;
          af[4 * i + 3] = v.w;
        }
#pragma unroll
        for (int i = 0; i < 32; i++) af[32 + i] = qf[i];
        asm volatile("fence.proxy.async.shared::cta;" ::: "memory");
        release(WQ0);
      }
    }
    TRC(12);
    const int tile = p * 8 + 2 * bp + w;
    uint4* part = g_part + (size_t)(tile * 16 + h) * 36 * 128 + t128;
#pragma unroll
    for (int pn = 0; pn < 3; pn++) {
#pragma unroll
      for (int kc = 0; kc < 4; kc++) {
        const int m = pn * 4 + kc;
        mbar_wait(full0 + (WO0 + m) * 8);
        const uint64_t db = make_desc(sbase + wo_off(m), 8192, 1024);
        wg_fence();
#pragma unroll
        for (int ks = 0; ks < 4; ks++) {
          const int a = (kc * 4 + ks) * 4;
          if ((kc | ks) == 0) wgmma_rs_n192_tb_z(s, o, af[a], af[a + 1], af[a + 2], af[a + 3], db);
          else wgmma_rs_n192_tb(s, o, af[a], af[a + 1], af[a + 2], af[a + 3], db + ks * 128);
        }
        wg_commit();
        if (kc > 0) {
          wg_wait<1>();
          if (m - 1 < 3) release(WO0 + m - 1);
        }
      }
      wg_wait<0>();
      fence_regs(s);
      fence_regs32(o);
      TRC(13 + pn * 2);
#pragma unroll
      for (int i = 0; i < 8; i++) __stcg(part + (pn * 12 + i) * 128, pack8(s, i));
#pragma unroll
      for (int i = 0; i < 4; i++) __stcg(part + (pn * 12 + 8 + i) * 128, pack8(o, i));
      __syncwarp();
      if (lane == 0) mbar_arrive(pub0 + (w * 3 + pn) * 8);
      TRC(14 + pn * 2);
    }
    if (t128 < 96) {
      const int u = h * 96 + t128;
      const int slot = u >> 7, thr = u & 127;
      const int row0 = (thr >> 5) * 16 + ((thr & 31) >> 2);
      __nv_bfloat16* orow = out + (size_t)((2 * bp + w) * 64 + row0) * 1152 + p * 576 + slot * 16 + (thr & 3) * 2;
      const uint4* pr = g_part + (size_t)(tile * 16) * 36 * 128 + slot * 128 + thr;
      uint4 v[3][16];
#pragma unroll
      for (int pn = 0; pn < 3; pn++) {
        mbar_wait(ready0 + (w * 3 + pn) * 8);
        TRC(19 + pn);
#pragma unroll
        for (int c = 0; c < 16; c++) v[pn][c] = __ldcg(pr + (size_t)(c * 36 + pn * 12) * 128);
      }
#pragma unroll
      for (int pn = 0; pn < 3; pn++) {
        float a[8];
#pragma unroll
        for (int e = 0; e < 8; e++) a[e] = 0.f;
#pragma unroll
        for (int c = 0; c < 16; c++) {
          a[0] += bf_lo(v[pn][c].x);
          a[1] += bf_hi(v[pn][c].x);
          a[2] += bf_lo(v[pn][c].y);
          a[3] += bf_hi(v[pn][c].y);
          a[4] += bf_lo(v[pn][c].z);
          a[5] += bf_hi(v[pn][c].z);
          a[6] += bf_lo(v[pn][c].w);
          a[7] += bf_hi(v[pn][c].w);
        }
        __nv_bfloat16* op = orow + pn * 192;
        *reinterpret_cast<uint32_t*>(op) = pack_bf16(a[0], a[1]);
        *reinterpret_cast<uint32_t*>(op + 8 * 1152) = pack_bf16(a[2], a[3]);
        *reinterpret_cast<uint32_t*>(op + 8) = pack_bf16(a[4], a[5]);
        *reinterpret_cast<uint32_t*>(op + 8 * 1152 + 8) = pack_bf16(a[6], a[7]);
      }
    }
    TRC(22);
  }
}

typedef CUresult (*EncodeFn)(CUtensorMap*, CUtensorMapDataType, cuuint32_t, void*, const cuuint64_t*, const cuuint64_t*,
                             const cuuint32_t*, const cuuint32_t*, CUtensorMapInterleave, CUtensorMapSwizzle,
                             CUtensorMapL2promotion, CUtensorMapFloatOOBfill);

void encode3d(EncodeFn fn, CUtensorMap* m, void* ptr, uint64_t cols, uint64_t rows, uint32_t box_rows, uint32_t box_chunks) {
  cuuint64_t dims[3] = {64, rows, cols / 64};
  cuuint64_t strides[2] = {cols * 2, 128};
  cuuint32_t box[3] = {64, box_rows, box_chunks};
  cuuint32_t es[3] = {1, 1, 1};
  fn(m, CU_TENSOR_MAP_DATA_TYPE_BFLOAT16, 3, ptr, dims, strides, box, es, CU_TENSOR_MAP_INTERLEAVE_NONE,
     CU_TENSOR_MAP_SWIZZLE_128B, CU_TENSOR_MAP_L2_PROMOTION_NONE, CU_TENSOR_MAP_FLOAT_OOB_FILL_NONE);
}

}

extern "C" void kernel_launch(void* const* d_in, const int* in_sizes, int n_in, void* d_out, int out_size) {
  static EncodeFn fn = nullptr;
  if (!fn) {
    void* f = nullptr;
    cudaDriverEntryPointQueryResult st;
    cudaGetDriverEntryPoint("cuTensorMapEncodeTiled", &f, cudaEnableDefault, &st);
    fn = (EncodeFn)f;
    cudaFuncSetAttribute(fused_gqa_kernel, cudaFuncAttributeMaxDynamicSharedMemorySize, SMEM_BYTES);
  }
  Maps maps;
  for (int p = 0; p < 2; p++) {
    encode3d(fn, &maps.x[p], d_in[p * 5 + 0], kD, 512, 128, 1);
    encode3d(fn, &maps.k[p], d_in[p * 5 + 1], kDH, 8 * 16 * kSK, 128, 2);
    encode3d(fn, &maps.v[p], d_in[p * 5 + 2], kDH, 8 * 16 * kSK, 128, 2);
    encode3d(fn, &maps.wq[p], d_in[p * 5 + 3], kHQD, kD, 64, 4);
    encode3d(fn, &maps.wo[p], d_in[p * 5 + 4], kD, kHQD, 64, 3);
    maps.px[p] = (const char*)d_in[p * 5 + 0];
  }
  fused_gqa_kernel<<<128, 384, SMEM_BYTES>>>(maps, (__nv_bfloat16*)d_out);
}
```

```cpp
#include <cuda_runtime.h>
#include <cuda_bf16.h>
#include <cuda.h>
#include <stdint.h>

namespace {

constexpr int kD = 576, kHQD = 4096, kSK = 512, kDH = 128;

constexpr int N_WQ = 9, N_X = 9, N_KV = 16, N_WO = 12;
constexpr int N_ITEMS = N_WQ + N_X + N_KV + N_WO;
constexpr int T32 = 32 * 1024;
constexpr int WO_BYTES = 24 * 1024;
constexpr int PARK_OFF = 192 * 1024;
constexpr int BAR_OFF = 224 * 1024;
constexpr int SMEM_BYTES = BAR_OFF + 2 * N_ITEMS * 8 + 256;
constexpr int WQ0 = 0, X0 = N_WQ, KV0 = X0 + N_X, WO0 = KV0 + N_KV;
#define KV_INFLIGHT 2

__device__ __forceinline__ int wq_off(int kc) { return (kc & 3) * T32; }
__device__ __forceinline__ int x_off(int kc) { return ((kc & 2) ? 5 * T32 : PARK_OFF) + (kc & 1) * 16384; }
__device__ __forceinline__ int ring_off(int pos) { return (int)((0x053214u >> ((pos % 6) * 4)) & 15u) * T32; }
__device__ __forceinline__ int kv_off(int n) { return ring_off(n); }
__device__ __forceinline__ int wo_off(int m) { return (int)((0x607854321607ull >> (m * 4)) & 15ull) * WO_BYTES; }

__device__ uint4 g_part[16 * 16 * 36 * 128];
__device__ unsigned int g_cnt[16 * 4 * 32];

#define TR(role, ev)
#define TRC(ev)
constexpr uint32_t WAIT_CYCLES = 1u << 24;
constexpr uint32_t WAIT_LIMIT = 1u << 15;
__device__ __forceinline__ uint32_t smem_u32(const void* p) { return (uint32_t)__cvta_generic_to_shared(p); }
__device__ __forceinline__ void mbar_init(uint32_t bar, uint32_t cnt) {
  asm volatile("mbarrier.init.shared::cta.b64 [%0], %1;" ::"r"(bar), "r"(cnt) : "memory");
}
__device__ __forceinline__ void mbar_expect_tx(uint32_t bar, uint32_t bytes) {
  asm volatile("mbarrier.arrive.expect_tx.shared::cta.b64 _, [%0], %1;" ::"r"(bar), "r"(bytes) : "memory");
}
__device__ __forceinline__ void mbar_arrive(uint32_t bar) {
  asm volatile("mbarrier.arrive.shared::cta.b64 _, [%0];" ::"r"(bar) : "memory");
}
__device__ __forceinline__ bool mbar_try(uint32_t bar, uint32_t parity) {
  uint32_t ok;
  asm volatile(
      "{\n.reg .pred p;\nmbarrier.try_wait.parity.shared::cta.b64 p, [%1], %2;\nselp.u32 %0, 1, 0, p;\n}\n"
      : "=r"(ok)
      : "r"(bar), "r"(parity)
      : "memory");
  return ok != 0;
}
__device__ __forceinline__ void mbar_wait(uint32_t bar) {
  if (mbar_try(bar, 0)) return;
  const uint32_t t0 = (uint32_t)clock();
  while (!mbar_try(bar, 0))
    if ((uint32_t)clock() - t0 > WAIT_CYCLES) break;
}
__device__ __forceinline__ void tma_load3(uint32_t dst, const CUtensorMap* tm, int c0, int c1, int c2, uint32_t bar) {
  asm volatile(
      "cp.async.bulk.tensor.3d.shared::cluster.global.mbarrier::complete_tx::bytes [%0], [%1, {%3, %4, %5}], [%2];" ::"r"(dst),
      "l"(tm), "r"(bar), "r"(c0), "r"(c1), "r"(c2)
      : "memory");
}
__device__ __forceinline__ void l2_prefetch(const void* p) { asm volatile("prefetch.global.L2 [%0];" ::"l"(p) : "memory"); }
__device__ __forceinline__ void prefetch_tmap(const CUtensorMap* tm) {
  asm volatile("prefetch.tensormap [%0];" ::"l"(tm) : "memory");
}
__device__ __forceinline__ void named_bar(int id, int n) { asm volatile("bar.sync %0, %1;" ::"r"(id), "r"(n) : "memory"); }
__device__ __forceinline__ void named_arrive(int id, int n) { asm volatile("bar.arrive %0, %1;" ::"r"(id), "r"(n) : "memory"); }
__device__ __forceinline__ void wg_fence() { asm volatile("wgmma.fence.sync.aligned;" ::: "memory"); }
__device__ __forceinline__ void wg_commit() { asm volatile("wgmma.commit_group.sync.aligned;" ::: "memory"); }
template <int N>
__device__ __forceinline__ void wg_wait() { asm volatile("wgmma.wait_group.sync.aligned %0;" ::"n"(N) : "memory"); }
template <int N>
__device__ __forceinline__ void fence_regs(float (&d)[N]) {
#pragma unroll
  for (int i = 0; i < N; i++) asm volatile("" : "+f"(d[i])::"memory");
}
__device__ __forceinline__ void fence_regs32(float (&d)[64]) {
#pragma unroll
  for (int i = 0; i < 32; i++) asm volatile("" : "+f"(d[i])::"memory");
}
__device__ __forceinline__ uint64_t make_desc(uint32_t addr, uint32_t lbo, uint32_t sbo) {
  return (uint64_t)((addr & 0x3FFFF) >> 4) | ((uint64_t)(lbo >> 4) << 16) | ((uint64_t)(sbo >> 4) << 32) | (1ull << 62);
}
__device__ __forceinline__ uint32_t pack_bf16(float lo, float hi) {
  uint32_t r;
  asm("cvt.rn.bf16x2.f32 %0, %1, %2;" : "=r"(r) : "f"(hi), "f"(lo));
  return r;
}
__device__ __forceinline__ float ex2(float x) {
  float y;
  asm("ex2.approx.ftz.f32 %0, %1;" : "=f"(y) : "f"(x));
  return y;
}
__device__ __forceinline__ float bf_lo(uint32_t v) { return __uint_as_float(v << 16); }
__device__ __forceinline__ float bf_hi(uint32_t v) { return __uint_as_float(v & 0xffff0000u); }
template <int N>
__device__ __forceinline__ uint4 pack8(const float (&a)[N], int i) {
  return make_uint4(pack_bf16(a[8 * i], a[8 * i + 1]), pack_bf16(a[8 * i + 2], a[8 * i + 3]), pack_bf16(a[8 * i + 4], a[8 * i + 5]),
                    pack_bf16(a[8 * i + 6], a[8 * i + 7]));
}

__device__ __forceinline__ void wgmma_ss_n128_tb(float (&d)[64], uint64_t da, uint64_t db, int scale_d) {
  asm volatile("{\n.reg .pred p;\nsetp.ne.b32 p, %66, 0;\n"
    "wgmma.mma_async.sync.aligned.m64n128k16.f32.bf16.bf16 {%0, %1, %2, %3, %4, %5, %6, %7, %8, %9, %10, %11, %12, %13, %14, %15, %16, %17, %18, %19, %20, %21, %22, %23, %24, %25, %26, %27, %28, %29, %30, %31, %32, %33, %34, %35, %36, %37, %38, %39, %40, %41, %42, %43, %44, %45, %46, %47, %48, %49, %50, %51, %52, %53, %54, %55, %56, %57, %58, %59, %60, %61, %62, %63}, %64, %65, p, 1, 1, 0, 1;\n}\n"
    : "+f"(d[0]), "+f"(d[1]), "+f"(d[2]), "+f"(d[3]), "+f"(d[4]), "+f"(d[5]), "+f"(d[6]), "+f"(d[7]), "+f"(d[8]), "+f"(d[9]), "+f"(d[10]), "+f"(d[11]), "+f"(d[12]), "+f"(d[13]), "+f"(d[14]), "+f"(d[15]), "+f"(d[16]), "+f"(d[17]), "+f"(d[18]), "+f"(d[19]), "+f"(d[20]), "+f"(d[21]), "+f"(d[22]), "+f"(d[23]), "+f"(d[24]), "+f"(d[25]), "+f"(d[26]), "+f"(d[27]), "+f"(d[28]), "+f"(d[29]), "+f"(d[30]), "+f"(d[31]), "+f"(d[32]), "+f"(d[33]), "+f"(d[34]), "+f"(d[35]), "+f"(d[36]), "+f"(d[37]), "+f"(d[38]), "+f"(d[39]), "+f"(d[40]), "+f"(d[41]), "+f"(d[42]), "+f"(d[43]), "+f"(d[44]), "+f"(d[45]), "+f"(d[46]), "+f"(d[47]), "+f"(d[48]), "+f"(d[49]), "+f"(d[50]), "+f"(d[51]), "+f"(d[52]), "+f"(d[53]), "+f"(d[54]), "+f"(d[55]), "+f"(d[56]), "+f"(d[57]), "+f"(d[58]), "+f"(d[59]), "+f"(d[60]), "+f"(d[61]), "+f"(d[62]), "+f"(d[63])
    : "l"(da), "l"(db), "r"(scale_d));
}

__device__ __forceinline__ void wgmma_rs_n128(float (&d)[64], uint32_t a0, uint32_t a1, uint32_t a2, uint32_t a3, uint64_t db, int scale_d) {
  asm volatile("{\n.reg .pred p;\nsetp.ne.b32 p, %69, 0;\n"
    "wgmma.mma_async.sync.aligned.m64n128k16.f32.bf16.bf16 {%0, %1, %2, %3, %4, %5, %6, %7, %8, %9, %10, %11, %12, %13, %14, %15, %16, %17, %18, %19, %20, %21, %22, %23, %24, %25, %26, %27, %28, %29, %30, %31, %32, %33, %34, %35, %36, %37, %38, %39, %40, %41, %42, %43, %44, %45, %46, %47, %48, %49, %50, %51, %52, %53, %54, %55, %56, %57, %58, %59, %60, %61, %62, %63}, {%64, %65, %66, %67}, %68, p, 1, 1, 0;\n}\n"
    : "+f"(d[0]), "+f"(d[1]), "+f"(d[2]), "+f"(d[3]), "+f"(d[4]), "+f"(d[5]), "+f"(d[6]), "+f"(d[7]), "+f"(d[8]), "+f"(d[9]), "+f"(d[10]), "+f"(d[11]), "+f"(d[12]), "+f"(d[13]), "+f"(d[14]), "+f"(d[15]), "+f"(d[16]), "+f"(d[17]), "+f"(d[18]), "+f"(d[19]), "+f"(d[20]), "+f"(d[21]), "+f"(d[22]), "+f"(d[23]), "+f"(d[24]), "+f"(d[25]), "+f"(d[26]), "+f"(d[27]), "+f"(d[28]), "+f"(d[29]), "+f"(d[30]), "+f"(d[31]), "+f"(d[32]), "+f"(d[33]), "+f"(d[34]), "+f"(d[35]), "+f"(d[36]), "+f"(d[37]), "+f"(d[38]), "+f"(d[39]), "+f"(d[40]), "+f"(d[41]), "+f"(d[42]), "+f"(d[43]), "+f"(d[44]), "+f"(d[45]), "+f"(d[46]), "+f"(d[47]), "+f"(d[48]), "+f"(d[49]), "+f"(d[50]), "+f"(d[51]), "+f"(d[52]), "+f"(d[53]), "+f"(d[54]), "+f"(d[55]), "+f"(d[56]), "+f"(d[57]), "+f"(d[58]), "+f"(d[59]), "+f"(d[60]), "+f"(d[61]), "+f"(d[62]), "+f"(d[63])
    : "r"(a0), "r"(a1), "r"(a2), "r"(a3), "l"(db), "r"(scale_d));
}

__device__ __forceinline__ void wgmma_rs_n128_tb(float (&d)[64], uint32_t a0, uint32_t a1, uint32_t a2, uint32_t a3, uint64_t db, int scale_d) {
  asm volatile("{\n.reg .pred p;\nsetp.ne.b32 p, %69, 0;\n"
    "wgmma.mma_async.sync.aligned.m64n128k16.f32.bf16.bf16 {%0, %1, %2, %3, %4, %5, %6, %7, %8, %9, %10, %11, %12, %13, %14, %15, %16, %17, %18, %19, %20, %21, %22, %23, %24, %25, %26, %27, %28, %29, %30, %31, %32, %33, %34, %35, %36, %37, %38, %39, %40, %41, %42, %43, %44, %45, %46, %47, %48, %49, %50, %51, %52, %53, %54, %55, %56, %57, %58, %59, %60, %61, %62, %63}, {%64, %65, %66, %67}, %68, p, 1, 1, 1;\n}\n"
    : "+f"(d[0]), "+f"(d[1]), "+f"(d[2]), "+f"(d[3]), "+f"(d[4]), "+f"(d[5]), "+f"(d[6]), "+f"(d[7]), "+f"(d[8]), "+f"(d[9]), "+f"(d[10]), "+f"(d[11]), "+f"(d[12]), "+f"(d[13]), "+f"(d[14]), "+f"(d[15]), "+f"(d[16]), "+f"(d[17]), "+f"(d[18]), "+f"(d[19]), "+f"(d[20]), "+f"(d[21]), "+f"(d[22]), "+f"(d[23]), "+f"(d[24]), "+f"(d[25]), "+f"(d[26]), "+f"(d[27]), "+f"(d[28]), "+f"(d[29]), "+f"(d[30]), "+f"(d[31]), "+f"(d[32]), "+f"(d[33]), "+f"(d[34]), "+f"(d[35]), "+f"(d[36]), "+f"(d[37]), "+f"(d[38]), "+f"(d[39]), "+f"(d[40]), "+f"(d[41]), "+f"(d[42]), "+f"(d[43]), "+f"(d[44]), "+f"(d[45]), "+f"(d[46]), "+f"(d[47]), "+f"(d[48]), "+f"(d[49]), "+f"(d[50]), "+f"(d[51]), "+f"(d[52]), "+f"(d[53]), "+f"(d[54]), "+f"(d[55]), "+f"(d[56]), "+f"(d[57]), "+f"(d[58]), "+f"(d[59]), "+f"(d[60]), "+f"(d[61]), "+f"(d[62]), "+f"(d[63])
    : "r"(a0), "r"(a1), "r"(a2), "r"(a3), "l"(db), "r"(scale_d));
}

__device__ __forceinline__ void wgmma_rs_n128_z(float (&d)[64], uint32_t a0, uint32_t a1, uint32_t a2, uint32_t a3, uint64_t db) {
  asm volatile("{\n.reg .pred p;\nsetp.ne.b32 p, 0, 0;\n"
    "wgmma.mma_async.sync.aligned.m64n128k16.f32.bf16.bf16 {%0, %1, %2, %3, %4, %5, %6, %7, %8, %9, %10, %11, %12, %13, %14, %15, %16, %17, %18, %19, %20, %21, %22, %23, %24, %25, %26, %27, %28, %29, %30, %31, %32, %33, %34, %35, %36, %37, %38, %39, %40, %41, %42, %43, %44, %45, %46, %47, %48, %49, %50, %51, %52, %53, %54, %55, %56, %57, %58, %59, %60, %61, %62, %63}, {%64, %65, %66, %67}, %68, p, 1, 1, 0;\n}\n"
    : "=f"(d[0]), "=f"(d[1]), "=f"(d[2]), "=f"(d[3]), "=f"(d[4]), "=f"(d[5]), "=f"(d[6]), "=f"(d[7]), "=f"(d[8]), "=f"(d[9]), "=f"(d[10]), "=f"(d[11]), "=f"(d[12]), "=f"(d[13]), "=f"(d[14]), "=f"(d[15]), "=f"(d[16]), "=f"(d[17]), "=f"(d[18]), "=f"(d[19]), "=f"(d[20]), "=f"(d[21]), "=f"(d[22]), "=f"(d[23]), "=f"(d[24]), "=f"(d[25]), "=f"(d[26]), "=f"(d[27]), "=f"(d[28]), "=f"(d[29]), "=f"(d[30]), "=f"(d[31]), "=f"(d[32]), "=f"(d[33]), "=f"(d[34]), "=f"(d[35]), "=f"(d[36]), "=f"(d[37]), "=f"(d[38]), "=f"(d[39]), "=f"(d[40]), "=f"(d[41]), "=f"(d[42]), "=f"(d[43]), "=f"(d[44]), "=f"(d[45]), "=f"(d[46]), "=f"(d[47]), "=f"(d[48]), "=f"(d[49]), "=f"(d[50]), "=f"(d[51]), "=f"(d[52]), "=f"(d[53]), "=f"(d[54]), "=f"(d[55]), "=f"(d[56]), "=f"(d[57]), "=f"(d[58]), "=f"(d[59]), "=f"(d[60]), "=f"(d[61]), "=f"(d[62]), "=f"(d[63])
    : "r"(a0), "r"(a1), "r"(a2), "r"(a3), "l"(db));
}

__device__ __forceinline__ void wgmma_rs_n192_tb(float (&d)[64], float (&e)[64], uint32_t a0, uint32_t a1, uint32_t a2, uint32_t a3, uint64_t db) {
  asm volatile("{\n.reg .pred p;\nsetp.eq.b32 p, 0, 0;\n"
    "wgmma.mma_async.sync.aligned.m64n192k16.f32.bf16.bf16 {%0, %1, %2, %3, %4, %5, %6, %7, %8, %9, %10, %11, %12, %13, %14, %15, %16, %17, %18, %19, %20, %21, %22, %23, %24, %25, %26, %27, %28, %29, %30, %31, %32, %33, %34, %35, %36, %37, %38, %39, %40, %41, %42, %43, %44, %45, %46, %47, %48, %49, %50, %51, %52, %53, %54, %55, %56, %57, %58, %59, %60, %61, %62, %63, %64, %65, %66, %67, %68, %69, %70, %71, %72, %73, %74, %75, %76, %77, %78, %79, %80, %81, %82, %83, %84, %85, %86, %87, %88, %89, %90, %91, %92, %93, %94, %95}, {%96, %97, %98, %99}, %100, p, 1, 1, 1;\n}\n"
    : "+f"(d[0]), "+f"(d[1]), "+f"(d[2]), "+f"(d[3]), "+f"(d[4]), "+f"(d[5]), "+f"(d[6]), "+f"(d[7]), "+f"(d[8]), "+f"(d[9]), "+f"(d[10]), "+f"(d[11]), "+f"(d[12]), "+f"(d[13]), "+f"(d[14]), "+f"(d[15]), "+f"(d[16]), "+f"(d[17]), "+f"(d[18]), "+f"(d[19]), "+f"(d[20]), "+f"(d[21]), "+f"(d[22]), "+f"(d[23]), "+f"(d[24]), "+f"(d[25]), "+f"(d[26]), "+f"(d[27]), "+f"(d[28]), "+f"(d[29]), "+f"(d[30]), "+f"(d[31]), "+f"(d[32]), "+f"(d[33]), "+f"(d[34]), "+f"(d[35]), "+f"(d[36]), "+f"(d[37]), "+f"(d[38]), "+f"(d[39]), "+f"(d[40]), "+f"(d[41]), "+f"(d[42]), "+f"(d[43]), "+f"(d[44]), "+f"(d[45]), "+f"(d[46]), "+f"(d[47]), "+f"(d[48]), "+f"(d[49]), "+f"(d[50]), "+f"(d[51]), "+f"(d[52]), "+f"(d[53]), "+f"(d[54]), "+f"(d[55]), "+f"(d[56]), "+f"(d[57]), "+f"(d[58]), "+f"(d[59]), "+f"(d[60]), "+f"(d[61]), "+f"(d[62]), "+f"(d[63]), "+f"(e[0]), "+f"(e[1]), "+f"(e[2]), "+f"(e[3]), "+f"(e[4]), "+f"(e[5]), "+f"(e[6]), "+f"(e[7]), "+f"(e[8]), "+f"(e[9]), "+f"(e[10]), "+f"(e[11]), "+f"(e[12]), "+f"(e[13]), "+f"(e[14]), "+f"(e[15]), "+f"(e[16]), "+f"(e[17]), "+f"(e[18]), "+f"(e[19]), "+f"(e[20]), "+f"(e[21]), "+f"(e[22]), "+f"(e[23]), "+f"(e[24]), "+f"(e[25]), "+f"(e[26]), "+f"(e[27]), "+f"(e[28]), "+f"(e[29]), "+f"(e[30]), "+f"(e[31])
    : "r"(a0), "r"(a1), "r"(a2), "r"(a3), "l"(db));
}

__device__ __forceinline__ void wgmma_rs_n192_tb_z(float (&d)[64], float (&e)[64], uint32_t a0, uint32_t a1, uint32_t a2, uint32_t a3, uint64_t db) {
  asm volatile("{\n.reg .pred p;\nsetp.ne.b32 p, 0, 0;\n"
    "wgmma.mma_async.sync.aligned.m64n192k16.f32.bf16.bf16 {%0, %1, %2, %3, %4, %5, %6, %7, %8, %9, %10, %11, %12, %13, %14, %15, %16, %17, %18, %19, %20, %21, %22, %23, %24, %25, %26, %27, %28, %29, %30, %31, %32, %33, %34, %35, %36, %37, %38, %39, %40, %41, %42, %43, %44, %45, %46, %47, %48, %49, %50, %51, %52, %53, %54, %55, %56, %57, %58, %59, %60, %61, %62, %63, %64, %65, %66, %67, %68, %69, %70, %71, %72, %73, %74, %75, %76, %77, %78, %79, %80, %81, %82, %83, %84, %85, %86, %87, %88, %89, %90, %91, %92, %93, %94, %95}, {%96, %97, %98, %99}, %100, p, 1, 1, 1;\n}\n"
    : "=f"(d[0]), "=f"(d[1]), "=f"(d[2]), "=f"(d[3]), "=f"(d[4]), "=f"(d[5]), "=f"(d[6]), "=f"(d[7]), "=f"(d[8]), "=f"(d[9]), "=f"(d[10]), "=f"(d[11]), "=f"(d[12]), "=f"(d[13]), "=f"(d[14]), "=f"(d[15]), "=f"(d[16]), "=f"(d[17]), "=f"(d[18]), "=f"(d[19]), "=f"(d[20]), "=f"(d[21]), "=f"(d[22]), "=f"(d[23]), "=f"(d[24]), "=f"(d[25]), "=f"(d[26]), "=f"(d[27]), "=f"(d[28]), "=f"(d[29]), "=f"(d[30]), "=f"(d[31]), "=f"(d[32]), "=f"(d[33]), "=f"(d[34]), "=f"(d[35]), "=f"(d[36]), "=f"(d[37]), "=f"(d[38]), "=f"(d[39]), "=f"(d[40]), "=f"(d[41]), "=f"(d[42]), "=f"(d[43]), "=f"(d[44]), "=f"(d[45]), "=f"(d[46]), "=f"(d[47]), "=f"(d[48]), "=f"(d[49]), "=f"(d[50]), "=f"(d[51]), "=f"(d[52]), "=f"(d[53]), "=f"(d[54]), "=f"(d[55]), "=f"(d[56]), "=f"(d[57]), "=f"(d[58]), "=f"(d[59]), "=f"(d[60]), "=f"(d[61]), "=f"(d[62]), "=f"(d[63]), "=f"(e[0]), "=f"(e[1]), "=f"(e[2]), "=f"(e[3]), "=f"(e[4]), "=f"(e[5]), "=f"(e[6]), "=f"(e[7]), "=f"(e[8]), "=f"(e[9]), "=f"(e[10]), "=f"(e[11]), "=f"(e[12]), "=f"(e[13]), "=f"(e[14]), "=f"(e[15]), "=f"(e[16]), "=f"(e[17]), "=f"(e[18]), "=f"(e[19]), "=f"(e[20]), "=f"(e[21]), "=f"(e[22]), "=f"(e[23]), "=f"(e[24]), "=f"(e[25]), "=f"(e[26]), "=f"(e[27]), "=f"(e[28]), "=f"(e[29]), "=f"(e[30]), "=f"(e[31])
    : "r"(a0), "r"(a1), "r"(a2), "r"(a3), "l"(db));
}

struct Maps {
  CUtensorMap x[2], k[2], v[2], wq[2], wo[2];
  const char* px[2];
};

__device__ __forceinline__ void poll_tiles(int tile, const unsigned (&target)[3], uint32_t ready) {
#pragma unroll
  for (int pn = 0; pn < 2; pn++) {
    const unsigned* c = &g_cnt[(tile * 4 + pn) * 32];
    for (uint32_t it = 0; it < WAIT_LIMIT; ++it) {
      unsigned v;
      asm volatile("ld.acquire.gpu.global.u32 %0, [%1];" : "=r"(v) : "l"(c) : "memory");
      if ((int)(v - target[pn]) >= 0) break;
    }
    mbar_arrive(ready + pn * 8);
  }
}
__device__ __forceinline__ void read_targets(int tile, unsigned (&target)[3]) {
#pragma unroll
  for (int pn = 0; pn < 3; pn++) {
    unsigned v;
    asm volatile("ld.relaxed.gpu.global.u32 %0, [%1];" : "=r"(v) : "l"(&g_cnt[(tile * 4 + pn) * 32]) : "memory");
    target[pn] = pn < 2 ? (v / 16u + 1u) * 16u : (v / 64u + 1u) * 64u;
  }
}

__global__ void __launch_bounds__(384, 1)
fused_gqa_kernel(const __grid_constant__ Maps maps, __nv_bfloat16* __restrict__ out) {
  extern __shared__ __align__(1024) unsigned char smem[];
  const uint32_t sbase = smem_u32(smem);
  const uint32_t full0 = sbase + BAR_OFF;
  const uint32_t empty0 = full0 + N_ITEMS * 8;
  const uint32_t ready0 = empty0 + N_ITEMS * 8;
  const uint32_t pub0 = ready0 + 6 * 8;
  const uint32_t tgt0 = pub0 + 6 * 8;
  volatile unsigned* s_tgt = reinterpret_cast<volatile unsigned*>(smem + BAR_OFF + 2 * N_ITEMS * 8 + 128);

  const int tid = threadIdx.x;
  const int wg = tid >> 7;
  const int bid = blockIdx.x;
  const int bp = bid & 3;
  const int h = (bid >> 2) & 15;
  const int p = bid >> 6;

  if (tid == 0) {
#pragma unroll
    for (int i = 0; i < 4; i++) mbar_init(full0 + (WQ0 + i) * 8, 1);
#pragma unroll
    for (int i = 0; i < 4; i++) mbar_init(full0 + (X0 + i) * 8, 1);
    mbar_init(full0 + KV0 * 8, 1);
    asm volatile("fence.mbarrier_init.release.cluster;" ::: "memory");
#pragma unroll
    for (int kc = 0; kc < 4; kc++) {
      mbar_expect_tx(full0 + (X0 + kc) * 8, 16384);
      tma_load3(sbase + x_off(kc), &maps.x[p], 0, bp * 128, kc, full0 + (X0 + kc) * 8);
      mbar_expect_tx(full0 + (WQ0 + kc) * 8, T32);
      tma_load3(sbase + wq_off(kc), &maps.wq[p], 0, kc * 64, h * 4, full0 + (WQ0 + kc) * 8);
    }
    mbar_expect_tx(full0 + KV0 * 8, T32);
    tma_load3(sbase + kv_off(0), &maps.k[p], 0, (2 * bp * 16 + h) * kSK, 0, full0 + KV0 * 8);
    TR(0, 56);
  } else if (tid >= 64 && tid < 96) {
    const char* base = maps.px[p] + (size_t)(bp * 128 + h * 8) * 1152;
#pragma unroll
    for (int i = 0; i < 3; i++)
      if ((tid & 31) + i * 32 < 72) l2_prefetch(base + ((tid & 31) + i * 32) * 128);
  } else if (tid == 32) {
    prefetch_tmap(&maps.v[p]);
    prefetch_tmap(&maps.wo[p]);
  } else if (tid >= 128) {
    const int i = tid - 128;
    if (i < N_ITEMS) {
      if (!(i < 4 || (i >= X0 && i < X0 + 4) || i == KV0)) mbar_init(full0 + i * 8, 1);
    } else if (i >= 64 && i < 64 + N_ITEMS) {
      mbar_init(empty0 + (i - 64) * 8, i == 64 + WQ0 ? 4 : 8);
    } else if (i >= 128 && i < 128 + 6) {
      mbar_init(ready0 + (i - 128) * 8, 1);
    } else if (i >= 160 && i < 160 + 6) {
      mbar_init(pub0 + (i - 160) * 8, 4);
    } else if (i >= 192 && i < 192 + 2) {
      mbar_init(tgt0 + (i - 192) * 8, 1);
    }
    asm volatile("fence.mbarrier_init.release.cluster;" ::: "memory");
  }
  __syncthreads();
  if (tid == 0) TR(0, 57);

  if (wg == 0) {
    asm volatile("setmaxnreg.dec.sync.aligned.u32 24;");
    if (tid == 0) {
      const int kvrow = (2 * bp * 16 + h) * kSK;
      auto load_kv = [&](int n) {
        if (n >= KV_INFLIGHT) mbar_wait(full0 + (KV0 + n - KV_INFLIGHT) * 8);
        const uint32_t fb = full0 + (KV0 + n) * 8;
        TR(0, KV0 + n);
        mbar_expect_tx(fb, T32);
        tma_load3(sbase + kv_off(n), (n & 1) ? &maps.v[p] : &maps.k[p], 0, kvrow + (n >> 3) * 16 * kSK + ((n & 7) >> 1) * 128, 0, fb);
      };
#pragma unroll 1
      for (int c = 0; c < 9; c++) {
        mbar_wait(empty0 + (X0 + c) * 8);
        if (c < 5) {
          mbar_expect_tx(full0 + (X0 + c + 4) * 8, 16384);
          tma_load3(sbase + x_off(c + 4), &maps.x[p], 0, bp * 128, c + 4, full0 + (X0 + c + 4) * 8);
        }
        if (c < 5) {
          TR(0, WQ0 + c + 4);
          mbar_expect_tx(full0 + (WQ0 + c + 4) * 8, T32);
          tma_load3(sbase + wq_off(c + 4), &maps.wq[p], 0, (c + 4) * 64, h * 4, full0 + (WQ0 + c + 4) * 8);
        } else if (c < 8) {
          load_kv(c - 4);
          if (c == 7) load_kv(4);
        } else {
          load_kv(5);
        }
      }
#pragma unroll 1
      for (int n = 6; n < N_KV; n++) {
        mbar_wait(empty0 + (KV0 + n - 6) * 8);
        load_kv(n);
      }
      mbar_wait(full0 + (KV0 + N_KV - 1) * 8);
#pragma unroll 1
      for (int m = 0; m < N_WO; m++) {
        const int dep = m >= 9 ? WO0 + m - 9 : (m == 8 ? WQ0 : KV0 + 10 + (int)((0x55443210u >> (m * 4)) & 15u));
        mbar_wait(empty0 + dep * 8);
        const uint32_t fb = full0 + (WO0 + m) * 8;
        TR(0, WO0 + m);
        mbar_expect_tx(fb, WO_BYTES);
        tma_load3(sbase + wo_off(m), &maps.wo[p], 0, h * 256 + (m & 3) * 64, (m >> 2) * 3, fb);
      }
    } else if (tid == 96 || tid == 112) {
      const int w = (tid >> 4) & 1;
      mbar_wait(tgt0 + w * 8);
      const unsigned target[3] = {s_tgt[w * 4], s_tgt[w * 4 + 1], s_tgt[w * 4 + 2]};
      mbar_wait(pub0 + w * 24);
      poll_tiles(p * 8 + 2 * bp + w, target, ready0 + w * 24);
    } else if (tid == 32 || tid == 64) {
      const int w = (tid >> 5) - 1;
      const int tile = p * 8 + 2 * bp + w;
      unsigned target[3];
      read_targets(tile, target);
      s_tgt[w * 4] = target[0];
      s_tgt[w * 4 + 1] = target[1];
      s_tgt[w * 4 + 2] = target[2];
      mbar_arrive(tgt0 + w * 8);
#pragma unroll 1
      for (int e = 0; e < 2; e++) {
        mbar_wait(pub0 + (w * 3 + e) * 8);
        asm volatile("red.release.gpu.global.add.u32 [%0], 1;" ::"l"(&g_cnt[(tile * 4 + e) * 32]) : "memory");
      }
    }
  } else {
    asm volatile("setmaxnreg.inc.sync.aligned.u32 240;");
    const int w = wg - 1;
    const int t128 = tid & 127;
    const int lane = tid & 31;

    auto release = [&](int item) {
      __syncwarp();
      if (lane == 0) mbar_arrive(empty0 + item * 8);
    };

    TRC(0);
    const float cs = 0.08838834764831845f * 1.4426950408889634f;
    float s[64], o[64];
#pragma unroll
    for (int i = 0; i < 64; i++) s[i] = 0.f, o[i] = 0.f;
    uint32_t qf[32];
    uint4* park = reinterpret_cast<uint4*>(smem + PARK_OFF) + w * 1024 + t128;
    {
#pragma unroll 1
      for (int kc = 0; kc < 9; kc++) {
        mbar_wait(full0 + (X0 + kc) * 8);
        mbar_wait(full0 + (WQ0 + kc) * 8);
        if (kc == 0) TRC(1);
        const uint64_t da = make_desc(sbase + x_off(kc), 16, 1024);
        const uint64_t db = make_desc(sbase + wq_off(kc) + w * 16384, 8192, 1024);
        wg_fence();
#pragma unroll
        for (int ks = 0; ks < 4; ks++) {
          wgmma_ss_n128_tb(s, da + ks * 2, db + ks * 128, (kc | ks) != 0);
          wgmma_ss_n128_tb(o, da + 512 + ks * 2, db + ks * 128, (kc | ks) != 0);
        }
        wg_commit();
        wg_wait<0>();
        release(X0 + kc);
      }
      fence_regs(s);
      fence_regs(o);
#pragma unroll
      for (int i = 0; i < 32; i++) qf[i] = pack_bf16(s[2 * i], s[2 * i + 1]);
      named_bar(1, 256);
#pragma unroll
      for (int i = 0; i < 8; i++) park[i * 128] = pack8(o, i);
      TRC(2);
    }
#pragma unroll 1
    for (int bb = 0; bb < 2; bb++) {
#pragma unroll
      for (int i = 0; i < 64; i++) o[i] = 0.f;
      float m0 = -INFINITY, m1 = -INFINITY, l0 = 0.f, l1 = 0.f;
#pragma unroll 1
      for (int t = 0; t < 4; t++) {
        const int n = bb * 8 + t * 2;
        {
          const uint32_t base = sbase + kv_off(n);
          mbar_wait(full0 + (KV0 + n) * 8);
          if (n == 0 && w == 1) named_bar(4, 256);
          const uint64_t db = make_desc(base, 16, 1024);
          wg_fence();
          wgmma_rs_n128_z(s, qf[0], qf[1], qf[2], qf[3], db);
#pragma unroll
          for (int ks = 1; ks < 8; ks++)
            wgmma_rs_n128(s, qf[4 * ks], qf[4 * ks + 1], qf[4 * ks + 2], qf[4 * ks + 3], db + (ks >> 2) * 1024 + (ks & 3) * 2, 1);
          wg_commit();
          wg_wait<0>();
          fence_regs(s);
          if (n == 0 && w == 0) named_arrive(4, 256);
          release(KV0 + n);
        }
        float mx0 = s[0], mx1 = s[2];
#pragma unroll
        for (int g = 0; g < 16; g++) {
          mx0 = fmaxf(mx0, fmaxf(s[4 * g], s[4 * g + 1]));
          mx1 = fmaxf(mx1, fmaxf(s[4 * g + 2], s[4 * g + 3]));
        }
        mx0 = fmaxf(mx0, __shfl_xor_sync(0xffffffffu, mx0, 1));
        mx0 = fmaxf(mx0, __shfl_xor_sync(0xffffffffu, mx0, 2));
        mx1 = fmaxf(mx1, __shfl_xor_sync(0xffffffffu, mx1, 1));
        mx1 = fmaxf(mx1, __shfl_xor_sync(0xffffffffu, mx1, 2));
        const float mn0 = fmaxf(m0, mx0), mn1 = fmaxf(m1, mx1);
        const float a0 = ex2((m0 - mn0) * cs), a1 = ex2((m1 - mn1) * cs);
        m0 = mn0;
        m1 = mn1;
        const float ms0 = mn0 * cs, ms1 = mn1 * cs;
        float rs0 = 0.f, rs1 = 0.f;
        uint32_t pf[32];
#pragma unroll
        for (int g = 0; g < 16; g++) {
          const float p0 = ex2(fmaf(s[4 * g], cs, -ms0));
          const float p1 = ex2(fmaf(s[4 * g + 1], cs, -ms0));
          const float p2 = ex2(fmaf(s[4 * g + 2], cs, -ms1));
          const float p3 = ex2(fmaf(s[4 * g + 3], cs, -ms1));
          rs0 += p0 + p1;
          rs1 += p2 + p3;
          pf[2 * g] = pack_bf16(p0, p1);
          pf[2 * g + 1] = pack_bf16(p2, p3);
        }
        l0 = l0 * a0 + rs0;
        l1 = l1 * a1 + rs1;
#pragma unroll
        for (int g = 0; g < 16; g++) {
          o[4 * g] *= a0;
          o[4 * g + 1] *= a0;
          o[4 * g + 2] *= a1;
          o[4 * g + 3] *= a1;
        }
        {
          const uint32_t base = sbase + kv_off(n + 1);
          mbar_wait(full0 + (KV0 + n + 1) * 8);
          const uint64_t db = make_desc(base, 16384, 1024);
          wg_fence();
#pragma unroll
          for (int ks = 0; ks < 8; ks++)
            wgmma_rs_n128_tb(o, pf[4 * ks], pf[4 * ks + 1], pf[4 * ks + 2], pf[4 * ks + 3], db + ks * 128, 1);
          wg_commit();
          wg_wait<0>();
          fence_regs(o);
          release(KV0 + n + 1);
          TRC(3 + bb * 5 + t);
        }
      }
      l0 += __shfl_xor_sync(0xffffffffu, l0, 1);
      l0 += __shfl_xor_sync(0xffffffffu, l0, 2);
      l1 += __shfl_xor_sync(0xffffffffu, l1, 1);
      l1 += __shfl_xor_sync(0xffffffffu, l1, 2);
      const float i0 = 1.f / l0, i1 = 1.f / l1;
      if (bb == 0) {
#pragma unroll
        for (int i = 0; i < 8; i++) {
          const uint4 v = park[i * 128];
          qf[4 * i] = v.x;
          qf[4 * i + 1] = v.y;
          qf[4 * i + 2] = v.z;
          qf[4 * i + 3] = v.w;
          park[i * 128] = make_uint4(pack_bf16(o[8 * i] * i0, o[8 * i + 1] * i0), pack_bf16(o[8 * i + 2] * i1, o[8 * i + 3] * i1),
                                     pack_bf16(o[8 * i + 4] * i0, o[8 * i + 5] * i0), pack_bf16(o[8 * i + 6] * i1, o[8 * i + 7] * i1));
        }
        if (w == 1) named_arrive(5, 256);
      } else {
#pragma unroll
        for (int i = 0; i < 16; i++) {
          qf[2 * i] = pack_bf16(o[4 * i] * i0, o[4 * i + 1] * i0);
          qf[2 * i + 1] = pack_bf16(o[4 * i + 2] * i1, o[4 * i + 3] * i1);
        }
      }
    }
    uint32_t af[64];
    {
      const uint4* src = reinterpret_cast<const uint4*>(smem + PARK_OFF) + t128;
      if (w == 0) {
        named_bar(5, 256);
#pragma unroll
        for (int i = 0; i < 16; i++) {
          const uint4 v = src[i * 128];
          af[4 * i] = v.x;
          af[4 * i + 1] = v.y;
          af[4 * i + 2] = v.z;
          af[4 * i + 3] = v.w;
        }
#pragma unroll
        for (int i = 0; i < 8; i++) park[i * 128] = make_uint4(qf[4 * i], qf[4 * i + 1], qf[4 * i + 2], qf[4 * i + 3]);
        asm volatile("fence.proxy.async.shared::cta;" ::: "memory");
        named_arrive(1, 256);
      } else {
        named_bar(1, 256);
#pragma unroll
        for (int i = 0; i < 8; i++) {
          const uint4 v = src[i * 128];
          af[4 * i] = v.x;
          af[4 * i + 1] = v.y;
          af[4 * i + 2] = v.z;
          af[4 * i + 3] = v.w;
        }
#pragma unroll
        for (int i = 0; i < 32; i++) af[32 + i] = qf[i];
        asm volatile("fence.proxy.async.shared::cta;" ::: "memory");
        release(WQ0);
      }
    }
    TRC(12);
    const int tile = p * 8 + 2 * bp + w;
    uint4* part = g_part + (size_t)(tile * 16 + h) * 36 * 128 + t128;
    mbar_wait(tgt0 + w * 8);
#pragma unroll
    for (int pn = 0; pn < 3; pn++) {
#pragma unroll
      for (int kc = 0; kc < 4; kc++) {
        const int m = pn * 4 + kc;
        mbar_wait(full0 + (WO0 + m) * 8);
        const uint64_t db = make_desc(sbase + wo_off(m), 8192, 1024);
        wg_fence();
#pragma unroll
        for (int ks = 0; ks < 4; ks++) {
          const int a = (kc * 4 + ks) * 4;
          if ((kc | ks) == 0) wgmma_rs_n192_tb_z(s, o, af[a], af[a + 1], af[a + 2], af[a + 3], db);
          else wgmma_rs_n192_tb(s, o, af[a], af[a + 1], af[a + 2], af[a + 3], db + ks * 128);
        }
        wg_commit();
        if (kc > 0) {
          wg_wait<1>();
          if (m - 1 < 3) release(WO0 + m - 1);
        }
      }
      wg_wait<0>();
      fence_regs(s);
      fence_regs32(o);
      TRC(13 + pn * 2);
#pragma unroll
      for (int i = 0; i < 8; i++) __stcg(part + (pn * 12 + i) * 128, pack8(s, i));
#pragma unroll
      for (int i = 0; i < 4; i++) __stcg(part + (pn * 12 + 8 + i) * 128, pack8(o, i));
      __syncwarp();
      if (lane == 0) {
        if (pn < 2) mbar_arrive(pub0 + (w * 3 + pn) * 8);
        else asm volatile("red.release.gpu.global.add.u32 [%0], 1;" ::"l"(&g_cnt[(tile * 4 + 2) * 32]) : "memory");
      }
      TRC(14 + pn * 2);
    }
    if (t128 < 96) {
      const int u = h * 96 + t128;
      const int slot = u >> 7, thr = u & 127;
      const int row0 = (thr >> 5) * 16 + ((thr & 31) >> 2);
      __nv_bfloat16* orow = out + (size_t)((2 * bp + w) * 64 + row0) * 1152 + p * 576 + slot * 16 + (thr & 3) * 2;
      const uint4* pr = g_part + (size_t)(tile * 16) * 36 * 128 + slot * 128 + thr;
      uint4 v[3][16];
      auto fetch = [&](int pn) {
        if (pn < 2) {
          mbar_wait(ready0 + (w * 3 + pn) * 8);
        } else {
          if (lane == 0) {
            const unsigned tgt = s_tgt[w * 4 + 2];
            for (uint32_t it = 0; it < WAIT_LIMIT; ++it) {
              unsigned c;
              asm volatile("ld.acquire.gpu.global.u32 %0, [%1];" : "=r"(c) : "l"(&g_cnt[(tile * 4 + 2) * 32]) : "memory");
              if ((int)(c - tgt) >= 0) break;
            }
          }
          __syncwarp();
        }
        TRC(19 + pn);
#pragma unroll
        for (int c = 0; c < 16; c++) v[pn][c] = __ldcg(pr + (size_t)(c * 36 + pn * 12) * 128);
      };
      auto finish = [&](int pn) {
        float a[8];
#pragma unroll
        for (int e = 0; e < 8; e++) a[e] = 0.f;
#pragma unroll
        for (int c = 0; c < 16; c++) {
          a[0] += bf_lo(v[pn][c].x);
          a[1] += bf_hi(v[pn][c].x);
          a[2] += bf_lo(v[pn][c].y);
          a[3] += bf_hi(v[pn][c].y);
          a[4] += bf_lo(v[pn][c].z);
          a[5] += bf_hi(v[pn][c].z);
          a[6] += bf_lo(v[pn][c].w);
          a[7] += bf_hi(v[pn][c].w);
        }
        __nv_bfloat16* op = orow + pn * 192;
        *reinterpret_cast<uint32_t*>(op) = pack_bf16(a[0], a[1]);
        *reinterpret_cast<uint32_t*>(op + 8 * 1152) = pack_bf16(a[2], a[3]);
        *reinterpret_cast<uint32_t*>(op + 8) = pack_bf16(a[4], a[5]);
        *reinterpret_cast<uint32_t*>(op + 8 * 1152 + 8) = pack_bf16(a[6], a[7]);
      };
      fetch(0);
      fetch(1);
      finish(0);
      finish(1);
      fetch(2);
      finish(2);
    }
    TRC(22);
  }
}

typedef CUresult (*EncodeFn)(CUtensorMap*, CUtensorMapDataType, cuuint32_t, void*, const cuuint64_t*, const cuuint64_t*,
                             const cuuint32_t*, const cuuint32_t*, CUtensorMapInterleave, CUtensorMapSwizzle,
                             CUtensorMapL2promotion, CUtensorMapFloatOOBfill);

void encode3d(EncodeFn fn, CUtensorMap* m, void* ptr, uint64_t cols, uint64_t rows, uint32_t box_rows, uint32_t box_chunks) {
  cuuint64_t dims[3] = {64, rows, cols / 64};
  cuuint64_t strides[2] = {cols * 2, 128};
  cuuint32_t box[3] = {64, box_rows, box_chunks};
  cuuint32_t es[3] = {1, 1, 1};
  fn(m, CU_TENSOR_MAP_DATA_TYPE_BFLOAT16, 3, ptr, dims, strides, box, es, CU_TENSOR_MAP_INTERLEAVE_NONE,
     CU_TENSOR_MAP_SWIZZLE_128B, CU_TENSOR_MAP_L2_PROMOTION_NONE, CU_TENSOR_MAP_FLOAT_OOB_FILL_NONE);
}

}

extern "C" void kernel_launch(void* const* d_in, const int* in_sizes, int n_in, void* d_out, int out_size) {
  static EncodeFn fn = nullptr;
  if (!fn) {
    void* f = nullptr;
    cudaDriverEntryPointQueryResult st;
    cudaGetDriverEntryPoint("cuTensorMapEncodeTiled", &f, cudaEnableDefault, &st);
    fn = (EncodeFn)f;
    cudaFuncSetAttribute(fused_gqa_kernel, cudaFuncAttributeMaxDynamicSharedMemorySize, SMEM_BYTES);
  }
  Maps maps;
  for (int p = 0; p < 2; p++) {
    encode3d(fn, &maps.x[p], d_in[p * 5 + 0], kD, 512, 128, 1);
    encode3d(fn, &maps.k[p], d_in[p * 5 + 1], kDH, 8 * 16 * kSK, 128, 2);
    encode3d(fn, &maps.v[p], d_in[p * 5 + 2], kDH, 8 * 16 * kSK, 128, 2);
    encode3d(fn, &maps.wq[p], d_in[p * 5 + 3], kHQD, kD, 64, 4);
    encode3d(fn, &maps.wo[p], d_in[p * 5 + 4], kD, kHQD, 64, 3);
    maps.px[p] = (const char*)d_in[p * 5 + 0];
  }
  fused_gqa_kernel<<<128, 384, SMEM_BYTES>>>(maps, (__nv_bfloat16*)d_out);
}
```

```cpp
#include <cuda_runtime.h>
#include <cuda_bf16.h>
#include <cuda.h>
#include <stdint.h>

namespace {

constexpr int kD = 576, kHQD = 4096, kSK = 512, kDH = 128;

constexpr int N_WQ = 9, N_X = 9, N_KV = 16, N_WO = 12;
constexpr int N_ITEMS = N_WQ + N_X + N_KV + N_WO;
constexpr int T32 = 32 * 1024;
constexpr int WO_BYTES = 24 * 1024;
constexpr int PARK_OFF = 192 * 1024;
constexpr int BAR_OFF = 224 * 1024;
constexpr int SMEM_BYTES = BAR_OFF + 2 * N_ITEMS * 8 + 256;
constexpr int WQ0 = 0, X0 = N_WQ, KV0 = X0 + N_X, WO0 = KV0 + N_KV;
#define KV_INFLIGHT 2

__device__ __forceinline__ int wq_off(int kc) { return (kc & 3) * T32; }
__device__ __forceinline__ int x_off(int kc) { return ((kc & 2) ? 5 * T32 : PARK_OFF) + (kc & 1) * 16384; }
__device__ __forceinline__ int ring_off(int pos) { return (int)((0x053214u >> ((pos % 6) * 4)) & 15u) * T32; }
__device__ __forceinline__ int kv_off(int n) { return ring_off(n); }
__device__ __forceinline__ int wo_off(int m) { return (int)((0x607854321607ull >> (m * 4)) & 15ull) * WO_BYTES; }

__device__ uint4 g_part[16 * 16 * 36 * 128];
__device__ unsigned int g_cnt[16 * 4 * 32];

#define TR(role, ev)
#define TRC(ev)
constexpr uint32_t WAIT_CYCLES = 1u << 24;
constexpr uint32_t WAIT_LIMIT = 1u << 15;
__device__ __forceinline__ uint32_t smem_u32(const void* p) { return (uint32_t)__cvta_generic_to_shared(p); }
__device__ __forceinline__ void mbar_init(uint32_t bar, uint32_t cnt) {
  asm volatile("mbarrier.init.shared::cta.b64 [%0], %1;" ::"r"(bar), "r"(cnt) : "memory");
}
__device__ __forceinline__ void mbar_expect_tx(uint32_t bar, uint32_t bytes) {
  asm volatile("mbarrier.arrive.expect_tx.shared::cta.b64 _, [%0], %1;" ::"r"(bar), "r"(bytes) : "memory");
}
__device__ __forceinline__ void mbar_arrive(uint32_t bar) {
  asm volatile("mbarrier.arrive.shared::cta.b64 _, [%0];" ::"r"(bar) : "memory");
}
__device__ __forceinline__ bool mbar_try(uint32_t bar, uint32_t parity) {
  uint32_t ok;
  asm volatile(
      "{\n.reg .pred p;\nmbarrier.try_wait.parity.shared::cta.b64 p, [%1], %2;\nselp.u32 %0, 1, 0, p;\n}\n"
      : "=r"(ok)
      : "r"(bar), "r"(parity)
      : "memory");
  return ok != 0;
}
__device__ __forceinline__ void mbar_wait(uint32_t bar) {
  if (mbar_try(bar, 0)) return;
  const uint32_t t0 = (uint32_t)clock();
  while (!mbar_try(bar, 0))
    if ((uint32_t)clock() - t0 > WAIT_CYCLES) break;
}
__device__ __forceinline__ void tma_load3(uint32_t dst, const CUtensorMap* tm, int c0, int c1, int c2, uint32_t bar) {
  asm volatile(
      "cp.async.bulk.tensor.3d.shared::cluster.global.mbarrier::complete_tx::bytes [%0], [%1, {%3, %4, %5}], [%2];" ::"r"(dst),
      "l"(tm), "r"(bar), "r"(c0), "r"(c1), "r"(c2)
      : "memory");
}
__device__ __forceinline__ void l2_prefetch(const void* p) { asm volatile("prefetch.global.L2 [%0];" ::"l"(p) : "memory"); }
__device__ __forceinline__ void prefetch_tmap(const CUtensorMap* tm) {
  asm volatile("prefetch.tensormap [%0];" ::"l"(tm) : "memory");
}
__device__ __forceinline__ void named_bar(int id, int n) { asm volatile("bar.sync %0, %1;" ::"r"(id), "r"(n) : "memory"); }
__device__ __forceinline__ void named_arrive(int id, int n) { asm volatile("bar.arrive %0, %1;" ::"r"(id), "r"(n) : "memory"); }
__device__ __forceinline__ void wg_fence() { asm volatile("wgmma.fence.sync.aligned;" ::: "memory"); }
__device__ __forceinline__ void wg_commit() { asm volatile("wgmma.commit_group.sync.aligned;" ::: "memory"); }
template <int N>
__device__ __forceinline__ void wg_wait() { asm volatile("wgmma.wait_group.sync.aligned %0;" ::"n"(N) : "memory"); }
template <int N>
__device__ __forceinline__ void fence_regs(float (&d)[N]) {
#pragma unroll
  for (int i = 0; i < N; i++) asm volatile("" : "+f"(d[i])::"memory");
}
__device__ __forceinline__ void fence_regs32(float (&d)[64]) {
#pragma unroll
  for (int i = 0; i < 32; i++) asm volatile("" : "+f"(d[i])::"memory");
}
__device__ __forceinline__ uint64_t make_desc(uint32_t addr, uint32_t lbo, uint32_t sbo) {
  return (uint64_t)((addr & 0x3FFFF) >> 4) | ((uint64_t)(lbo >> 4) << 16) | ((uint64_t)(sbo >> 4) << 32) | (1ull << 62);
}
__device__ __forceinline__ uint32_t pack_bf16(float lo, float hi) {
  uint32_t r;
  asm("cvt.rn.bf16x2.f32 %0, %1, %2;" : "=r"(r) : "f"(hi), "f"(lo));
  return r;
}
__device__ __forceinline__ float ex2(float x) {
  float y;
  asm("ex2.approx.ftz.f32 %0, %1;" : "=f"(y) : "f"(x));
  return y;
}
__device__ __forceinline__ float bf_lo(uint32_t v) { return __uint_as_float(v << 16); }
__device__ __forceinline__ float bf_hi(uint32_t v) { return __uint_as_float(v & 0xffff0000u); }
template <int N>
__device__ __forceinline__ uint4 pack8(const float (&a)[N], int i) {
  return make_uint4(pack_bf16(a[8 * i], a[8 * i + 1]), pack_bf16(a[8 * i + 2], a[8 * i + 3]), pack_bf16(a[8 * i + 4], a[8 * i + 5]),
                    pack_bf16(a[8 * i + 6], a[8 * i + 7]));
}

__device__ __forceinline__ void wgmma_ss_n128_tb(float (&d)[64], uint64_t da, uint64_t db, int scale_d) {
  asm volatile("{\n.reg .pred p;\nsetp.ne.b32 p, %66, 0;\n"
    "wgmma.mma_async.sync.aligned.m64n128k16.f32.bf16.bf16 {%0, %1, %2, %3, %4, %5, %6, %7, %8, %9, %10, %11, %12, %13, %14, %15, %16, %17, %18, %19, %20, %21, %22, %23, %24, %25, %26, %27, %28, %29, %30, %31, %32, %33, %34, %35, %36, %37, %38, %39, %40, %41, %42, %43, %44, %45, %46, %47, %48, %49, %50, %51, %52, %53, %54, %55, %56, %57, %58, %59, %60, %61, %62, %63}, %64, %65, p, 1, 1, 0, 1;\n}\n"
    : "+f"(d[0]), "+f"(d[1]), "+f"(d[2]), "+f"(d[3]), "+f"(d[4]), "+f"(d[5]), "+f"(d[6]), "+f"(d[7]), "+f"(d[8]), "+f"(d[9]), "+f"(d[10]), "+f"(d[11]), "+f"(d[12]), "+f"(d[13]), "+f"(d[14]), "+f"(d[15]), "+f"(d[16]), "+f"(d[17]), "+f"(d[18]), "+f"(d[19]), "+f"(d[20]), "+f"(d[21]), "+f"(d[22]), "+f"(d[23]), "+f"(d[24]), "+f"(d[25]), "+f"(d[26]), "+f"(d[27]), "+f"(d[28]), "+f"(d[29]), "+f"(d[30]), "+f"(d[31]), "+f"(d[32]), "+f"(d[33]), "+f"(d[34]), "+f"(d[35]), "+f"(d[36]), "+f"(d[37]), "+f"(d[38]), "+f"(d[39]), "+f"(d[40]), "+f"(d[41]), "+f"(d[42]), "+f"(d[43]), "+f"(d[44]), "+f"(d[45]), "+f"(d[46]), "+f"(d[47]), "+f"(d[48]), "+f"(d[49]), "+f"(d[50]), "+f"(d[51]), "+f"(d[52]), "+f"(d[53]), "+f"(d[54]), "+f"(d[55]), "+f"(d[56]), "+f"(d[57]), "+f"(d[58]), "+f"(d[59]), "+f"(d[60]), "+f"(d[61]), "+f"(d[62]), "+f"(d[63])
    : "l"(da), "l"(db), "r"(scale_d));
}

__device__ __forceinline__ void wgmma_rs_n128(float (&d)[64], uint32_t a0, uint32_t a1, uint32_t a2, uint32_t a3, uint64_t db, int scale_d) {
  asm volatile("{\n.reg .pred p;\nsetp.ne.b32 p, %69, 0;\n"
    "wgmma.mma_async.sync.aligned.m64n128k16.f32.bf16.bf16 {%0, %1, %2, %3, %4, %5, %6, %7, %8, %9, %10, %11, %12, %13, %14, %15, %16, %17, %18, %19, %20, %21, %22, %23, %24, %25, %26, %27, %28, %29, %30, %31, %32, %33, %34, %35, %36, %37, %38, %39, %40, %41, %42, %43, %44, %45, %46, %47, %48, %49, %50, %51, %52, %53, %54, %55, %56, %57, %58, %59, %60, %61, %62, %63}, {%64, %65, %66, %67}, %68, p, 1, 1, 0;\n}\n"
    : "+f"(d[0]), "+f"(d[1]), "+f"(d[2]), "+f"(d[3]), "+f"(d[4]), "+f"(d[5]), "+f"(d[6]), "+f"(d[7]), "+f"(d[8]), "+f"(d[9]), "+f"(d[10]), "+f"(d[11]), "+f"(d[12]), "+f"(d[13]), "+f"(d[14]), "+f"(d[15]), "+f"(d[16]), "+f"(d[17]), "+f"(d[18]), "+f"(d[19]), "+f"(d[20]), "+f"(d[21]), "+f"(d[22]), "+f"(d[23]), "+f"(d[24]), "+f"(d[25]), "+f"(d[26]), "+f"(d[27]), "+f"(d[28]), "+f"(d[29]), "+f"(d[30]), "+f"(d[31]), "+f"(d[32]), "+f"(d[33]), "+f"(d[34]), "+f"(d[35]), "+f"(d[36]), "+f"(d[37]), "+f"(d[38]), "+f"(d[39]), "+f"(d[40]), "+f"(d[41]), "+f"(d[42]), "+f"(d[43]), "+f"(d[44]), "+f"(d[45]), "+f"(d[46]), "+f"(d[47]), "+f"(d[48]), "+f"(d[49]), "+f"(d[50]), "+f"(d[51]), "+f"(d[52]), "+f"(d[53]), "+f"(d[54]), "+f"(d[55]), "+f"(d[56]), "+f"(d[57]), "+f"(d[58]), "+f"(d[59]), "+f"(d[60]), "+f"(d[61]), "+f"(d[62]), "+f"(d[63])
    : "r"(a0), "r"(a1), "r"(a2), "r"(a3), "l"(db), "r"(scale_d));
}

__device__ __forceinline__ void wgmma_rs_n128_tb(float (&d)[64], uint32_t a0, uint32_t a1, uint32_t a2, uint32_t a3, uint64_t db, int scale_d) {
  asm volatile("{\n.reg .pred p;\nsetp.ne.b32 p, %69, 0;\n"
    "wgmma.mma_async.sync.aligned.m64n128k16.f32.bf16.bf16 {%0, %1, %2, %3, %4, %5, %6, %7, %8, %9, %10, %11, %12, %13, %14, %15, %16, %17, %18, %19, %20, %21, %22, %23, %24, %25, %26, %27, %28, %29, %30, %31, %32, %33, %34, %35, %36, %37, %38, %39, %40, %41, %42, %43, %44, %45, %46, %47, %48, %49, %50, %51, %52, %53, %54, %55, %56, %57, %58, %59, %60, %61, %62, %63}, {%64, %65, %66, %67}, %68, p, 1, 1, 1;\n}\n"
    : "+f"(d[0]), "+f"(d[1]), "+f"(d[2]), "+f"(d[3]), "+f"(d[4]), "+f"(d[5]), "+f"(d[6]), "+f"(d[7]), "+f"(d[8]), "+f"(d[9]), "+f"(d[10]), "+f"(d[11]), "+f"(d[12]), "+f"(d[13]), "+f"(d[14]), "+f"(d[15]), "+f"(d[16]), "+f"(d[17]), "+f"(d[18]), "+f"(d[19]), "+f"(d[20]), "+f"(d[21]), "+f"(d[22]), "+f"(d[23]), "+f"(d[24]), "+f"(d[25]), "+f"(d[26]), "+f"(d[27]), "+f"(d[28]), "+f"(d[29]), "+f"(d[30]), "+f"(d[31]), "+f"(d[32]), "+f"(d[33]), "+f"(d[34]), "+f"(d[35]), "+f"(d[36]), "+f"(d[37]), "+f"(d[38]), "+f"(d[39]), "+f"(d[40]), "+f"(d[41]), "+f"(d[42]), "+f"(d[43]), "+f"(d[44]), "+f"(d[45]), "+f"(d[46]), "+f"(d[47]), "+f"(d[48]), "+f"(d[49]), "+f"(d[50]), "+f"(d[51]), "+f"(d[52]), "+f"(d[53]), "+f"(d[54]), "+f"(d[55]), "+f"(d[56]), "+f"(d[57]), "+f"(d[58]), "+f"(d[59]), "+f"(d[60]), "+f"(d[61]), "+f"(d[62]), "+f"(d[63])
    : "r"(a0), "r"(a1), "r"(a2), "r"(a3), "l"(db), "r"(scale_d));
}

__device__ __forceinline__ void wgmma_rs_n128_z(float (&d)[64], uint32_t a0, uint32_t a1, uint32_t a2, uint32_t a3, uint64_t db) {
  asm volatile("{\n.reg .pred p;\nsetp.ne.b32 p, 0, 0;\n"
    "wgmma.mma_async.sync.aligned.m64n128k16.f32.bf16.bf16 {%0, %1, %2, %3, %4, %5, %6, %7, %8, %9, %10, %11, %12, %13, %14, %15, %16, %17, %18, %19, %20, %21, %22, %23, %24, %25, %26, %27, %28, %29, %30, %31, %32, %33, %34, %35, %36, %37, %38, %39, %40, %41, %42, %43, %44, %45, %46, %47, %48, %49, %50, %51, %52, %53, %54, %55, %56, %57, %58, %59, %60, %61, %62, %63}, {%64, %65, %66, %67}, %68, p, 1, 1, 0;\n}\n"
    : "=f"(d[0]), "=f"(d[1]), "=f"(d[2]), "=f"(d[3]), "=f"(d[4]), "=f"(d[5]), "=f"(d[6]), "=f"(d[7]), "=f"(d[8]), "=f"(d[9]), "=f"(d[10]), "=f"(d[11]), "=f"(d[12]), "=f"(d[13]), "=f"(d[14]), "=f"(d[15]), "=f"(d[16]), "=f"(d[17]), "=f"(d[18]), "=f"(d[19]), "=f"(d[20]), "=f"(d[21]), "=f"(d[22]), "=f"(d[23]), "=f"(d[24]), "=f"(d[25]), "=f"(d[26]), "=f"(d[27]), "=f"(d[28]), "=f"(d[29]), "=f"(d[30]), "=f"(d[31]), "=f"(d[32]), "=f"(d[33]), "=f"(d[34]), "=f"(d[35]), "=f"(d[36]), "=f"(d[37]), "=f"(d[38]), "=f"(d[39]), "=f"(d[40]), "=f"(d[41]), "=f"(d[42]), "=f"(d[43]), "=f"(d[44]), "=f"(d[45]), "=f"(d[46]), "=f"(d[47]), "=f"(d[48]), "=f"(d[49]), "=f"(d[50]), "=f"(d[51]), "=f"(d[52]), "=f"(d[53]), "=f"(d[54]), "=f"(d[55]), "=f"(d[56]), "=f"(d[57]), "=f"(d[58]), "=f"(d[59]), "=f"(d[60]), "=f"(d[61]), "=f"(d[62]), "=f"(d[63])
    : "r"(a0), "r"(a1), "r"(a2), "r"(a3), "l"(db));
}

__device__ __forceinline__ void wgmma_rs_n192_tb(float (&d)[64], float (&e)[64], uint32_t a0, uint32_t a1, uint32_t a2, uint32_t a3, uint64_t db) {
  asm volatile("{\n.reg .pred p;\nsetp.eq.b32 p, 0, 0;\n"
    "wgmma.mma_async.sync.aligned.m64n192k16.f32.bf16.bf16 {%0, %1, %2, %3, %4, %5, %6, %7, %8, %9, %10, %11, %12, %13, %14, %15, %16, %17, %18, %19, %20, %21, %22, %23, %24, %25, %26, %27, %28, %29, %30, %31, %32, %33, %34, %35, %36, %37, %38, %39, %40, %41, %42, %43, %44, %45, %46, %47, %48, %49, %50, %51, %52, %53, %54, %55, %56, %57, %58, %59, %60, %61, %62, %63, %64, %65, %66, %67, %68, %69, %70, %71, %72, %73, %74, %75, %76, %77, %78, %79, %80, %81, %82, %83, %84, %85, %86, %87, %88, %89, %90, %91, %92, %93, %94, %95}, {%96, %97, %98, %99}, %100, p, 1, 1, 1;\n}\n"
    : "+f"(d[0]), "+f"(d[1]), "+f"(d[2]), "+f"(d[3]), "+f"(d[4]), "+f"(d[5]), "+f"(d[6]), "+f"(d[7]), "+f"(d[8]), "+f"(d[9]), "+f"(d[10]), "+f"(d[11]), "+f"(d[12]), "+f"(d[13]), "+f"(d[14]), "+f"(d[15]), "+f"(d[16]), "+f"(d[17]), "+f"(d[18]), "+f"(d[19]), "+f"(d[20]), "+f"(d[21]), "+f"(d[22]), "+f"(d[23]), "+f"(d[24]), "+f"(d[25]), "+f"(d[26]), "+f"(d[27]), "+f"(d[28]), "+f"(d[29]), "+f"(d[30]), "+f"(d[31]), "+f"(d[32]), "+f"(d[33]), "+f"(d[34]), "+f"(d[35]), "+f"(d[36]), "+f"(d[37]), "+f"(d[38]), "+f"(d[39]), "+f"(d[40]), "+f"(d[41]), "+f"(d[42]), "+f"(d[43]), "+f"(d[44]), "+f"(d[45]), "+f"(d[46]), "+f"(d[47]), "+f"(d[48]), "+f"(d[49]), "+f"(d[50]), "+f"(d[51]), "+f"(d[52]), "+f"(d[53]), "+f"(d[54]), "+f"(d[55]), "+f"(d[56]), "+f"(d[57]), "+f"(d[58]), "+f"(d[59]), "+f"(d[60]), "+f"(d[61]), "+f"(d[62]), "+f"(d[63]), "+f"(e[0]), "+f"(e[1]), "+f"(e[2]), "+f"(e[3]), "+f"(e[4]), "+f"(e[5]), "+f"(e[6]), "+f"(e[7]), "+f"(e[8]), "+f"(e[9]), "+f"(e[10]), "+f"(e[11]), "+f"(e[12]), "+f"(e[13]), "+f"(e[14]), "+f"(e[15]), "+f"(e[16]), "+f"(e[17]), "+f"(e[18]), "+f"(e[19]), "+f"(e[20]), "+f"(e[21]), "+f"(e[22]), "+f"(e[23]), "+f"(e[24]), "+f"(e[25]), "+f"(e[26]), "+f"(e[27]), "+f"(e[28]), "+f"(e[29]), "+f"(e[30]), "+f"(e[31])
    : "r"(a0), "r"(a1), "r"(a2), "r"(a3), "l"(db));
}

__device__ __forceinline__ void wgmma_rs_n192_tb_z(float (&d)[64], float (&e)[64], uint32_t a0, uint32_t a1, uint32_t a2, uint32_t a3, uint64_t db) {
  asm volatile("{\n.reg .pred p;\nsetp.ne.b32 p, 0, 0;\n"
    "wgmma.mma_async.sync.aligned.m64n192k16.f32.bf16.bf16 {%0, %1, %2, %3, %4, %5, %6, %7, %8, %9, %10, %11, %12, %13, %14, %15, %16, %17, %18, %19, %20, %21, %22, %23, %24, %25, %26, %27, %28, %29, %30, %31, %32, %33, %34, %35, %36, %37, %38, %39, %40, %41, %42, %43, %44, %45, %46, %47, %48, %49, %50, %51, %52, %53, %54, %55, %56, %57, %58, %59, %60, %61, %62, %63, %64, %65, %66, %67, %68, %69, %70, %71, %72, %73, %74, %75, %76, %77, %78, %79, %80, %81, %82, %83, %84, %85, %86, %87, %88, %89, %90, %91, %92, %93, %94, %95}, {%96, %97, %98, %99}, %100, p, 1, 1, 1;\n}\n"
    : "=f"(d[0]), "=f"(d[1]), "=f"(d[2]), "=f"(d[3]), "=f"(d[4]), "=f"(d[5]), "=f"(d[6]), "=f"(d[7]), "=f"(d[8]), "=f"(d[9]), "=f"(d[10]), "=f"(d[11]), "=f"(d[12]), "=f"(d[13]), "=f"(d[14]), "=f"(d[15]), "=f"(d[16]), "=f"(d[17]), "=f"(d[18]), "=f"(d[19]), "=f"(d[20]), "=f"(d[21]), "=f"(d[22]), "=f"(d[23]), "=f"(d[24]), "=f"(d[25]), "=f"(d[26]), "=f"(d[27]), "=f"(d[28]), "=f"(d[29]), "=f"(d[30]), "=f"(d[31]), "=f"(d[32]), "=f"(d[33]), "=f"(d[34]), "=f"(d[35]), "=f"(d[36]), "=f"(d[37]), "=f"(d[38]), "=f"(d[39]), "=f"(d[40]), "=f"(d[41]), "=f"(d[42]), "=f"(d[43]), "=f"(d[44]), "=f"(d[45]), "=f"(d[46]), "=f"(d[47]), "=f"(d[48]), "=f"(d[49]), "=f"(d[50]), "=f"(d[51]), "=f"(d[52]), "=f"(d[53]), "=f"(d[54]), "=f"(d[55]), "=f"(d[56]), "=f"(d[57]), "=f"(d[58]), "=f"(d[59]), "=f"(d[60]), "=f"(d[61]), "=f"(d[62]), "=f"(d[63]), "=f"(e[0]), "=f"(e[1]), "=f"(e[2]), "=f"(e[3]), "=f"(e[4]), "=f"(e[5]), "=f"(e[6]), "=f"(e[7]), "=f"(e[8]), "=f"(e[9]), "=f"(e[10]), "=f"(e[11]), "=f"(e[12]), "=f"(e[13]), "=f"(e[14]), "=f"(e[15]), "=f"(e[16]), "=f"(e[17]), "=f"(e[18]), "=f"(e[19]), "=f"(e[20]), "=f"(e[21]), "=f"(e[22]), "=f"(e[23]), "=f"(e[24]), "=f"(e[25]), "=f"(e[26]), "=f"(e[27]), "=f"(e[28]), "=f"(e[29]), "=f"(e[30]), "=f"(e[31])
    : "r"(a0), "r"(a1), "r"(a2), "r"(a3), "l"(db));
}

struct Maps {
  CUtensorMap x[2], k[2], v[2], wq[2], wo[2];
  const char* px[2];
};

__device__ __forceinline__ void poll_tiles(int tile, const unsigned (&target)[3], uint32_t ready) {
#pragma unroll
  for (int pn = 0; pn < 3; pn++) {
    const unsigned* c = &g_cnt[(tile * 4 + pn) * 32];
    for (uint32_t it = 0; it < WAIT_LIMIT; ++it) {
      unsigned v;
      asm volatile("ld.acquire.gpu.global.u32 %0, [%1];" : "=r"(v) : "l"(c) : "memory");
      if ((int)(v - target[pn]) >= 0) break;
    }
    mbar_arrive(ready + pn * 8);
  }
}
__device__ __forceinline__ void read_targets(int tile, unsigned (&target)[3]) {
#pragma unroll
  for (int pn = 0; pn < 3; pn++) {
    unsigned v;
    asm volatile("ld.relaxed.gpu.global.u32 %0, [%1];" : "=r"(v) : "l"(&g_cnt[(tile * 4 + pn) * 32]) : "memory");
    target[pn] = (v / 16u + 1u) * 16u;
  }
}

__global__ void __launch_bounds__(384, 1)
fused_gqa_kernel(const __grid_constant__ Maps maps, __nv_bfloat16* __restrict__ out) {
  extern __shared__ __align__(1024) unsigned char smem[];
  const uint32_t sbase = smem_u32(smem);
  const uint32_t full0 = sbase + BAR_OFF;
  const uint32_t empty0 = full0 + N_ITEMS * 8;
  const uint32_t ready0 = empty0 + N_ITEMS * 8;
  const uint32_t pub0 = ready0 + 6 * 8;
  const uint32_t tgt0 = pub0 + 6 * 8;
  volatile unsigned* s_tgt = reinterpret_cast<volatile unsigned*>(smem + BAR_OFF + 2 * N_ITEMS * 8 + 128);

  const int tid = threadIdx.x;
  const int wg = tid >> 7;
  const int bid = blockIdx.x;
  const int bp = bid & 3;
  const int h = (bid >> 2) & 15;
  const int p = bid >> 6;

  if (tid == 0) {
#pragma unroll
    for (int i = 0; i < 4; i++) mbar_init(full0 + (WQ0 + i) * 8, 1);
#pragma unroll
    for (int i = 0; i < 4; i++) mbar_init(full0 + (X0 + i) * 8, 1);
    mbar_init(full0 + KV0 * 8, 1);
    asm volatile("fence.mbarrier_init.release.cluster;" ::: "memory");
#pragma unroll
    for (int kc = 0; kc < 4; kc++) {
      mbar_expect_tx(full0 + (X0 + kc) * 8, 16384);
      tma_load3(sbase + x_off(kc), &maps.x[p], 0, bp * 128, kc, full0 + (X0 + kc) * 8);
      mbar_expect_tx(full0 + (WQ0 + kc) * 8, T32);
      tma_load3(sbase + wq_off(kc), &maps.wq[p], 0, kc * 64, h * 4, full0 + (WQ0 + kc) * 8);
    }
    mbar_expect_tx(full0 + KV0 * 8, T32);
    tma_load3(sbase + kv_off(0), &maps.k[p], 0, (2 * bp * 16 + h) * kSK, 0, full0 + KV0 * 8);
    TR(0, 56);
  } else if (tid >= 64 && tid < 96) {
    const char* base = maps.px[p] + (size_t)(bp * 128 + h * 8) * 1152;
#pragma unroll
    for (int i = 0; i < 3; i++)
      if ((tid & 31) + i * 32 < 72) l2_prefetch(base + ((tid & 31) + i * 32) * 128);
  } else if (tid == 32) {
    prefetch_tmap(&maps.v[p]);
    prefetch_tmap(&maps.wo[p]);
  } else if (tid >= 128) {
    const int i = tid - 128;
    if (i < N_ITEMS) {
      if (!(i < 4 || (i >= X0 && i < X0 + 4) || i == KV0)) mbar_init(full0 + i * 8, 1);
    } else if (i >= 64 && i < 64 + N_ITEMS) {
      mbar_init(empty0 + (i - 64) * 8, i == 64 + WQ0 ? 4 : 8);
    } else if (i >= 128 && i < 128 + 6) {
      mbar_init(ready0 + (i - 128) * 8, 1);
    } else if (i >= 160 && i < 160 + 6) {
      mbar_init(pub0 + (i - 160) * 8, 4);
    } else if (i >= 192 && i < 192 + 2) {
      mbar_init(tgt0 + (i - 192) * 8, 1);
    }
    asm volatile("fence.mbarrier_init.release.cluster;" ::: "memory");
  }
  __syncthreads();
  if (tid == 0) TR(0, 57);

  if (wg == 0) {
    asm volatile("setmaxnreg.dec.sync.aligned.u32 24;");
    if (tid == 0) {
      const int kvrow = (2 * bp * 16 + h) * kSK;
      auto load_kv = [&](int n) {
        if (n >= KV_INFLIGHT) mbar_wait(full0 + (KV0 + n - KV_INFLIGHT) * 8);
        const uint32_t fb = full0 + (KV0 + n) * 8;
        TR(0, KV0 + n);
        mbar_expect_tx(fb, T32);
        tma_load3(sbase + kv_off(n), (n & 1) ? &maps.v[p] : &maps.k[p], 0, kvrow + (n >> 3) * 16 * kSK + ((n & 7) >> 1) * 128, 0, fb);
      };
#pragma unroll 1
      for (int c = 0; c < 9; c++) {
        mbar_wait(empty0 + (X0 + c) * 8);
        if (c < 5) {
          mbar_expect_tx(full0 + (X0 + c + 4) * 8, 16384);
          tma_load3(sbase + x_off(c + 4), &maps.x[p], 0, bp * 128, c + 4, full0 + (X0 + c + 4) * 8);
        }
        if (c < 5) {
          TR(0, WQ0 + c + 4);
          mbar_expect_tx(full0 + (WQ0 + c + 4) * 8, T32);
          tma_load3(sbase + wq_off(c + 4), &maps.wq[p], 0, (c + 4) * 64, h * 4, full0 + (WQ0 + c + 4) * 8);
        } else if (c < 8) {
          load_kv(c - 4);
          if (c == 7) load_kv(4);
        } else {
          load_kv(5);
        }
      }
#pragma unroll 1
      for (int n = 6; n < N_KV; n++) {
        mbar_wait(empty0 + (KV0 + n - 6) * 8);
        load_kv(n);
      }
      mbar_wait(full0 + (KV0 + N_KV - 1) * 8);
#pragma unroll 1
      for (int m = 0; m < N_WO; m++) {
        const int dep = m >= 9 ? WO0 + m - 9 : (m == 8 ? WQ0 : KV0 + 10 + (int)((0x55443210u >> (m * 4)) & 15u));
        mbar_wait(empty0 + dep * 8);
        const uint32_t fb = full0 + (WO0 + m) * 8;
        TR(0, WO0 + m);
        mbar_expect_tx(fb, WO_BYTES);
        tma_load3(sbase + wo_off(m), &maps.wo[p], 0, h * 256 + (m & 3) * 64, (m >> 2) * 3, fb);
      }
    } else if (tid == 96 || tid == 112) {
      const int w = (tid >> 4) & 1;
      mbar_wait(tgt0 + w * 8);
      const unsigned target[3] = {s_tgt[w * 4], s_tgt[w * 4 + 1], s_tgt[w * 4 + 2]};
      mbar_wait(pub0 + w * 24);
      poll_tiles(p * 8 + 2 * bp + w, target, ready0 + w * 24);
    } else if (tid == 32 || tid == 64) {
      const int w = (tid >> 5) - 1;
      const int tile = p * 8 + 2 * bp + w;
      unsigned target[3];
      read_targets(tile, target);
      s_tgt[w * 4] = target[0];
      s_tgt[w * 4 + 1] = target[1];
      s_tgt[w * 4 + 2] = target[2];
      mbar_arrive(tgt0 + w * 8);
#pragma unroll 1
      for (int e = 0; e < 3; e++) {
        mbar_wait(pub0 + (w * 3 + e) * 8);
        asm volatile("red.release.gpu.global.add.u32 [%0], 1;" ::"l"(&g_cnt[(tile * 4 + e) * 32]) : "memory");
      }
    }
  } else {
    asm volatile("setmaxnreg.inc.sync.aligned.u32 240;");
    const int w = wg - 1;
    const int t128 = tid & 127;
    const int lane = tid & 31;

    auto release = [&](int item) {
      __syncwarp();
      if (lane == 0) mbar_arrive(empty0 + item * 8);
    };

    TRC(0);
    const float cs = 0.08838834764831845f * 1.4426950408889634f;
    float s[64], o[64];
#pragma unroll
    for (int i = 0; i < 64; i++) s[i] = 0.f, o[i] = 0.f;
    uint32_t qf[32];
    uint4* park = reinterpret_cast<uint4*>(smem + PARK_OFF) + w * 1024 + t128;
    {
#pragma unroll 1
      for (int kc = 0; kc < 9; kc++) {
        mbar_wait(full0 + (X0 + kc) * 8);
        mbar_wait(full0 + (WQ0 + kc) * 8);
        if (kc == 0) TRC(1);
        const uint64_t da = make_desc(sbase + x_off(kc), 16, 1024);
        const uint64_t db = make_desc(sbase + wq_off(kc) + w * 16384, 8192, 1024);
        wg_fence();
#pragma unroll
        for (int ks = 0; ks < 4; ks++) {
          wgmma_ss_n128_tb(s, da + ks * 2, db + ks * 128, (kc | ks) != 0);
          wgmma_ss_n128_tb(o, da + 512 + ks * 2, db + ks * 128, (kc | ks) != 0);
        }
        wg_commit();
        wg_wait<0>();
        release(X0 + kc);
      }
      fence_regs(s);
      fence_regs(o);
#pragma unroll
      for (int i = 0; i < 32; i++) qf[i] = pack_bf16(s[2 * i], s[2 * i + 1]);
      named_bar(1, 256);
#pragma unroll
      for (int i = 0; i < 8; i++) park[i * 128] = pack8(o, i);
      TRC(2);
    }
#pragma unroll 1
    for (int bb = 0; bb < 2; bb++) {
#pragma unroll
      for (int i = 0; i < 64; i++) o[i] = 0.f;
      float m0 = -INFINITY, m1 = -INFINITY, l0 = 0.f, l1 = 0.f;
#pragma unroll 1
      for (int t = 0; t < 4; t++) {
        const int n = bb * 8 + t * 2;
        {
          const uint32_t base = sbase + kv_off(n);
          mbar_wait(full0 + (KV0 + n) * 8);
          if (n == 0 && w == 1) named_bar(4, 256);
          const uint64_t db = make_desc(base, 16, 1024);
          wg_fence();
          wgmma_rs_n128_z(s, qf[0], qf[1], qf[2], qf[3], db);
#pragma unroll
          for (int ks = 1; ks < 8; ks++)
            wgmma_rs_n128(s, qf[4 * ks], qf[4 * ks + 1], qf[4 * ks + 2], qf[4 * ks + 3], db + (ks >> 2) * 1024 + (ks & 3) * 2, 1);
          wg_commit();
          wg_wait<0>();
          fence_regs(s);
          if (n == 0 && w == 0) named_arrive(4, 256);
          release(KV0 + n);
        }
        float mx0 = s[0], mx1 = s[2];
#pragma unroll
        for (int g = 0; g < 16; g++) {
          mx0 = fmaxf(mx0, fmaxf(s[4 * g], s[4 * g + 1]));
          mx1 = fmaxf(mx1, fmaxf(s[4 * g + 2], s[4 * g + 3]));
        }
        mx0 = fmaxf(mx0, __shfl_xor_sync(0xffffffffu, mx0, 1));
        mx0 = fmaxf(mx0, __shfl_xor_sync(0xffffffffu, mx0, 2));
        mx1 = fmaxf(mx1, __shfl_xor_sync(0xffffffffu, mx1, 1));
        mx1 = fmaxf(mx1, __shfl_xor_sync(0xffffffffu, mx1, 2));
        const float mn0 = fmaxf(m0, mx0), mn1 = fmaxf(m1, mx1);
        const float a0 = ex2((m0 - mn0) * cs), a1 = ex2((m1 - mn1) * cs);
        m0 = mn0;
        m1 = mn1;
        const float ms0 = mn0 * cs, ms1 = mn1 * cs;
        float rs0 = 0.f, rs1 = 0.f;
        uint32_t pf[32];
#pragma unroll
        for (int g = 0; g < 16; g++) {
          const float p0 = ex2(fmaf(s[4 * g], cs, -ms0));
          const float p1 = ex2(fmaf(s[4 * g + 1], cs, -ms0));
          const float p2 = ex2(fmaf(s[4 * g + 2], cs, -ms1));
          const float p3 = ex2(fmaf(s[4 * g + 3], cs, -ms1));
          rs0 += p0 + p1;
          rs1 += p2 + p3;
          pf[2 * g] = pack_bf16(p0, p1);
          pf[2 * g + 1] = pack_bf16(p2, p3);
        }
        l0 = l0 * a0 + rs0;
        l1 = l1 * a1 + rs1;
#pragma unroll
        for (int g = 0; g < 16; g++) {
          o[4 * g] *= a0;
          o[4 * g + 1] *= a0;
          o[4 * g + 2] *= a1;
          o[4 * g + 3] *= a1;
        }
        {
          const uint32_t base = sbase + kv_off(n + 1);
          mbar_wait(full0 + (KV0 + n + 1) * 8);
          const uint64_t db = make_desc(base, 16384, 1024);
          wg_fence();
#pragma unroll
          for (int ks = 0; ks < 8; ks++)
            wgmma_rs_n128_tb(o, pf[4 * ks], pf[4 * ks + 1], pf[4 * ks + 2], pf[4 * ks + 3], db + ks * 128, 1);
          wg_commit();
          wg_wait<0>();
          fence_regs(o);
          release(KV0 + n + 1);
          TRC(3 + bb * 5 + t);
        }
      }
      l0 += __shfl_xor_sync(0xffffffffu, l0, 1);
      l0 += __shfl_xor_sync(0xffffffffu, l0, 2);
      l1 += __shfl_xor_sync(0xffffffffu, l1, 1);
      l1 += __shfl_xor_sync(0xffffffffu, l1, 2);
      const float i0 = 1.f / l0, i1 = 1.f / l1;
      if (bb == 0) {
#pragma unroll
        for (int i = 0; i < 8; i++) {
          const uint4 v = park[i * 128];
          qf[4 * i] = v.x;
          qf[4 * i + 1] = v.y;
          qf[4 * i + 2] = v.z;
          qf[4 * i + 3] = v.w;
          park[i * 128] = make_uint4(pack_bf16(o[8 * i] * i0, o[8 * i + 1] * i0), pack_bf16(o[8 * i + 2] * i1, o[8 * i + 3] * i1),
                                     pack_bf16(o[8 * i + 4] * i0, o[8 * i + 5] * i0), pack_bf16(o[8 * i + 6] * i1, o[8 * i + 7] * i1));
        }
        if (w == 1) named_arrive(5, 256);
      } else {
#pragma unroll
        for (int i = 0; i < 16; i++) {
          qf[2 * i] = pack_bf16(o[4 * i] * i0, o[4 * i + 1] * i0);
          qf[2 * i + 1] = pack_bf16(o[4 * i + 2] * i1, o[4 * i + 3] * i1);
        }
      }
    }
    uint32_t af[64];
    {
      const uint4* src = reinterpret_cast<const uint4*>(smem + PARK_OFF) + t128;
      if (w == 0) {
        named_bar(5, 256);
#pragma unroll
        for (int i = 0; i < 16; i++) {
          const uint4 v = src[i * 128];
          af[4 * i] = v.x;
          af[4 * i + 1] = v.y;
          af[4 * i + 2] = v.z;
          af[4 * i + 3] = v.w;
        }
#pragma unroll
        for (int i = 0; i < 8; i++) park[i * 128] = make_uint4(qf[4 * i], qf[4 * i + 1], qf[4 * i + 2], qf[4 * i + 3]);
        asm volatile("fence.proxy.async.shared::cta;" ::: "memory");
        named_arrive(1, 256);
      } else {
        named_bar(1, 256);
#pragma unroll
        for (int i = 0; i < 8; i++) {
          const uint4 v = src[i * 128];
          af[4 * i] = v.x;
          af[4 * i + 1] = v.y;
          af[4 * i + 2] = v.z;
          af[4 * i + 3] = v.w;
        }
#pragma unroll
        for (int i = 0; i < 32; i++) af[32 + i] = qf[i];
        asm volatile("fence.proxy.async.shared::cta;" ::: "memory");
        release(WQ0);
      }
    }
    TRC(12);
    const int tile = p * 8 + 2 * bp + w;
    uint4* part = g_part + (size_t)(tile * 16 + h) * 36 * 128 + t128;
#pragma unroll
    for (int pn = 0; pn < 3; pn++) {
#pragma unroll
      for (int kc = 0; kc < 4; kc++) {
        const int m = pn * 4 + kc;
        mbar_wait(full0 + (WO0 + m) * 8);
        const uint64_t db = make_desc(sbase + wo_off(m), 8192, 1024);
        wg_fence();
#pragma unroll
        for (int ks = 0; ks < 4; ks++) {
          const int a = (kc * 4 + ks) * 4;
          if ((kc | ks) == 0) wgmma_rs_n192_tb_z(s, o, af[a], af[a + 1], af[a + 2], af[a + 3], db);
          else wgmma_rs_n192_tb(s, o, af[a], af[a + 1], af[a + 2], af[a + 3], db + ks * 128);
        }
        wg_commit();
        if (kc > 0) {
          wg_wait<1>();
          if (m - 1 < 3) release(WO0 + m - 1);
        }
      }
      wg_wait<0>();
      fence_regs(s);
      fence_regs32(o);
      TRC(13 + pn * 2);
#pragma unroll
      for (int i = 0; i < 8; i++) __stcg(part + (pn * 12 + i) * 128, pack8(s, i));
#pragma unroll
      for (int i = 0; i < 4; i++) __stcg(part + (pn * 12 + 8 + i) * 128, pack8(o, i));
      __syncwarp();
      if (lane == 0) mbar_arrive(pub0 + (w * 3 + pn) * 8);
      TRC(14 + pn * 2);
    }
    if (t128 < 96) {
      const int u = h * 96 + t128;
      const int slot = u >> 7, thr = u & 127;
      const int row0 = (thr >> 5) * 16 + ((thr & 31) >> 2);
      __nv_bfloat16* orow = out + (size_t)((2 * bp + w) * 64 + row0) * 1152 + p * 576 + slot * 16 + (thr & 3) * 2;
      const uint4* pr = g_part + (size_t)(tile * 16) * 36 * 128 + slot * 128 + thr;
      uint4 v[3][16];
      auto fetch = [&](int pn) {
        mbar_wait(ready0 + (w * 3 + pn) * 8);
        TRC(19 + pn);
#pragma unroll
        for (int c = 0; c < 16; c++) v[pn][c] = __ldcg(pr + (size_t)(c * 36 + pn * 12) * 128);
      };
      auto finish = [&](int pn) {
        float a[8];
#pragma unroll
        for (int e = 0; e < 8; e++) a[e] = 0.f;
#pragma unroll
        for (int c = 0; c < 16; c++) {
          a[0] += bf_lo(v[pn][c].x);
          a[1] += bf_hi(v[pn][c].x);
          a[2] += bf_lo(v[pn][c].y);
          a[3] += bf_hi(v[pn][c].y);
          a[4] += bf_lo(v[pn][c].z);
          a[5] += bf_hi(v[pn][c].z);
          a[6] += bf_lo(v[pn][c].w);
          a[7] += bf_hi(v[pn][c].w);
        }
        __nv_bfloat16* op = orow + pn * 192;
        *reinterpret_cast<uint32_t*>(op) = pack_bf16(a[0], a[1]);
        *reinterpret_cast<uint32_t*>(op + 8 * 1152) = pack_bf16(a[2], a[3]);
        *reinterpret_cast<uint32_t*>(op + 8) = pack_bf16(a[4], a[5]);
        *reinterpret_cast<uint32_t*>(op + 8 * 1152 + 8) = pack_bf16(a[6], a[7]);
      };
      fetch(0);
      fetch(1);
      finish(0);
      finish(1);
      fetch(2);
      finish(2);
    }
    TRC(22);
  }
}

typedef CUresult (*EncodeFn)(CUtensorMap*, CUtensorMapDataType, cuuint32_t, void*, const cuuint64_t*, const cuuint64_t*,
                             const cuuint32_t*, const cuuint32_t*, CUtensorMapInterleave, CUtensorMapSwizzle,
                             CUtensorMapL2promotion, CUtensorMapFloatOOBfill);

void encode3d(EncodeFn fn, CUtensorMap* m, void* ptr, uint64_t cols, uint64_t rows, uint32_t box_rows, uint32_t box_chunks) {
  cuuint64_t dims[3] = {64, rows, cols / 64};
  cuuint64_t strides[2] = {cols * 2, 128};
  cuuint32_t box[3] = {64, box_rows, box_chunks};
  cuuint32_t es[3] = {1, 1, 1};
  fn(m, CU_TENSOR_MAP_DATA_TYPE_BFLOAT16, 3, ptr, dims, strides, box, es, CU_TENSOR_MAP_INTERLEAVE_NONE,
     CU_TENSOR_MAP_SWIZZLE_128B, CU_TENSOR_MAP_L2_PROMOTION_NONE, CU_TENSOR_MAP_FLOAT_OOB_FILL_NONE);
}

}

extern "C" void kernel_launch(void* const* d_in, const int* in_sizes, int n_in, void* d_out, int out_size) {
  static EncodeFn fn = nullptr;
  if (!fn) {
    void* f = nullptr;
    cudaDriverEntryPointQueryResult st;
    cudaGetDriverEntryPoint("cuTensorMapEncodeTiled", &f, cudaEnableDefault, &st);
    fn = (EncodeFn)f;
    cudaFuncSetAttribute(fused_gqa_kernel, cudaFuncAttributeMaxDynamicSharedMemorySize, SMEM_BYTES);
  }
  Maps maps;
  for (int p = 0; p < 2; p++) {
    encode3d(fn, &maps.x[p], d_in[p * 5 + 0], kD, 512, 128, 1);
    encode3d(fn, &maps.k[p], d_in[p * 5 + 1], kDH, 8 * 16 * kSK, 128, 2);
    encode3d(fn, &maps.v[p], d_in[p * 5 + 2], kDH, 8 * 16 * kSK, 128, 2);
    encode3d(fn, &maps.wq[p], d_in[p * 5 + 3], kHQD, kD, 64, 4);
    encode3d(fn, &maps.wo[p], d_in[p * 5 + 4], kD, kHQD, 64, 3);
    maps.px[p] = (const char*)d_in[p * 5 + 0];
  }
  fused_gqa_kernel<<<128, 384, SMEM_BYTES>>>(maps, (__nv_bfloat16*)d_out);
}
```
